```python
import torch

def _softmax(x, axis=-1):
    return torch.softmax(x, dim=axis)
def _gelu(x):
    return torch.nn.functional.gelu(x, approximate="tanh")
def _silu(x):
    return torch.nn.functional.silu(x)
def _sigmoid(x):
    return torch.sigmoid(x)
def _layernorm(x, axis=-1, eps=1e-5):
    m = x.mean(dim=axis, keepdim=True)
    v = x.var(dim=axis, keepdim=True, unbiased=False)
    return (x - m) / torch.sqrt(v + eps)
def _scatter_add(tgt, idx, src, axis=0):
    return tgt.clone().index_add_(axis, idx, src)
def _segment_sum(src, seg, n):
    out = torch.zeros((n,) + src.shape[1:], dtype=src.dtype)
    return out.index_add_(0, seg, src)
def _pad(x, pw):
    flat = tuple(v for pair in reversed(pw) for v in pair)
    return torch.nn.functional.pad(x, flat)

kernel_name = 'concat_heads__sliding_block_cached__compressed_kv_cla__decode'

def setup_inputs():

    _w = (lambda a: (lambda t: t.to(torch.bfloat16) if t.is_floating_point() else t)(torch.as_tensor(a)))
    def _A_setup():
        B, Sq, D = 4, 1, 512
        Hq, Hkv, Sk, Dh = 32, 32, 4096, 128
        assert Hq % Hkv == 0, (Hq, Hkv)
        return {
            "x": _w((lambda *s: torch.randn(*s, dtype=torch.bfloat16) * 0.8)(B, Sq, D)),
            "k_cache": _w((lambda *s: torch.randn(*s, dtype=torch.bfloat16) * 0.8)(B, Hkv, Sk, Dh)),
            "v_cache": _w((lambda *s: torch.randn(*s, dtype=torch.bfloat16) * 0.05)(B, Hkv, Sk, Dh)),
            "wq": _w((lambda *s: torch.randn(*s, dtype=torch.bfloat16) * 0.8)(D, Hq * Dh) * (D ** -0.5)),
            "wo": _w((lambda *s: torch.randn(*s, dtype=torch.bfloat16) * 0.05)(Hq * Dh, D) * ((Hq * Dh) ** -0.5)),
        }
    _A_in = _A_setup()

    def _B_setup():
        B, H, Sq, Sk, D, M = 4, 32, 1, 4096, 128, 512
        Dc = 4 * D
        return {
            "x": _w((lambda *s: torch.randn(*s, dtype=torch.bfloat16) * 1.6)(B, Sq, M)),
            "c_kv": _w((lambda *s: torch.randn(*s, dtype=torch.bfloat16) * 0.1)(B, Sk, Dc)),
            "w_q": _w((lambda *s: torch.randn(*s, dtype=torch.bfloat16) * 3.2)(M, H, D) * (M ** -0.5)),
            "w_uk": _w((lambda *s: torch.randn(*s, dtype=torch.bfloat16) * 3.2)(Dc, H, D) * (Dc ** -0.5)),
            "w_uv": _w((lambda *s: torch.randn(*s, dtype=torch.bfloat16) * 0.1)(Dc, H, D) * (Dc ** -0.5)),
            "w_o": _w((lambda *s: torch.randn(*s, dtype=torch.bfloat16) * 0.1)(H, D, M) * ((H * D) ** -0.5)),
        }
    _B_in = _B_setup()

    return {
        "A_x": _A_in["x"],
        "A_k_cache": _A_in["k_cache"],
        "A_v_cache": _A_in["v_cache"],
        "A_wq": _A_in["wq"],
        "A_wo": _A_in["wo"],
        "B_x": _B_in["x"],
        "B_c_kv": _B_in["c_kv"],
        "B_w_q": _B_in["w_q"],
        "B_w_uk": _B_in["w_uk"],
        "B_w_uv": _B_in["w_uv"],
        "B_w_o": _B_in["w_o"],
    }

def reference(A_x, A_k_cache, A_v_cache, A_wq, A_wo, B_x, B_c_kv, B_w_q, B_w_uk, B_w_uv, B_w_o):
    def _A_ref(x, k_cache, v_cache, wq, wo):
        B, Sq, D = x.shape
        Hq, Dh = 32, 128
        Hkv, Sk = k_cache.shape[1], k_cache.shape[2]
        W = min(4096, max(256, Sk // 4))
        rep = Hq // Hkv
        q = (lambda x, *d: x.permute(*d))((x @ wq).reshape(B, Sq, Hq, Dh), 0, 2, 1, 3)
        k = (lambda x, n, axis: torch.repeat_interleave(x, n, dim=axis))(k_cache[:, :, Sk - W:, :], rep, axis=1)
        v = (lambda x, n, axis: torch.repeat_interleave(x, n, dim=axis))(v_cache[:, :, Sk - W:, :], rep, axis=1)
        scores = torch.einsum("bhqd,bhkd->bhqk", q, k) * (Dh ** -0.5)
        p = _softmax(scores, axis=-1)
        o = torch.einsum("bhqk,bhkd->bhqd", p, v)
        return (lambda x, *d: x.permute(*d))(o, 0, 2, 1, 3).reshape(B, Sq, Hq * Dh) @ wo

    def _B_ref(x, c_kv, w_q, w_uk, w_uv, w_o):
        B, Sq, M = x.shape[0], x.shape[1], x.shape[2]
        Sk = c_kv.shape[1]
        H, D = w_q.shape[1], w_q.shape[2]
        q = torch.einsum("bqm,mhd->bhqd", x, w_q)
        k = torch.einsum("bkc,chd->bhkd", c_kv, w_uk)
        v = torch.einsum("bkc,chd->bhkd", c_kv, w_uv)
        scores = torch.einsum("bhqd,bhkd->bhqk", q, k) * (D ** -0.5)
        off = Sk - Sq
        qi = torch.arange(Sq)[:, None]
        kj = torch.arange(Sk)[None, :]
        cmask = kj <= (qi + off)
        scores = torch.where(cmask[None, None], scores, -1e9)
        p = _softmax(scores, axis=-1)
        ctx = torch.einsum("bhqk,bhkd->bhqd", p, v)
        return torch.einsum("bhqd,hdm->bqm", ctx, w_o)

    a = _A_ref(A_x, A_k_cache, A_v_cache, A_wq, A_wo)
    b = _B_ref(B_x, B_c_kv, B_w_q, B_w_uk, B_w_uv, B_w_o)
    return torch.concatenate([a, b], axis=-1)
```

```cpp
#include <cuda_runtime.h>
#include <cuda_bf16.h>
#include <cuda.h>
#include <stdint.h>

namespace {

constexpr int NCTA   = 128;
constexpr int NSLOT  = 13;
constexpr int SLOT   = 16384;
constexpr int NITEM  = 56;
constexpr int NTHR   = 320;

constexpr int IT_WQB = 0, IT_WQA = 2, IT_WUK = 4, IT_K0 = 6, IT_Q = 14, IT_C = 16, IT_K1 = 24, IT_V0 = 32,
              IT_OP = 40, IT_WUV = 42, IT_V1 = 44, IT_WOB = 52, IT_WOA = 54;

constexpr int SM_RING  = 0;
constexpr int SM_FULL  = NSLOT * SLOT;
constexpr int SM_EMPTY = SM_FULL + 512;
constexpr int SM_IN0   = SM_EMPTY + 512;
constexpr int SM_IN1   = SM_IN0 + 1088;
constexpr int SM_SC    = SM_IN1 + 1088;
constexpr int SM_PA    = SM_SC + 4096;
constexpr int SM_PF    = SM_PA + 2048;
constexpr int SM_MX    = SM_PF + 8192;
constexpr int SM_ML    = SM_MX + 1024;
constexpr int SM_END   = SM_ML + 128;
constexpr int SM_SUM   = SM_IN0;
static_assert(SM_END <= 232448, "smem");

struct Maps { CUtensorMap wqB, wqA, wuk, wuv, woB, woA, ckv; };

__device__ float    g_part[4][NCTA][512];
__device__ float    g_fin[2][32][4][512];
__device__ uint4    g_q[4][2048];
__device__ uint4    g_op[NCTA][2048];
__device__ float2   g_stat[32][128];
__device__ unsigned g_cnt[2][32];
__device__ unsigned g_epoch[NCTA];
#define TL(i) do {} while (0)

constexpr int SPIN_LIMIT = 1 << 22;

__device__ __forceinline__ uint32_t smem_u32(const void* p) { return (uint32_t)__cvta_generic_to_shared(p); }
__device__ __forceinline__ void mbar_init(uint32_t bar, uint32_t cnt) {
    asm volatile("mbarrier.init.shared::cta.b64 [%0], %1;" ::"r"(bar), "r"(cnt) : "memory");
}
__device__ __forceinline__ void mbar_expect_tx(uint32_t bar, uint32_t bytes) {
    asm volatile("mbarrier.arrive.expect_tx.shared::cta.b64 _, [%0], %1;" ::"r"(bar), "r"(bytes) : "memory");
}
__device__ __forceinline__ void mbar_arrive(uint32_t bar) {
    asm volatile("mbarrier.arrive.shared::cta.b64 _, [%0];" ::"r"(bar) : "memory");
}
__device__ __forceinline__ void mbar_wait(uint32_t bar) {
    uint32_t done;
    int it = 0;
    do {
        asm volatile("{\n.reg .pred p;\nmbarrier.try_wait.parity.shared::cta.b64 p, [%1], 0;\nselp.u32 %0, 1, 0, p;\n}"
                     : "=r"(done) : "r"(bar) : "memory");
        if (++it > SPIN_LIMIT) __trap();
    } while (!done);
}
__device__ __forceinline__ void bulk_load(uint32_t dst, const void* src, uint32_t bytes, uint32_t bar, uint64_t pol) {
    asm volatile("cp.async.bulk.shared::cluster.global.mbarrier::complete_tx::bytes.L2::cache_hint [%0], [%1], %2, [%3], %4;"
                 ::"r"(dst), "l"(src), "r"(bytes), "r"(bar), "l"(pol) : "memory");
}
__device__ __forceinline__ void bulk_load_nohint(uint32_t dst, const void* src, uint32_t bytes, uint32_t bar) {
    asm volatile("cp.async.bulk.shared::cluster.global.mbarrier::complete_tx::bytes [%0], [%1], %2, [%3];"
                 ::"r"(dst), "l"(src), "r"(bytes), "r"(bar) : "memory");
}
__device__ __forceinline__ void tma2d(uint32_t dst, const CUtensorMap* tm, int c0, int c1, uint32_t bar, uint64_t pol) {
    asm volatile("cp.async.bulk.tensor.2d.shared::cluster.global.mbarrier::complete_tx::bytes.L2::cache_hint [%0], [%1, {%3, %4}], [%2], %5;"
                 ::"r"(dst), "l"(tm), "r"(bar), "r"(c0), "r"(c1), "l"(pol) : "memory");
}
__device__ __forceinline__ void tma3d(uint32_t dst, const CUtensorMap* tm, int c0, int c1, int c2, uint32_t bar, uint64_t pol) {
    asm volatile("cp.async.bulk.tensor.3d.shared::cluster.global.mbarrier::complete_tx::bytes.L2::cache_hint [%0], [%1, {%3, %4, %5}], [%2], %6;"
                 ::"r"(dst), "l"(tm), "r"(bar), "r"(c0), "r"(c1), "r"(c2), "l"(pol) : "memory");
}
__device__ __forceinline__ void ldsm4(uint32_t a, uint32_t& r0, uint32_t& r1, uint32_t& r2, uint32_t& r3) {
    asm volatile("ldmatrix.sync.aligned.m8n8.x4.shared.b16 {%0,%1,%2,%3}, [%4];"
                 : "=r"(r0), "=r"(r1), "=r"(r2), "=r"(r3) : "r"(a) : "memory");
}
__device__ __forceinline__ void ldsm4t(uint32_t a, uint32_t& r0, uint32_t& r1, uint32_t& r2, uint32_t& r3) {
    asm volatile("ldmatrix.sync.aligned.m8n8.x4.trans.shared.b16 {%0,%1,%2,%3}, [%4];"
                 : "=r"(r0), "=r"(r1), "=r"(r2), "=r"(r3) : "r"(a) : "memory");
}
__device__ __forceinline__ void mma16816(float (&c)[4], uint32_t a0, uint32_t a1, uint32_t a2, uint32_t a3,
                                         uint32_t b0, uint32_t b1) {
    asm volatile("mma.sync.aligned.m16n8k16.row.col.f32.bf16.bf16.f32 {%0,%1,%2,%3}, {%4,%5,%6,%7}, {%8,%9}, {%0,%1,%2,%3};"
                 : "+f"(c[0]), "+f"(c[1]), "+f"(c[2]), "+f"(c[3])
                 : "r"(a0), "r"(a1), "r"(a2), "r"(a3), "r"(b0), "r"(b1));
}
__device__ __forceinline__ uint32_t lds32(uint32_t a) {
    uint32_t v; asm volatile("ld.shared.b32 %0, [%1];" : "=r"(v) : "r"(a) : "memory"); return v;
}
__device__ __forceinline__ float ldsf(uint32_t a) {
    float v; asm volatile("ld.shared.f32 %0, [%1];" : "=f"(v) : "r"(a) : "memory"); return v;
}
__device__ __forceinline__ float2 ldsf2(uint32_t a) {
    float2 v; asm volatile("ld.shared.v2.f32 {%0,%1}, [%2];" : "=f"(v.x), "=f"(v.y) : "r"(a) : "memory"); return v;
}
__device__ __forceinline__ float4 ldsf4(uint32_t a) {
    float4 v; asm volatile("ld.shared.v4.f32 {%0,%1,%2,%3}, [%4];" : "=f"(v.x), "=f"(v.y), "=f"(v.z), "=f"(v.w) : "r"(a) : "memory"); return v;
}
__device__ __forceinline__ uint4 lds128(uint32_t a) {
    uint4 v; asm volatile("ld.shared.v4.b32 {%0,%1,%2,%3}, [%4];" : "=r"(v.x), "=r"(v.y), "=r"(v.z), "=r"(v.w) : "r"(a) : "memory"); return v;
}
__device__ __forceinline__ void sts16(uint32_t a, uint16_t v) { asm volatile("st.shared.b16 [%0], %1;" ::"r"(a), "h"(v) : "memory"); }
__device__ __forceinline__ void sts32(uint32_t a, uint32_t v) { asm volatile("st.shared.b32 [%0], %1;" ::"r"(a), "r"(v) : "memory"); }
__device__ __forceinline__ void stsf(uint32_t a, float v) { asm volatile("st.shared.f32 [%0], %1;" ::"r"(a), "f"(v) : "memory"); }
__device__ __forceinline__ void sts64(uint32_t a, uint32_t x, uint32_t y) {
    asm volatile("st.shared.v2.b32 [%0], {%1,%2};" ::"r"(a), "r"(x), "r"(y) : "memory");
}
__device__ __forceinline__ void sts128(uint32_t a, uint4 v) {
    asm volatile("st.shared.v4.b32 [%0], {%1,%2,%3,%4};" ::"r"(a), "r"(v.x), "r"(v.y), "r"(v.z), "r"(v.w) : "memory");
}
__device__ __forceinline__ uint32_t pack_bf16(float lo, float hi) {
    uint32_t r; asm("cvt.rn.bf16x2.f32 %0, %1, %2;" : "=r"(r) : "f"(hi), "f"(lo)); return r;
}
__device__ __forceinline__ float bf_lo(uint32_t v) { return __uint_as_float(v << 16); }
__device__ __forceinline__ float bf_hi(uint32_t v) { return __uint_as_float(v & 0xffff0000u); }
__device__ __forceinline__ float ex2(float x) { float y; asm("ex2.approx.ftz.f32 %0, %1;" : "=f"(y) : "f"(x)); return y; }
__device__ __forceinline__ void bar_consumers() { asm volatile("bar.sync 1, 256;" ::: "memory"); }

__device__ __forceinline__ uint32_t tagf(float v, uint32_t tag) { return (__float_as_uint(v) & 0xffffff00u) | tag; }
__device__ __forceinline__ void st_tag2(float* p, float a, float b, uint32_t tag) {
    asm volatile("st.relaxed.gpu.global.v2.b32 [%0], {%1,%2};" ::"l"(p), "r"(tagf(a, tag)), "r"(tagf(b, tag)) : "memory");
}
__device__ __forceinline__ uint2 ld_rlx2(const float* p) {
    uint2 v; asm volatile("ld.relaxed.gpu.global.v2.b32 {%0,%1}, [%2];" : "=r"(v.x), "=r"(v.y) : "l"(p) : "memory"); return v;
}
__device__ __forceinline__ uint4 ld_rlx4(const float* p) {
    uint4 v; asm volatile("ld.relaxed.gpu.global.v4.b32 {%0,%1,%2,%3}, [%4];" : "=r"(v.x), "=r"(v.y), "=r"(v.z), "=r"(v.w) : "l"(p) : "memory"); return v;
}
__device__ __forceinline__ float untag(uint32_t v) { return __uint_as_float(v & 0xffffff00u); }

__device__ __forceinline__ uint32_t slot_off(int item) { return (uint32_t)(item % NSLOT) * SLOT; }

template <bool TRANS>
__device__ __forceinline__ void tile_mma(uint32_t sb, int item, uint32_t in, int w, int lane, float (&acc)[2][4]) {
    const int g = lane >> 2, t = lane & 3;
#pragma unroll
    for (int i = 0; i < 4; i++) { acc[0][i] = 0.f; acc[1][i] = 0.f; }
    uint32_t a[16];
    const uint32_t ia = in + (g & 3) * 272 + t * 4;
#pragma unroll
    for (int i = 0; i < 16; i++) a[i] = lds32(ia + i * 16);
    const uint32_t s0 = sb + slot_off(item), s1 = sb + slot_off(item + 1);
    if (TRANS) {
        mbar_wait(sb + SM_FULL + (item + (w >> 2)) * 8);
        const int r = (lane & 7) + (lane & 8);
        const int ch = 2 * (w & 3) + (lane >> 4);
        const uint32_t base = ((w >> 2) ? s1 : s0) + r * 128 + ((ch ^ (lane & 7)) << 4);
#pragma unroll
        for (int kk = 0; kk < 8; kk++) {
            uint32_t r0, r1, r2, r3;
            ldsm4t(base + kk * 2048, r0, r1, r2, r3);
            mma16816(acc[0], a[2 * kk], 0u, a[2 * kk + 1], 0u, r0, r1);
            mma16816(acc[1], a[2 * kk], 0u, a[2 * kk + 1], 0u, r2, r3);
        }
    } else {
        mbar_wait(sb + SM_FULL + item * 8);
        mbar_wait(sb + SM_FULL + (item + 1) * 8);
        const int r = 16 * w + (lane & 7) + ((lane >> 4) << 3);
        const uint32_t off = r * 128 + ((((lane >> 3) & 1) ^ (lane & 7)) << 4);
#pragma unroll
        for (int kk = 0; kk < 8; kk++) {
            uint32_t r0, r1, r2, r3;
            ldsm4(((kk >> 2) ? s1 : s0) + (off ^ ((kk & 3) << 5)), r0, r1, r2, r3);
            mma16816(acc[0], a[2 * kk], 0u, a[2 * kk + 1], 0u, r0, r1);
            mma16816(acc[1], a[2 * kk], 0u, a[2 * kk + 1], 0u, r2, r3);
        }
    }
    __syncwarp();
    if (lane == 0) {
        mbar_arrive(sb + SM_EMPTY + item * 8);
        mbar_arrive(sb + SM_EMPTY + (item + 1) * 8);
    }
}

__device__ __forceinline__ void publish(float* dst, int pitch, int w, int lane, const float (&acc)[2][4], uint32_t tag) {
    if (lane < 16) {
        float* p = dst + (lane >> 2) * pitch + 16 * w + 2 * (lane & 3);
        st_tag2(p, acc[0][0], acc[0][1], tag);
        st_tag2(p + 8, acc[1][0], acc[1][1], tag);
    }
}

__device__ __forceinline__ void gather(const float* part, uint32_t in, int tid, uint32_t tag) {
    const float* p = part + tid * 2;
    uint2 v0, v1, v2, v3;
    int it = 0;
    while (true) {
        v0 = ld_rlx2(p); v1 = ld_rlx2(p + 512); v2 = ld_rlx2(p + 1024); v3 = ld_rlx2(p + 1536);
        uint32_t bad = ((v0.x ^ tag) | (v0.y ^ tag) | (v1.x ^ tag) | (v1.y ^ tag) |
                        (v2.x ^ tag) | (v2.y ^ tag) | (v3.x ^ tag) | (v3.y ^ tag)) & 0xffu;
        if (bad == 0) break;
        if (++it > SPIN_LIMIT) __trap();
        __nanosleep(100);
    }
    float x = (untag(v0.x) + untag(v1.x)) + (untag(v2.x) + untag(v3.x));
    float y = (untag(v0.y) + untag(v1.y)) + (untag(v2.y) + untag(v3.y));
    sts32(in + (tid >> 6) * 272 + (tid & 63) * 4, pack_bf16(x, y));
    bar_consumers();
}

__device__ __forceinline__ void wait_counter(const unsigned* cnt, unsigned target) {
    int it = 0;
    while (true) {
        unsigned v;
        asm volatile("ld.acquire.gpu.global.u32 %0, [%1];" : "=r"(v) : "l"(cnt) : "memory");
        if ((int)(v - target) >= 0) break;
        if (++it > SPIN_LIMIT) __trap();
        __nanosleep(100);
    }
    asm volatile("fence.proxy.async;" ::: "memory");
}
__device__ __forceinline__ void signal_counter(unsigned* cnt) {
    asm volatile("red.release.gpu.global.add.u32 [%0], 1;" ::"l"(cnt) : "memory");
}

__global__ void __launch_bounds__(NTHR, 1)
fused_decode_kernel(const __grid_constant__ Maps maps,
                    const __nv_bfloat16* __restrict__ xA, const __nv_bfloat16* __restrict__ xB,
                    const __nv_bfloat16* __restrict__ Kc, const __nv_bfloat16* __restrict__ Vc,
                    __nv_bfloat16* __restrict__ out) {
    extern __shared__ __align__(1024) unsigned char smem_raw[];
    const uint32_t sb = smem_u32(smem_raw);
    const int tid = threadIdx.x, w = tid >> 5, lane = tid & 31;
    const int cta = blockIdx.x, h = cta >> 2, j = cta & 3;
    const size_t kv_off = ((size_t)(j * 32 + h) * 4096 + 3072) * 128;

    if (w == 8) {
        if (lane == 0) {
            TL(0);
            asm volatile("cp.async.bulk.prefetch.L2.global [%0], %1;" ::"l"(Kc + kv_off), "r"(SLOT) : "memory");
        }
        if (lane < 7) asm volatile("prefetch.tensormap [%0];" ::"l"((const char*)&maps + lane * sizeof(CUtensorMap)) : "memory");
        for (int i = lane; i < NITEM; i += 32) {
            const bool single = (i >= IT_K0 && i < IT_Q) || (i >= IT_K1 && i < IT_OP) || (i >= IT_V1 && i < IT_WOB);
            mbar_init(sb + SM_FULL + i * 8, 1);
            mbar_init(sb + SM_EMPTY + i * 8, single ? 1 : 8);
        }
        asm volatile("fence.mbarrier_init.release.cluster;" ::: "memory");
        asm volatile("fence.proxy.async.shared::cta;" ::: "memory");
        __syncwarp();
        asm volatile("bar.arrive 2, 320;" ::: "memory");
        if (lane == 0) {
            uint64_t pol;
            asm volatile("createpolicy.fractional.L2::evict_first.b64 %0, 1.0;" : "=l"(pol));
            int slot = 0;
#pragma unroll 1
            for (int i = 0; i < NITEM; i++) {
                const uint32_t dst = sb + slot * SLOT, bar = sb + SM_FULL + i * 8;
                if (++slot == NSLOT) slot = 0;
                if ((i & ~1) == IT_Q || (i & ~1) == IT_OP) continue;
                if (i >= NSLOT) mbar_wait(sb + SM_EMPTY + (i - NSLOT) * 8);
                mbar_expect_tx(bar, SLOT);
                if (i < IT_K0 || (i & ~1) == IT_WUV) {
                    const CUtensorMap* tm = &maps.wqB + (i < IT_K0 ? (i >> 1) : 3);
                    tma2d(dst, tm, h * 128 + (i & 1) * 64, j * 128, bar, pol);
                } else if (i >= IT_WOB) {
                    const CUtensorMap* tm = &maps.woB + ((i - IT_WOB) >> 1);
                    tma2d(dst, tm, j * 128 + (i & 1) * 64, h * 128, bar, pol);
                } else if (i >= IT_C && i < IT_K1) {
                    tma3d(dst, &maps.ckv, 0, cta * 128 + (i - IT_C) * 16, 0, bar, pol);
                } else {
                    const __nv_bfloat16* src = (i < IT_V0 ? Kc : Vc) + kv_off;
                    const int c = i < IT_Q ? i - IT_K0 : i < IT_V0 ? i - IT_K1 + 8 : i < IT_OP ? i - IT_V0 : i - IT_V1 + 8;
                    bulk_load(dst, src + (size_t)c * (SLOT / 2), SLOT, bar, pol);
                }
            }
            TL(1);
        }
        return;
    }

    const unsigned epoch = g_epoch[cta] + 1;
    const uint32_t tag = epoch & 0xffu;

    if (w == 9) {
        asm volatile("bar.sync 2, 320;" ::: "memory");
        if (lane == 0) {
            mbar_wait(sb + SM_EMPTY + (IT_Q - NSLOT) * 8);
            mbar_wait(sb + SM_EMPTY + (IT_Q + 1 - NSLOT) * 8);
            wait_counter(&g_cnt[0][0], epoch * NCTA);
            TL(2);
            const uint4* q = g_q[cta >> 5];
            mbar_expect_tx(sb + SM_FULL + IT_Q * 8, SLOT);
            bulk_load_nohint(sb + slot_off(IT_Q), q, SLOT, sb + SM_FULL + IT_Q * 8);
            mbar_expect_tx(sb + SM_FULL + (IT_Q + 1) * 8, SLOT);
            bulk_load_nohint(sb + slot_off(IT_Q + 1), q + 1024, SLOT, sb + SM_FULL + (IT_Q + 1) * 8);

            mbar_wait(sb + SM_EMPTY + (IT_OP - NSLOT) * 8);
            mbar_wait(sb + SM_EMPTY + (IT_OP + 1 - NSLOT) * 8);
            wait_counter(&g_cnt[1][0], epoch * NCTA);
            TL(3);
            const uint4* op = g_op[cta];
            mbar_expect_tx(sb + SM_FULL + IT_OP * 8, SLOT + 1024);
            bulk_load_nohint(sb + SM_MX, g_stat[h], 1024, sb + SM_FULL + IT_OP * 8);
            bulk_load_nohint(sb + slot_off(IT_OP), op, SLOT, sb + SM_FULL + IT_OP * 8);
            mbar_expect_tx(sb + SM_FULL + (IT_OP + 1) * 8, SLOT);
            bulk_load_nohint(sb + slot_off(IT_OP + 1), op + 1024, SLOT, sb + SM_FULL + (IT_OP + 1) * 8);
        }
        __syncwarp();
        const int b = cta >> 5, col0 = 16 * (cta & 31) + 4 * (lane & 3);
#pragma unroll 1
        for (int part = 0; part < 2; part++) {
            mbar_wait(sb + SM_FULL + (IT_WOB + 1 + 2 * part) * 8);
            const float* p = &g_fin[part][lane >> 2][b][col0];
            uint4 v0, v1, v2, v3;
            int it = 0;
            while (true) {
                v0 = ld_rlx4(p); v1 = ld_rlx4(p + 8 * 2048); v2 = ld_rlx4(p + 16 * 2048); v3 = ld_rlx4(p + 24 * 2048);
                uint32_t bad = ((v0.x ^ tag) | (v0.y ^ tag) | (v0.z ^ tag) | (v0.w ^ tag) |
                                (v1.x ^ tag) | (v1.y ^ tag) | (v1.z ^ tag) | (v1.w ^ tag) |
                                (v2.x ^ tag) | (v2.y ^ tag) | (v2.z ^ tag) | (v2.w ^ tag) |
                                (v3.x ^ tag) | (v3.y ^ tag) | (v3.z ^ tag) | (v3.w ^ tag)) & 0xffu;
                if (bad == 0) break;
                if (++it > SPIN_LIMIT) __trap();
            }
            float s0 = (untag(v0.x) + untag(v1.x)) + (untag(v2.x) + untag(v3.x));
            float s1 = (untag(v0.y) + untag(v1.y)) + (untag(v2.y) + untag(v3.y));
            float s2 = (untag(v0.z) + untag(v1.z)) + (untag(v2.z) + untag(v3.z));
            float s3 = (untag(v0.w) + untag(v1.w)) + (untag(v2.w) + untag(v3.w));
#pragma unroll
            for (int m = 4; m < 32; m <<= 1) {
                s0 += __shfl_xor_sync(0xffffffffu, s0, m);
                s1 += __shfl_xor_sync(0xffffffffu, s1, m);
                s2 += __shfl_xor_sync(0xffffffffu, s2, m);
                s3 += __shfl_xor_sync(0xffffffffu, s3, m);
            }
            if (lane < 4)
                *reinterpret_cast<uint2*>(out + b * 1024 + (part == 0 ? 512 : 0) + col0) =
                    make_uint2(pack_bf16(s0, s1), pack_bf16(s2, s3));
            if (lane == 0) TL(4 + part);
        }
        if (lane == 0) g_epoch[cta] = epoch;
        return;
    }

    const int g = lane >> 2, t = lane & 3;
    const uint32_t in0 = sb + SM_IN0, in1 = sb + SM_IN1;
    if (tid < 128) {
        const __nv_bfloat16* x = (tid < 64 ? xB : xA) + ((tid >> 4) & 3) * 512 + j * 128 + (tid & 15) * 8;
        const uint4 v = __ldg(reinterpret_cast<const uint4*>(x));
        sts128((tid < 64 ? in0 : in1) + ((tid >> 4) & 3) * 272 + (tid & 15) * 16, v);
    }
    asm volatile("bar.sync 2, 320;" ::: "memory");

    float acc[2][4];
    tile_mma<true>(sb, IT_WQB, in0, w, lane, acc);
    publish(g_part[0][cta], 128, w, lane, acc, tag);
    if (tid == 0) TL(6);
    tile_mma<true>(sb, IT_WQA, in1, w, lane, acc);
    publish(g_part[1][cta], 128, w, lane, acc, tag);
    if (tid == 0) TL(7);
    bar_consumers();

    const float SC = 0.08838834764831845f * 1.4426950408889634f;
    gather(g_part[0][h * 4], in0, tid, tag);
    if (tid == 0) TL(8);
    tile_mma<false>(sb, IT_WUK, in0, w, lane, acc);
    if (lane < 16) {
        uint32_t* q = reinterpret_cast<uint32_t*>(g_q[g]) + (2 * j + (w >> 2)) * 1024 + h * 32 + t;
        const int ch = 2 * (w & 3);
        q[((ch) ^ (h & 7)) * 4]     = pack_bf16(acc[0][0] * SC, acc[0][1] * SC);
        q[((ch + 1) ^ (h & 7)) * 4] = pack_bf16(acc[1][0] * SC, acc[1][1] * SC);
        asm volatile("fence.proxy.async;" ::: "memory");
    }
    gather(g_part[1][h * 4], in1, tid, tag);
    if (tid == 0) { signal_counter(&g_cnt[0][0]); TL(9); }

    uint32_t qf[16];
#pragma unroll
    for (int c = 0; c < 8; c++) {
        qf[2 * c]     = lds32(in1 + j * 272 + ((c ^ g) << 4) + t * 4);
        qf[2 * c + 1] = lds32(in1 + j * 272 + 128 + ((c ^ g) << 4) + t * 4);
    }
    const uint32_t sc_w = sb + SM_SC + w * 512;
    auto k_item = [&](int item, uint32_t sc) {
        mbar_wait(sb + SM_FULL + item * 8);
        const uint32_t base = sb + slot_off(item) + ((lane & 7) + (lane & 8)) * 256 + ((lane >> 4) << 7);
        float s[4][4];
#pragma unroll
        for (int T = 0; T < 4; T++) { s[T][0] = s[T][1] = s[T][2] = s[T][3] = 0.f; }
#pragma unroll
        for (int c = 0; c < 8; c++) {
            const uint32_t a = base + ((c ^ (lane & 7)) << 4);
#pragma unroll
            for (int T = 0; T < 4; T++) {
                uint32_t r0, r1, r2, r3;
                ldsm4(a + T * 4096, r0, r1, r2, r3);
                mma16816(s[T], r0, r1, r2, r3, qf[2 * c], qf[2 * c + 1]);
            }
        }
        __syncwarp();
        if (lane == 0) mbar_arrive(sb + SM_EMPTY + item * 8);
        if (t == (g >> 1)) {
#pragma unroll
            for (int T = 0; T < 4; T++) {
                stsf(sc + (16 * T + g) * 4,     (g & 1) ? s[T][1] : s[T][0]);
                stsf(sc + (16 * T + g + 8) * 4, (g & 1) ? s[T][3] : s[T][2]);
            }
        }
    };
    k_item(IT_K0 + w, sc_w);
    if (tid == 224) TL(10);

    {
        float s[2][2][4];
#pragma unroll
        for (int i = 0; i < 16; i++) (&s[0][0][0])[i] = 0.f;
        mbar_wait(sb + SM_FULL + IT_Q * 8);
        mbar_wait(sb + SM_FULL + (IT_Q + 1) * 8);
        mbar_wait(sb + SM_FULL + (IT_C + w) * 8);
        const uint32_t cb0 = sb + slot_off(IT_C + w) + ((lane & 7) + ((lane >> 4) << 3)) * 128;
        const uint32_t cx = (((lane >> 3) & 1) ^ (lane & 7)) << 4;
        const uint32_t qr = ((lane & 7) + (lane & 8)) * 128;
        const uint32_t qx = ((lane >> 4) ^ (lane & 7)) << 4;
#pragma unroll
        for (int cb = 0; cb < 8; cb++) {
            const uint32_t qb = sb + slot_off(IT_Q + (cb >> 2)) + (cb & 3) * 4096 + qr;
#pragma unroll
            for (int k4 = 0; k4 < 4; k4++) {
                uint32_t b0, b1, b2, b3, a0, a1, a2, a3;
                ldsm4(cb0 + cb * 2048 + (cx ^ (k4 << 5)), b0, b1, b2, b3);
                ldsm4(qb + (qx ^ (k4 << 5)), a0, a1, a2, a3);
                mma16816(s[0][0], a0, a1, a2, a3, b0, b1);
                mma16816(s[0][1], a0, a1, a2, a3, b2, b3);
                ldsm4(qb + 2048 + (qx ^ (k4 << 5)), a0, a1, a2, a3);
                mma16816(s[1][0], a0, a1, a2, a3, b0, b1);
                mma16816(s[1][1], a0, a1, a2, a3, b2, b3);
            }
        }
        __syncwarp();
        if (lane == 0) { mbar_arrive(sb + SM_EMPTY + IT_Q * 8); mbar_arrive(sb + SM_EMPTY + (IT_Q + 1) * 8); }
#pragma unroll
        for (int r = 0; r < 4; r++) {
            const int mt = r >> 1, hi = (r & 1) * 2;
            float m = fmaxf(fmaxf(s[mt][0][hi], s[mt][0][hi + 1]), fmaxf(s[mt][1][hi], s[mt][1][hi + 1]));
            m = fmaxf(m, __shfl_xor_sync(0xffffffffu, m, 1));
            m = fmaxf(m, __shfl_xor_sync(0xffffffffu, m, 2));
            if (t == 0) stsf(sb + SM_MX + (8 * r + g) * 32 + w * 4, m);
        }
        bar_consumers();
        if (tid == 0) TL(11);
        uint32_t pf[2][4];
#pragma unroll
        for (int r = 0; r < 4; r++) {
            const int mt = r >> 1, hi = r & 1;
            const float4 m0 = ldsf4(sb + SM_MX + (8 * r + g) * 32), m1 = ldsf4(sb + SM_MX + (8 * r + g) * 32 + 16);
            const float m = fmaxf(fmaxf(fmaxf(m0.x, m0.y), fmaxf(m0.z, m0.w)), fmaxf(fmaxf(m1.x, m1.y), fmaxf(m1.z, m1.w)));
            const uint32_t p0 = pack_bf16(ex2(s[mt][0][2 * hi] - m), ex2(s[mt][0][2 * hi + 1] - m));
            const uint32_t p1 = pack_bf16(ex2(s[mt][1][2 * hi] - m), ex2(s[mt][1][2 * hi + 1] - m));
            pf[mt][hi] = p0; pf[mt][2 + hi] = p1;
            float l = (bf_lo(p0) + bf_hi(p0)) + (bf_lo(p1) + bf_hi(p1));
            l += __shfl_xor_sync(0xffffffffu, l, 1);
            l += __shfl_xor_sync(0xffffffffu, l, 2);
            if (t == 0) stsf(sb + SM_SUM + (8 * r + g) * 32 + w * 4, l);
        }
        sts128(sb + SM_PF + (w * 2 + 0) * 512 + lane * 16, make_uint4(pf[0][0], pf[0][1], pf[0][2], pf[0][3]));
        sts128(sb + SM_PF + (w * 2 + 1) * 512 + lane * 16, make_uint4(pf[1][0], pf[1][1], pf[1][2], pf[1][3]));
        bar_consumers();
        if (w == 0) {
            const float4 m0 = ldsf4(sb + SM_MX + lane * 32), m1 = ldsf4(sb + SM_MX + lane * 32 + 16);
            const float4 l0 = ldsf4(sb + SM_SUM + lane * 32), l1 = ldsf4(sb + SM_SUM + lane * 32 + 16);
            const float m = fmaxf(fmaxf(fmaxf(m0.x, m0.y), fmaxf(m0.z, m0.w)), fmaxf(fmaxf(m1.x, m1.y), fmaxf(m1.z, m1.w)));
            const float l = ((l0.x + l0.y) + (l0.z + l0.w)) + ((l1.x + l1.y) + (l1.z + l1.w));
            g_stat[lane][cta] = make_float2(m, l);
        }
        float o[2][8][4];
#pragma unroll
        for (int i = 0; i < 64; i++) (&o[0][0][0])[i] = 0.f;
        const uint32_t vr = w * 2048 + ((lane & 7) + (lane & 8)) * 128;
        const uint32_t vx = ((lane >> 4) ^ (lane & 7)) << 4;
#pragma unroll
        for (int ks = 0; ks < 8; ks++) {
            const uint4 p0 = lds128(sb + SM_PF + (ks * 2 + 0) * 512 + lane * 16);
            const uint4 p1 = lds128(sb + SM_PF + (ks * 2 + 1) * 512 + lane * 16);
            const uint32_t vb = sb + slot_off(IT_C + ks) + vr;
#pragma unroll
            for (int n2 = 0; n2 < 4; n2++) {
                uint32_t b0, b1, b2, b3;
                ldsm4t(vb + (vx ^ (n2 << 5)), b0, b1, b2, b3);
                mma16816(o[0][2 * n2],     p0.x, p0.y, p0.z, p0.w, b0, b1);
                mma16816(o[0][2 * n2 + 1], p0.x, p0.y, p0.z, p0.w, b2, b3);
                mma16816(o[1][2 * n2],     p1.x, p1.y, p1.z, p1.w, b0, b1);
                mma16816(o[1][2 * n2 + 1], p1.x, p1.y, p1.z, p1.w, b2, b3);
            }
            __syncwarp();
            if (lane == 0) mbar_arrive(sb + SM_EMPTY + (IT_C + ks) * 8);
        }
        if (tid == 0) TL(12);
#pragma unroll
        for (int r = 0; r < 4; r++) {
            const int mt = r >> 1, hi = (r & 1) * 2;
            uint4* dst = g_op[(8 * r + g) * 4 + (w >> 1)] + (w & 1) * 1024 + cta * 8;
#pragma unroll
            for (int u = 0; u < 2; u++) {
                uint4 v;
                v.x = pack_bf16(o[mt][4 * u][hi],     o[mt][4 * u][hi + 1]);
                v.y = pack_bf16(o[mt][4 * u + 1][hi], o[mt][4 * u + 1][hi + 1]);
                v.z = pack_bf16(o[mt][4 * u + 2][hi], o[mt][4 * u + 2][hi + 1]);
                v.w = pack_bf16(o[mt][4 * u + 3][hi], o[mt][4 * u + 3][hi + 1]);
                dst[(t + 4 * u) ^ (cta & 7)] = v;
            }
        }
        asm volatile("fence.proxy.async;" ::: "memory");
        bar_consumers();
        if (tid == 0) { signal_counter(&g_cnt[1][0]); TL(13); }
    }

    k_item(IT_K1 + w, sc_w + 256);
    __syncwarp();
    float mA, lA;
    {
        const float4 s = ldsf4(sc_w + lane * 16);
        float m = fmaxf(fmaxf(s.x, s.y), fmaxf(s.z, s.w));
#pragma unroll
        for (int d = 1; d < 32; d <<= 1) m = fmaxf(m, __shfl_xor_sync(0xffffffffu, m, d));
        mA = m * SC;
        const uint32_t p0 = pack_bf16(ex2(fmaf(s.x, SC, -mA)), ex2(fmaf(s.y, SC, -mA)));
        const uint32_t p1 = pack_bf16(ex2(fmaf(s.z, SC, -mA)), ex2(fmaf(s.w, SC, -mA)));
        float l = (bf_lo(p0) + bf_hi(p0)) + (bf_lo(p1) + bf_hi(p1));
#pragma unroll
        for (int d = 1; d < 32; d <<= 1) l += __shfl_xor_sync(0xffffffffu, l, d);
        lA = l;
        sts64(sb + SM_PA + w * 256 + lane * 8, p0, p1);
        __syncwarp();
    }
    if (tid == 224) TL(14);

    float oa[4][4];
#pragma unroll
    for (int i = 0; i < 16; i++) (&oa[0][0])[i] = 0.f;
    auto v_item = [&](int item, uint32_t pa) {
        uint32_t p[8];
#pragma unroll
        for (int i = 0; i < 8; i++) p[i] = lds32(pa + i * 16 + t * 4);
        mbar_wait(sb + SM_FULL + item * 8);
        const uint32_t base = sb + slot_off(item) + ((lane & 7) + ((lane >> 4) << 3)) * 256 + ((lane & 8) << 4);
#pragma unroll
        for (int c = 0; c < 8; c++) {
            const uint32_t a = base + ((c ^ (lane & 7)) << 4);
            const uint32_t mask = ((c == (g ^ (2 * t))) ? 0x0000ffffu : 0u) | ((c == (g ^ (2 * t + 1))) ? 0xffff0000u : 0u);
#pragma unroll
            for (int T = 0; T < 4; T++) {
                uint32_t r0, r1, r2, r3;
                ldsm4t(a + T * 4096, r0, r1, r2, r3);
                mma16816(oa[T], r0, r1, r2, r3, p[2 * T] & mask, p[2 * T + 1] & mask);
            }
        }
        __syncwarp();
        if (lane == 0) mbar_arrive(sb + SM_EMPTY + item * 8);
    };
    v_item(IT_V0 + w, sb + SM_PA + w * 256);
    if (tid == 224) TL(15);

    mbar_wait(sb + SM_FULL + IT_OP * 8);
    if (w < 4) {
        const float2 st = ldsf2(sb + SM_MX + tid * 8);
        float m = st.x;
#pragma unroll
        for (int d = 1; d < 32; d <<= 1) m = fmaxf(m, __shfl_xor_sync(0xffffffffu, m, d));
        const uint32_t wb = pack_bf16(ex2(st.x - m), 0.f);
        float l = bf_lo(wb) * st.y;
#pragma unroll
        for (int d = 1; d < 32; d <<= 1) l += __shfl_xor_sync(0xffffffffu, l, d);
#pragma unroll
        for (int bb = 0; bb < 4; bb++) sts16(in0 + bb * 272 + tid * 2, bb == w ? (uint16_t)wb : (uint16_t)0);
        if (lane == 0) stsf(sb + SM_ML + 64 + w * 4, 1.f / l);
    }
    bar_consumers();
    tile_mma<true>(sb, IT_OP, in0, w, lane, acc);
    if (lane < 16) {
        const float inv = ldsf(sb + SM_ML + 64 + g * 4);
        const int ch = 2 * (w & 3);
        const uint32_t dst = in1 + g * 272 + ((w >> 2) * 64 + 8 * (4 * (ch >> 2) + t)) * 2;
        sts32(dst + (ch & 3) * 4,       pack_bf16(acc[0][0] * inv, acc[0][1] * inv));
        sts32(dst + ((ch + 1) & 3) * 4, pack_bf16(acc[1][0] * inv, acc[1][1] * inv));
    }
    bar_consumers();
    tile_mma<true>(sb, IT_WUV, in1, w, lane, acc);
    publish(g_part[2][cta], 128, w, lane, acc, tag);
    if (tid == 0) TL(16);

    v_item(IT_V1 + w, sb + SM_PA + w * 256 + 128);
    {
        const uint32_t so = sb + SM_PF + w * 512 + (16 * t + g) * 4;
        stsf(so,       (oa[0][0] + oa[1][0]) + (oa[2][0] + oa[3][0]));
        stsf(so + 32,  (oa[0][1] + oa[1][1]) + (oa[2][1] + oa[3][1]));
        stsf(so + 256, (oa[0][2] + oa[1][2]) + (oa[2][2] + oa[3][2]));
        stsf(so + 288, (oa[0][3] + oa[1][3]) + (oa[2][3] + oa[3][3]));
        if (lane == 0) { stsf(sb + SM_ML + w * 4, mA); stsf(sb + SM_ML + 32 + w * 4, lA); }
        bar_consumers();
        float x = 0.f, y = 0.f;
        if ((tid >> 6) == j) {
            const float4 m0 = ldsf4(sb + SM_ML), m1 = ldsf4(sb + SM_ML + 16);
            const float m = fmaxf(fmaxf(fmaxf(m0.x, m0.y), fmaxf(m0.z, m0.w)), fmaxf(fmaxf(m1.x, m1.y), fmaxf(m1.z, m1.w)));
            float l = 0.f;
#pragma unroll
            for (int i = 0; i < 8; i++) {
                const float f = ex2(ldsf(sb + SM_ML + i * 4) - m);
                l = fmaf(f, ldsf(sb + SM_ML + 32 + i * 4), l);
                const float2 v = ldsf2(sb + SM_PF + i * 512 + (tid & 63) * 8);
                x = fmaf(f, v.x, x); y = fmaf(f, v.y, y);
            }
            const float inv = 1.f / l;
            x *= inv; y *= inv;
        }
        st_tag2(g_part[3][cta] + tid * 2, x, y, tag);
    }
    if (tid == 0) TL(17);

#pragma unroll 1
    for (int part = 0; part < 2; part++) {
        const uint32_t in = part ? in1 : in0;
        gather(g_part[2 + part][h * 4], in, tid, tag);
        if (tid == 0) TL(18 + 2 * part);
        tile_mma<true>(sb, IT_WOB + 2 * part, in, w, lane, acc);
        publish(&g_fin[part][h][0][j * 128], 512, w, lane, acc, tag);
        if (tid == 224) TL(19 + 2 * part);
    }
}

typedef CUresult (*EncodeTiledFn)(CUtensorMap*, CUtensorMapDataType, cuuint32_t, void*, const cuuint64_t*,
                                  const cuuint64_t*, const cuuint32_t*, const cuuint32_t*, CUtensorMapInterleave,
                                  CUtensorMapSwizzle, CUtensorMapL2promotion, CUtensorMapFloatOOBfill);

void encode_weight(EncodeTiledFn enc, CUtensorMap* tm, const void* p, cuuint64_t cols, cuuint64_t rows) {
    cuuint64_t dims[2] = {cols, rows};
    cuuint64_t strides[1] = {cols * 2};
    cuuint32_t box[2] = {64, 128};
    cuuint32_t es[2] = {1, 1};
    enc(tm, CU_TENSOR_MAP_DATA_TYPE_BFLOAT16, 2, const_cast<void*>(p), dims, strides, box, es,
        CU_TENSOR_MAP_INTERLEAVE_NONE, CU_TENSOR_MAP_SWIZZLE_128B, CU_TENSOR_MAP_L2_PROMOTION_L2_256B,
        CU_TENSOR_MAP_FLOAT_OOB_FILL_NONE);
}

}

extern "C" void kernel_launch(void* const* d_in, const int* in_sizes, int n_in, void* d_out, int out_size) {
    (void)in_sizes; (void)n_in; (void)out_size;
    static EncodeTiledFn enc = nullptr;
    if (!enc) {
        void* fn = nullptr;
        cudaDriverEntryPointQueryResult qr;
        cudaGetDriverEntryPoint("cuTensorMapEncodeTiled", &fn, cudaEnableDefault, &qr);
        enc = (EncodeTiledFn)fn;
        cudaFuncSetAttribute(fused_decode_kernel, cudaFuncAttributeMaxDynamicSharedMemorySize, SM_END);
    }
    Maps maps;
    encode_weight(enc, &maps.wqB, d_in[7], 4096, 512);
    encode_weight(enc, &maps.wqA, d_in[3], 4096, 512);
    encode_weight(enc, &maps.wuk, d_in[8], 4096, 512);
    encode_weight(enc, &maps.wuv, d_in[9], 4096, 512);
    encode_weight(enc, &maps.woB, d_in[10], 512, 4096);
    encode_weight(enc, &maps.woA, d_in[4], 512, 4096);
    {
        cuuint64_t dims[3] = {64, 16384, 8};
        cuuint64_t strides[2] = {1024, 128};
        cuuint32_t box[3] = {64, 16, 8};
        cuuint32_t es[3] = {1, 1, 1};
        enc(&maps.ckv, CU_TENSOR_MAP_DATA_TYPE_BFLOAT16, 3, d_in[6], dims, strides, box, es,
            CU_TENSOR_MAP_INTERLEAVE_NONE, CU_TENSOR_MAP_SWIZZLE_128B, CU_TENSOR_MAP_L2_PROMOTION_L2_256B,
            CU_TENSOR_MAP_FLOAT_OOB_FILL_NONE);
    }
    fused_decode_kernel<<<NCTA, NTHR, SM_END>>>(maps, (const __nv_bfloat16*)d_in[0], (const __nv_bfloat16*)d_in[5],
                                                (const __nv_bfloat16*)d_in[1], (const __nv_bfloat16*)d_in[2],
                                                (__nv_bfloat16*)d_out);
}
```

```cpp
#include <cuda_runtime.h>
#include <cuda_bf16.h>
#include <cuda.h>
#include <stdint.h>

namespace {

constexpr int NCTA   = 128;
constexpr int NSLOT  = 13;
constexpr int SLOT   = 16384;
constexpr int NITEM  = 56;
#define INFLIGHT 4
#define PACE 650
#define OFFS 0
#define STAG 0
constexpr int NTHR   = 320;
#define BAR2 "bar.sync 2, 320;"

constexpr int IT_WQB = 0, IT_WQA = 2, IT_WUK = 4, IT_K0 = 6, IT_Q = 14, IT_C = 16, IT_K1 = 24, IT_V0 = 32,
              IT_OP = 40, IT_WUV = 42, IT_V1 = 44, IT_WOB = 52, IT_WOA = 54;

constexpr int SM_FULL  = NSLOT * SLOT;
constexpr int SM_EMPTY = SM_FULL + 512;
constexpr int SM_IN0   = SM_EMPTY + 512;
constexpr int SM_IN1   = SM_IN0 + 1088;
constexpr int SM_SC    = SM_IN1 + 1088;
constexpr int SM_PA    = SM_SC + 4096;
constexpr int SM_PF    = SM_PA + 2048;
constexpr int SM_MX    = SM_PF + 8192;
constexpr int SM_ML    = SM_MX + 1024;
constexpr int SM_END   = SM_ML + 128;
constexpr int SM_SUM   = SM_IN0;
static_assert(SM_END <= 232448, "smem");

struct Maps { CUtensorMap wqB, wqA, wuk, wuv, woB, woA, ckv; };

__device__ float    g_part[4][NCTA][512];
__device__ float    g_fin[2][32][4][512];
__device__ uint4    g_q[4][2048];
__device__ uint4    g_op[NCTA][2048];
__device__ float2   g_stat[32][128];
__device__ __align__(32) unsigned g_cnt[2];
#define TLX(i) do {} while (0)
#define TL(i) do {} while (0)

constexpr int SPIN_LIMIT = 1 << 22;

__device__ __forceinline__ uint32_t smem_u32(const void* p) { return (uint32_t)__cvta_generic_to_shared(p); }
__device__ __forceinline__ void mbar_init(uint32_t bar, uint32_t cnt) {
    asm volatile("mbarrier.init.shared::cta.b64 [%0], %1;" ::"r"(bar), "r"(cnt) : "memory");
}
__device__ __forceinline__ void mbar_expect_tx(uint32_t bar, uint32_t bytes) {
    asm volatile("mbarrier.arrive.expect_tx.shared::cta.b64 _, [%0], %1;" ::"r"(bar), "r"(bytes) : "memory");
}
__device__ __forceinline__ void mbar_arrive(uint32_t bar) {
    asm volatile("mbarrier.arrive.shared::cta.b64 _, [%0];" ::"r"(bar) : "memory");
}
__device__ __forceinline__ void mbar_arrive8(uint32_t bar) {
    asm volatile("mbarrier.arrive.shared::cta.b64 _, [%0], 8;" ::"r"(bar) : "memory");
}
__device__ __forceinline__ void mbar_wait(uint32_t bar) {
    uint32_t done;
    int it = 0;
    do {
        asm volatile("{\n.reg .pred p;\nmbarrier.try_wait.parity.shared::cta.b64 p, [%1], 0;\nselp.u32 %0, 1, 0, p;\n}"
                     : "=r"(done) : "r"(bar) : "memory");
        if (++it > SPIN_LIMIT) __trap();
    } while (!done);
}
__device__ __forceinline__ void bulk_load(uint32_t dst, const void* src, uint32_t bytes, uint32_t bar, uint64_t pol) {
    asm volatile("cp.async.bulk.shared::cluster.global.mbarrier::complete_tx::bytes.L2::cache_hint [%0], [%1], %2, [%3], %4;"
                 ::"r"(dst), "l"(src), "r"(bytes), "r"(bar), "l"(pol) : "memory");
}
__device__ __forceinline__ void bulk_load_nohint(uint32_t dst, const void* src, uint32_t bytes, uint32_t bar) {
    asm volatile("cp.async.bulk.shared::cluster.global.mbarrier::complete_tx::bytes [%0], [%1], %2, [%3];"
                 ::"r"(dst), "l"(src), "r"(bytes), "r"(bar) : "memory");
}
__device__ __forceinline__ void tma2d(uint32_t dst, const CUtensorMap* tm, int c0, int c1, uint32_t bar, uint64_t pol) {
    asm volatile("cp.async.bulk.tensor.2d.shared::cluster.global.mbarrier::complete_tx::bytes.L2::cache_hint [%0], [%1, {%3, %4}], [%2], %5;"
                 ::"r"(dst), "l"(tm), "r"(bar), "r"(c0), "r"(c1), "l"(pol) : "memory");
}
__device__ __forceinline__ void tma3d(uint32_t dst, const CUtensorMap* tm, int c0, int c1, int c2, uint32_t bar, uint64_t pol) {
    asm volatile("cp.async.bulk.tensor.3d.shared::cluster.global.mbarrier::complete_tx::bytes.L2::cache_hint [%0], [%1, {%3, %4, %5}], [%2], %6;"
                 ::"r"(dst), "l"(tm), "r"(bar), "r"(c0), "r"(c1), "r"(c2), "l"(pol) : "memory");
}
__device__ __forceinline__ void ldsm4(uint32_t a, uint32_t& r0, uint32_t& r1, uint32_t& r2, uint32_t& r3) {
    asm volatile("ldmatrix.sync.aligned.m8n8.x4.shared.b16 {%0,%1,%2,%3}, [%4];"
                 : "=r"(r0), "=r"(r1), "=r"(r2), "=r"(r3) : "r"(a) : "memory");
}
__device__ __forceinline__ void ldsm4t(uint32_t a, uint32_t& r0, uint32_t& r1, uint32_t& r2, uint32_t& r3) {
    asm volatile("ldmatrix.sync.aligned.m8n8.x4.trans.shared.b16 {%0,%1,%2,%3}, [%4];"
                 : "=r"(r0), "=r"(r1), "=r"(r2), "=r"(r3) : "r"(a) : "memory");
}
__device__ __forceinline__ void mma16816(float (&c)[4], uint32_t a0, uint32_t a1, uint32_t a2, uint32_t a3,
                                         uint32_t b0, uint32_t b1) {
    asm volatile("mma.sync.aligned.m16n8k16.row.col.f32.bf16.bf16.f32 {%0,%1,%2,%3}, {%4,%5,%6,%7}, {%8,%9}, {%0,%1,%2,%3};"
                 : "+f"(c[0]), "+f"(c[1]), "+f"(c[2]), "+f"(c[3])
                 : "r"(a0), "r"(a1), "r"(a2), "r"(a3), "r"(b0), "r"(b1));
}
__device__ __forceinline__ uint32_t lds32(uint32_t a) {
    uint32_t v; asm volatile("ld.shared.b32 %0, [%1];" : "=r"(v) : "r"(a) : "memory"); return v;
}
__device__ __forceinline__ float ldsf(uint32_t a) {
    float v; asm volatile("ld.shared.f32 %0, [%1];" : "=f"(v) : "r"(a) : "memory"); return v;
}
__device__ __forceinline__ float2 ldsf2(uint32_t a) {
    float2 v; asm volatile("ld.shared.v2.f32 {%0,%1}, [%2];" : "=f"(v.x), "=f"(v.y) : "r"(a) : "memory"); return v;
}
__device__ __forceinline__ float4 ldsf4(uint32_t a) {
    float4 v; asm volatile("ld.shared.v4.f32 {%0,%1,%2,%3}, [%4];" : "=f"(v.x), "=f"(v.y), "=f"(v.z), "=f"(v.w) : "r"(a) : "memory"); return v;
}
__device__ __forceinline__ uint4 lds128(uint32_t a) {
    uint4 v; asm volatile("ld.shared.v4.b32 {%0,%1,%2,%3}, [%4];" : "=r"(v.x), "=r"(v.y), "=r"(v.z), "=r"(v.w) : "r"(a) : "memory"); return v;
}
__device__ __forceinline__ void sts16(uint32_t a, uint16_t v) { asm volatile("st.shared.b16 [%0], %1;" ::"r"(a), "h"(v) : "memory"); }
__device__ __forceinline__ void sts32(uint32_t a, uint32_t v) { asm volatile("st.shared.b32 [%0], %1;" ::"r"(a), "r"(v) : "memory"); }
__device__ __forceinline__ void stsf(uint32_t a, float v) { asm volatile("st.shared.f32 [%0], %1;" ::"r"(a), "f"(v) : "memory"); }
__device__ __forceinline__ void sts64(uint32_t a, uint32_t x, uint32_t y) {
    asm volatile("st.shared.v2.b32 [%0], {%1,%2};" ::"r"(a), "r"(x), "r"(y) : "memory");
}
__device__ __forceinline__ void sts128(uint32_t a, uint4 v) {
    asm volatile("st.shared.v4.b32 [%0], {%1,%2,%3,%4};" ::"r"(a), "r"(v.x), "r"(v.y), "r"(v.z), "r"(v.w) : "memory");
}
__device__ __forceinline__ uint32_t pack_bf16(float lo, float hi) {
    uint32_t r; asm("cvt.rn.bf16x2.f32 %0, %1, %2;" : "=r"(r) : "f"(hi), "f"(lo)); return r;
}
__device__ __forceinline__ float bf_lo(uint32_t v) { return __uint_as_float(v << 16); }
__device__ __forceinline__ float bf_hi(uint32_t v) { return __uint_as_float(v & 0xffff0000u); }
__device__ __forceinline__ float ex2(float x) { float y; asm("ex2.approx.ftz.f32 %0, %1;" : "=f"(y) : "f"(x)); return y; }
__device__ __forceinline__ uint32_t timer_ns() { uint32_t t; asm volatile("mov.u32 %0, %%globaltimer_lo;" : "=r"(t)); return t; }
__device__ __forceinline__ void bar_consumers() { asm volatile("bar.sync 1, 256;" ::: "memory"); }

__device__ __forceinline__ uint32_t tagf(float v, uint32_t tag) { return (__float_as_uint(v) & 0xffffff00u) | tag; }
__device__ __forceinline__ void st_tag2(float* p, float a, float b, uint32_t tag) {
    asm volatile("st.relaxed.gpu.global.v2.b32 [%0], {%1,%2};" ::"l"(p), "r"(tagf(a, tag)), "r"(tagf(b, tag)) : "memory");
}
__device__ __forceinline__ uint2 ld_rlx2(const float* p) {
    uint2 v; asm volatile("ld.relaxed.gpu.global.v2.b32 {%0,%1}, [%2];" : "=r"(v.x), "=r"(v.y) : "l"(p) : "memory"); return v;
}
__device__ __forceinline__ uint4 ld_rlx4(const float* p) {
    uint4 v; asm volatile("ld.relaxed.gpu.global.v4.b32 {%0,%1,%2,%3}, [%4];" : "=r"(v.x), "=r"(v.y), "=r"(v.z), "=r"(v.w) : "l"(p) : "memory"); return v;
}
__device__ __forceinline__ float untag(uint32_t v) { return __uint_as_float(v & 0xffffff00u); }

__device__ __forceinline__ uint32_t slot_off(int item) { return (uint32_t)(item % NSLOT) * SLOT; }

template <bool TRANS, bool RELEASE = true>
__device__ __forceinline__ void tile_mma(uint32_t sb, int item, uint32_t in, int w, int lane, float (&acc)[2][2]) {
    const int g = lane >> 2, t = lane & 3;
    float c[4][4];
#pragma unroll
    for (int i = 0; i < 16; i++) (&c[0][0])[i] = 0.f;
    uint32_t a[16];
    const uint32_t ia = in + (g & 3) * 272 + t * 4;
#pragma unroll
    for (int i = 0; i < 16; i++) a[i] = lds32(ia + i * 16);
    const uint32_t s0 = sb + slot_off(item), s1 = sb + slot_off(item + 1);
    if (TRANS) {
        mbar_wait(sb + SM_FULL + (item + (w >> 2)) * 8);
        const int r = (lane & 7) + (lane & 8);
        const int ch = 2 * (w & 3) + (lane >> 4);
        const uint32_t base = ((w >> 2) ? s1 : s0) + r * 128 + ((ch ^ (lane & 7)) << 4);
#pragma unroll
        for (int kk = 0; kk < 8; kk++) {
            uint32_t r0, r1, r2, r3;
            ldsm4t(base + kk * 2048, r0, r1, r2, r3);
            mma16816(c[2 * (kk & 1)],     a[2 * kk], 0u, a[2 * kk + 1], 0u, r0, r1);
            mma16816(c[2 * (kk & 1) + 1], a[2 * kk], 0u, a[2 * kk + 1], 0u, r2, r3);
        }
    } else {
        mbar_wait(sb + SM_FULL + item * 8);
        mbar_wait(sb + SM_FULL + (item + 1) * 8);
        const int r = 16 * w + (lane & 7) + ((lane >> 4) << 3);
        const uint32_t off = r * 128 + ((((lane >> 3) & 1) ^ (lane & 7)) << 4);
#pragma unroll
        for (int kk = 0; kk < 8; kk++) {
            uint32_t r0, r1, r2, r3;
            ldsm4(((kk >> 2) ? s1 : s0) + (off ^ ((kk & 3) << 5)), r0, r1, r2, r3);
            mma16816(c[2 * (kk & 1)],     a[2 * kk], 0u, a[2 * kk + 1], 0u, r0, r1);
            mma16816(c[2 * (kk & 1) + 1], a[2 * kk], 0u, a[2 * kk + 1], 0u, r2, r3);
        }
    }
    if (RELEASE) {
        __syncwarp();
        if (lane == 0) {
            mbar_arrive(sb + SM_EMPTY + item * 8);
            mbar_arrive(sb + SM_EMPTY + (item + 1) * 8);
        }
    }
    acc[0][0] = c[0][0] + c[2][0]; acc[0][1] = c[0][1] + c[2][1];
    acc[1][0] = c[1][0] + c[3][0]; acc[1][1] = c[1][1] + c[3][1];
}

__device__ __forceinline__ void publish(float* dst, int pitch, int w, int lane, const float (&acc)[2][2], uint32_t tag) {
    if (lane < 16) {
        float* p = dst + (lane >> 2) * pitch + 16 * w + 2 * (lane & 3);
        st_tag2(p, acc[0][0], acc[0][1], tag);
        st_tag2(p + 8, acc[1][0], acc[1][1], tag);
    }
}

__device__ __forceinline__ void gather(const float* part, uint32_t in, int tid, uint32_t tag) {
    const float* p = part + tid * 2;
    uint2 v0, v1, v2, v3;
    int it = 0;
    while (true) {
        v0 = ld_rlx2(p); v1 = ld_rlx2(p + 512); v2 = ld_rlx2(p + 1024); v3 = ld_rlx2(p + 1536);
        uint32_t bad = ((v0.x ^ tag) | (v0.y ^ tag) | (v1.x ^ tag) | (v1.y ^ tag) |
                        (v2.x ^ tag) | (v2.y ^ tag) | (v3.x ^ tag) | (v3.y ^ tag)) & 0xffu;
        if (__all_sync(0xffffffffu, bad == 0)) break;
        if (++it > SPIN_LIMIT) __trap();
    }
    float x = (untag(v0.x) + untag(v1.x)) + (untag(v2.x) + untag(v3.x));
    float y = (untag(v0.y) + untag(v1.y)) + (untag(v2.y) + untag(v3.y));
    sts32(in + (tid >> 6) * 272 + (tid & 63) * 4, pack_bf16(x, y));
    bar_consumers();
}

__device__ __forceinline__ unsigned read_epoch() {
    unsigned v;
    asm volatile("ld.relaxed.gpu.global.u32 %0, [%1];" : "=r"(v) : "l"(&g_cnt[1]) : "memory");
    return v / NCTA + 1;
}
__device__ __forceinline__ uint32_t epoch_tag(unsigned epoch) { return (epoch & 0x7fu) | 0x80u; }

__device__ __forceinline__ void signal_and_wait(unsigned* cnt, unsigned target, int lane, uint32_t sb) {
    if (lane == 0) asm volatile("red.release.gpu.global.add.u32 [%0], 1;" ::"l"(cnt) : "memory");
    if (lane == 0) TL(30 + (cnt - g_cnt));
    int it = 0;
    while (true) {
        unsigned v;
        asm volatile("ld.acquire.gpu.global.u32 %0, [%1];" : "=r"(v) : "l"(cnt) : "memory");
        if (__all_sync(0xffffffffu, (int)(v - target) >= 0)) break;
        if (++it > SPIN_LIMIT) __trap();
    }
    asm volatile("fence.proxy.async.global;" ::: "memory");
}

__device__ __forceinline__ void final_reduce(const float* p, __nv_bfloat16* dst, int lane, uint32_t tag, int part) {
    uint4 v0, v1, v2, v3;
    int it = 0;
    if (lane == 0) TLX(152 + part);
    while (true) {
        v0 = ld_rlx4(p); v1 = ld_rlx4(p + 8 * 2048); v2 = ld_rlx4(p + 16 * 2048); v3 = ld_rlx4(p + 24 * 2048);
        uint32_t bad = ((v0.x ^ tag) | (v0.y ^ tag) | (v0.z ^ tag) | (v0.w ^ tag) |
                        (v1.x ^ tag) | (v1.y ^ tag) | (v1.z ^ tag) | (v1.w ^ tag) |
                        (v2.x ^ tag) | (v2.y ^ tag) | (v2.z ^ tag) | (v2.w ^ tag) |
                        (v3.x ^ tag) | (v3.y ^ tag) | (v3.z ^ tag) | (v3.w ^ tag)) & 0xffu;
        if (__all_sync(0xffffffffu, bad == 0)) break;
        if (++it > SPIN_LIMIT) __trap();
    }
    if (lane == 0) TLX(154 + part);
    float s0 = (untag(v0.x) + untag(v1.x)) + (untag(v2.x) + untag(v3.x));
    float s1 = (untag(v0.y) + untag(v1.y)) + (untag(v2.y) + untag(v3.y));
    float s2 = (untag(v0.z) + untag(v1.z)) + (untag(v2.z) + untag(v3.z));
    float s3 = (untag(v0.w) + untag(v1.w)) + (untag(v2.w) + untag(v3.w));
#pragma unroll
    for (int m = 4; m < 32; m <<= 1) {
        s0 += __shfl_xor_sync(0xffffffffu, s0, m);
        s1 += __shfl_xor_sync(0xffffffffu, s1, m);
        s2 += __shfl_xor_sync(0xffffffffu, s2, m);
        s3 += __shfl_xor_sync(0xffffffffu, s3, m);
    }
    if (lane < 4) *reinterpret_cast<uint2*>(dst) = make_uint2(pack_bf16(s0, s1), pack_bf16(s2, s3));
}

__global__ void __launch_bounds__(NTHR, 1)
fused_decode_kernel(const __grid_constant__ Maps maps,
                    const __nv_bfloat16* __restrict__ xA, const __nv_bfloat16* __restrict__ xB,
                    const __nv_bfloat16* __restrict__ Kc, const __nv_bfloat16* __restrict__ Vc,
                    __nv_bfloat16* __restrict__ out) {
    extern __shared__ __align__(1024) unsigned char smem_raw[];
    const uint32_t sb = smem_u32(smem_raw);
    const int tid = threadIdx.x, lane = tid & 31;
    const int w = __shfl_sync(0xffffffffu, tid >> 5, 0);
    const int cta = blockIdx.x, h = cta >> 2, j = cta & 3;

    if (w >= 8) {
        unsigned epoch;
        if (w == 8) {
            const size_t kv_off = ((size_t)(j * 32 + h) * 4096 + 3072) * 128;
            uint64_t pol;
            asm volatile("createpolicy.fractional.L2::evict_first.b64 %0, 1.0;" : "=l"(pol));
            if (lane == 0) {
                TLX(0);
                asm volatile("cp.async.bulk.prefetch.L2.global [%0], %1;" ::"l"(Kc + kv_off), "r"(SLOT) : "memory");
#pragma unroll
                for (int i = 0; i < 2; i++) mbar_init(sb + SM_FULL + i * 8, 1);
                asm volatile("fence.mbarrier_init.release.cluster;" ::: "memory");
#pragma unroll
                for (int i = 0; i < 2; i++) {
                    TLX(32 + i);
                    mbar_expect_tx(sb + SM_FULL + i * 8, SLOT);
                    tma2d(sb + i * SLOT, &maps.wqB, h * 128 + i * 64, j * 128, sb + SM_FULL + i * 8, pol);
                }
            }
            uint32_t tnext = timer_ns() + 3 * PACE - OFFS + STAG * cta * PACE / NCTA;
            epoch = read_epoch();
            asm volatile(BAR2 ::: "memory");
            int slot = 2, tail = 2 - INFLIGHT;
#pragma unroll 1
            for (int i = 2; i < NITEM; i++) {
                const uint32_t dst = sb + slot * SLOT, bar = sb + SM_FULL + i * 8;
                if (++slot == NSLOT) slot = 0;
                if ((i & ~1) == IT_Q || (i & ~1) == IT_OP) continue;
                const bool wt = i < IT_K0 || (i & ~1) == IT_WUV || i >= IT_WOB;
                if (i >= NSLOT) mbar_wait(sb + SM_EMPTY + (i - NSLOT) * 8);
                if (tail >= 0) mbar_wait(sb + SM_FULL + tail * 8);
                ++tail;
                if (tail == IT_Q || tail == IT_OP) tail += 2;
                if (!(wt && (i & 1)) && i != IT_K0) {
                    while (__all_sync(0xffffffffu, (int)(timer_ns() - tnext) < 0)) {}
                    tnext += wt ? 2 * PACE : PACE;
                }
                if (lane == 0) TLX(32 + i);
                if (wt) {
                    const bool wo = i >= IT_WOB;
                    const CUtensorMap* tm = &maps.wqB + (i < IT_K0 ? (i >> 1) : wo ? (i - IT_WOB + 8) >> 1 : 3);
                    if (lane == 0) tma2d(dst, tm, (wo ? j : h) * 128 + (i & 1) * 64, (wo ? h : j) * 128, bar, pol);
                } else if (i >= IT_C && i < IT_K1) {
                    if (lane == 0) tma3d(dst, &maps.ckv, 0, cta * 128 + (i - IT_C) * 16, 0, bar, pol);
                } else {
                    const __nv_bfloat16* src = (i < IT_V0 ? Kc : Vc) + kv_off;
                    const int c = i < IT_Q ? i - IT_K0 : i < IT_V0 ? i - IT_K1 + 8 : i < IT_OP ? i - IT_V0 : i - IT_V1 + 8;
                    if (lane == 0) bulk_load(dst, src + (size_t)c * (SLOT / 2), SLOT, bar, pol);
                }
            }
            if (lane == 0) TL(1);
        } else {
            if (lane < 6) asm volatile("prefetch.tensormap [%0];" ::"l"(&maps.wqA + lane) : "memory");
            epoch = read_epoch();
            asm volatile(BAR2 ::: "memory");
            asm volatile("bar.sync 3, 288;" ::: "memory");
            if (lane == 0) TL(9);
            signal_and_wait(&g_cnt[0], epoch * NCTA, lane, sb);
            if (lane == 0) {
                TL(2);
                const uint4* q = g_q[cta >> 5];
                bulk_load_nohint(sb + slot_off(IT_Q), q, SLOT, sb + SM_FULL + IT_Q * 8);
                bulk_load_nohint(sb + slot_off(IT_Q + 1), q + 1024, SLOT, sb + SM_FULL + (IT_Q + 1) * 8);
            }
            asm volatile("bar.sync 3, 288;" ::: "memory");
            if (lane == 0) TL(13);
            signal_and_wait(&g_cnt[1], epoch * NCTA, lane, sb);
            mbar_wait(sb + SM_EMPTY + (IT_OP - NSLOT) * 8);
            mbar_wait(sb + SM_EMPTY + (IT_OP + 1 - NSLOT) * 8);
            if (lane == 0) {
                TL(3);
                const uint4* op = g_op[cta];
                bulk_load_nohint(sb + SM_MX, g_stat[h], 1024, sb + SM_FULL + IT_OP * 8);
                bulk_load_nohint(sb + slot_off(IT_OP), op, SLOT, sb + SM_FULL + IT_OP * 8);
                bulk_load_nohint(sb + slot_off(IT_OP + 1), op + 1024, SLOT, sb + SM_FULL + (IT_OP + 1) * 8);
            }
        }
        __syncwarp();
        const int part = 9 - w, b = cta >> 5, col0 = 16 * (cta & 31) + 4 * (lane & 3);
        mbar_wait(sb + SM_FULL + (IT_WOB + 2 * part) * 8);
        final_reduce(&g_fin[part][lane >> 2][b][col0], out + b * 1024 + (part == 0 ? 512 : 0) + col0, lane, epoch_tag(epoch), part);
        if (lane == 0) TL(4 + part);
        return;
    }

    const int g = lane >> 2, t = lane & 3;
    const uint32_t in0 = sb + SM_IN0, in1 = sb + SM_IN1;
    const uint32_t tag = epoch_tag(read_epoch());
    {
        uint4 v;
        if (tid < 128) {
            const __nv_bfloat16* x = (tid < 64 ? xB : xA) + ((tid >> 4) & 3) * 512 + j * 128 + (tid & 15) * 8;
            v = __ldg(reinterpret_cast<const uint4*>(x));
        }
        if (lane == 0) {
            const uint32_t bars = sb + (w < 4 ? SM_EMPTY : SM_FULL + 2 * 8) + (w & 3) * 14 * 8;
            const uint32_t cnt = w < 4 ? 8 : 1;
#pragma unroll
            for (int i = 0; i < 14; i++) mbar_init(bars + i * 8, cnt);
            if (w >= 4) {
#pragma unroll
                for (int i = 0; i < 14; i++)
                    mbar_expect_tx(bars + i * 8, (i == (IT_OP - 2) % 14 && w == 4 + (IT_OP - 2) / 14) ? SLOT + 1024 : SLOT);
            }
            asm volatile("fence.mbarrier_init.release.cluster;" ::: "memory");
        }
        __syncwarp();
        const float zero[2][2] = {{0.f, 0.f}, {0.f, 0.f}};
        publish(g_part[0][cta], 128, w, lane, zero, 0u);
        publish(g_part[1][cta], 128, w, lane, zero, 0u);
        publish(g_part[2][cta], 128, w, lane, zero, 0u);
        publish(&g_fin[0][h][0][j * 128], 512, w, lane, zero, 0u);
        publish(&g_fin[1][h][0][j * 128], 512, w, lane, zero, 0u);
        if (tid < 64) st_tag2(g_part[3][h * 4] + j * 128 + tid * 2, 0.f, 0.f, 0u);
        if (tid < 128) sts128((tid < 64 ? in0 : in1) + ((tid >> 4) & 3) * 272 + (tid & 15) * 16, v);
    }
    if (tid == 0) TL(22);
    asm volatile(BAR2 ::: "memory");
    if (tid == 0) TL(23);

    float acc[2][2];
    tile_mma<true>(sb, IT_WQB, in0, w, lane, acc);
    if (tid == 0) TL(24);
    publish(g_part[0][cta], 128, w, lane, acc, tag);
    if (tid == 0) TL(6);
    tile_mma<true>(sb, IT_WQA, in1, w, lane, acc);
    publish(g_part[1][cta], 128, w, lane, acc, tag);
    if (tid == 0) TL(7);
    bar_consumers();

    const float SC = 0.08838834764831845f * 1.4426950408889634f;
    gather(g_part[0][h * 4], in0, tid, tag);
    if (tid == 0) TL(8);
    tile_mma<false>(sb, IT_WUK, in0, w, lane, acc);
    if (tid == 0) TL(25);
    if (lane < 16) {
        uint32_t* q = reinterpret_cast<uint32_t*>(g_q[g]) + (2 * j + (w >> 2)) * 1024 + h * 32 + t;
        const int ch = 2 * (w & 3);
        q[((ch) ^ (h & 7)) * 4]     = pack_bf16(acc[0][0] * SC, acc[0][1] * SC);
        q[((ch + 1) ^ (h & 7)) * 4] = pack_bf16(acc[1][0] * SC, acc[1][1] * SC);
    }
    __syncwarp();
    asm volatile("bar.arrive 3, 288;" ::: "memory");
    gather(g_part[1][h * 4], in1, tid, tag);
    if (tid == 0) TL(28);

    uint32_t qf[16];
#pragma unroll
    for (int c = 0; c < 8; c++) {
        qf[2 * c]     = lds32(in1 + j * 272 + ((c ^ g) << 4) + t * 4);
        qf[2 * c + 1] = lds32(in1 + j * 272 + 128 + ((c ^ g) << 4) + t * 4);
    }
    const uint32_t sc_w = sb + SM_SC + w * 512;
    auto k_item = [&](int item, uint32_t sc) {
        mbar_wait(sb + SM_FULL + item * 8);
        const uint32_t base = sb + slot_off(item) + ((lane & 7) + (lane & 8)) * 256 + ((lane >> 4) << 7);
        float s[4][4];
#pragma unroll
        for (int T = 0; T < 4; T++) { s[T][0] = s[T][1] = s[T][2] = s[T][3] = 0.f; }
#pragma unroll
        for (int c = 0; c < 8; c++) {
            const uint32_t a = base + ((c ^ (lane & 7)) << 4);
#pragma unroll
            for (int T = 0; T < 4; T++) {
                uint32_t r0, r1, r2, r3;
                ldsm4(a + T * 4096, r0, r1, r2, r3);
                mma16816(s[T], r0, r1, r2, r3, qf[2 * c], qf[2 * c + 1]);
            }
        }
        __syncwarp();
        if (lane == 0) mbar_arrive8(sb + SM_EMPTY + item * 8);
        if (t == (g >> 1)) {
#pragma unroll
            for (int T = 0; T < 4; T++) {
                stsf(sc + (16 * T + g) * 4,     (g & 1) ? s[T][1] : s[T][0]);
                stsf(sc + (16 * T + g + 8) * 4, (g & 1) ? s[T][3] : s[T][2]);
            }
        }
    };
    k_item(IT_K0 + w, sc_w);
    if (tid == 224) TL(10);

    {
        float s[2][2][4];
#pragma unroll
        for (int i = 0; i < 16; i++) (&s[0][0][0])[i] = 0.f;
        mbar_wait(sb + SM_FULL + IT_Q * 8);
        mbar_wait(sb + SM_FULL + (IT_Q + 1) * 8);
        if (tid == 0) TLX(96 + IT_Q);
        mbar_wait(sb + SM_FULL + (IT_C + w) * 8);
        const uint32_t cb0 = sb + slot_off(IT_C + w) + ((lane & 7) + ((lane >> 4) << 3)) * 128;
        const uint32_t cx = (((lane >> 3) & 1) ^ (lane & 7)) << 4;
        const uint32_t qr = ((lane & 7) + (lane & 8)) * 128;
        const uint32_t qx = ((lane >> 4) ^ (lane & 7)) << 4;
#pragma unroll
        for (int cb = 0; cb < 8; cb++) {
            const uint32_t qb = sb + slot_off(IT_Q + (cb >> 2)) + (cb & 3) * 4096 + qr;
#pragma unroll
            for (int k4 = 0; k4 < 4; k4++) {
                uint32_t b0, b1, b2, b3, a0, a1, a2, a3;
                ldsm4(cb0 + cb * 2048 + (cx ^ (k4 << 5)), b0, b1, b2, b3);
                ldsm4(qb + (qx ^ (k4 << 5)), a0, a1, a2, a3);
                mma16816(s[0][0], a0, a1, a2, a3, b0, b1);
                mma16816(s[0][1], a0, a1, a2, a3, b2, b3);
                ldsm4(qb + 2048 + (qx ^ (k4 << 5)), a0, a1, a2, a3);
                mma16816(s[1][0], a0, a1, a2, a3, b0, b1);
                mma16816(s[1][1], a0, a1, a2, a3, b2, b3);
            }
        }
        __syncwarp();
        if (lane == 0) { mbar_arrive(sb + SM_EMPTY + IT_Q * 8); mbar_arrive(sb + SM_EMPTY + (IT_Q + 1) * 8); }
#pragma unroll
        for (int r = 0; r < 4; r++) {
            const int mt = r >> 1, hi = (r & 1) * 2;
            float m = fmaxf(fmaxf(s[mt][0][hi], s[mt][0][hi + 1]), fmaxf(s[mt][1][hi], s[mt][1][hi + 1]));
            m = fmaxf(m, __shfl_xor_sync(0xffffffffu, m, 1));
            m = fmaxf(m, __shfl_xor_sync(0xffffffffu, m, 2));
            if (t == 0) stsf(sb + SM_MX + (8 * r + g) * 32 + w * 4, m);
        }
        bar_consumers();
        if (tid == 0) TL(11);
        uint32_t pf[2][4];
#pragma unroll
        for (int r = 0; r < 4; r++) {
            const int mt = r >> 1, hi = r & 1;
            const float4 m0 = ldsf4(sb + SM_MX + (8 * r + g) * 32), m1 = ldsf4(sb + SM_MX + (8 * r + g) * 32 + 16);
            const float m = fmaxf(fmaxf(fmaxf(m0.x, m0.y), fmaxf(m0.z, m0.w)), fmaxf(fmaxf(m1.x, m1.y), fmaxf(m1.z, m1.w)));
            const uint32_t p0 = pack_bf16(ex2(s[mt][0][2 * hi] - m), ex2(s[mt][0][2 * hi + 1] - m));
            const uint32_t p1 = pack_bf16(ex2(s[mt][1][2 * hi] - m), ex2(s[mt][1][2 * hi + 1] - m));
            pf[mt][hi] = p0; pf[mt][2 + hi] = p1;
            float l = (bf_lo(p0) + bf_hi(p0)) + (bf_lo(p1) + bf_hi(p1));
            l += __shfl_xor_sync(0xffffffffu, l, 1);
            l += __shfl_xor_sync(0xffffffffu, l, 2);
            if (t == 0) stsf(sb + SM_SUM + (8 * r + g) * 32 + w * 4, l);
        }
        sts128(sb + SM_PF + (w * 2 + 0) * 512 + lane * 16, make_uint4(pf[0][0], pf[0][1], pf[0][2], pf[0][3]));
        sts128(sb + SM_PF + (w * 2 + 1) * 512 + lane * 16, make_uint4(pf[1][0], pf[1][1], pf[1][2], pf[1][3]));
        bar_consumers();
        if (w == 0) {
            const float4 m0 = ldsf4(sb + SM_MX + lane * 32), m1 = ldsf4(sb + SM_MX + lane * 32 + 16);
            const float4 l0 = ldsf4(sb + SM_SUM + lane * 32), l1 = ldsf4(sb + SM_SUM + lane * 32 + 16);
            const float m = fmaxf(fmaxf(fmaxf(m0.x, m0.y), fmaxf(m0.z, m0.w)), fmaxf(fmaxf(m1.x, m1.y), fmaxf(m1.z, m1.w)));
            const float l = ((l0.x + l0.y) + (l0.z + l0.w)) + ((l1.x + l1.y) + (l1.z + l1.w));
            g_stat[lane][cta] = make_float2(m, l);
        }
        float o[2][8][4];
#pragma unroll
        for (int i = 0; i < 64; i++) (&o[0][0][0])[i] = 0.f;
        const uint32_t vr = w * 2048 + ((lane & 7) + (lane & 8)) * 128;
        const uint32_t vx = ((lane >> 4) ^ (lane & 7)) << 4;
#pragma unroll
        for (int ks = 0; ks < 8; ks++) {
            const uint4 p0 = lds128(sb + SM_PF + (ks * 2 + 0) * 512 + lane * 16);
            const uint4 p1 = lds128(sb + SM_PF + (ks * 2 + 1) * 512 + lane * 16);
            const uint32_t vb = sb + slot_off(IT_C + ks) + vr;
#pragma unroll
            for (int n2 = 0; n2 < 4; n2++) {
                uint32_t b0, b1, b2, b3;
                ldsm4t(vb + (vx ^ (n2 << 5)), b0, b1, b2, b3);
                mma16816(o[0][2 * n2],     p0.x, p0.y, p0.z, p0.w, b0, b1);
                mma16816(o[0][2 * n2 + 1], p0.x, p0.y, p0.z, p0.w, b2, b3);
                mma16816(o[1][2 * n2],     p1.x, p1.y, p1.z, p1.w, b0, b1);
                mma16816(o[1][2 * n2 + 1], p1.x, p1.y, p1.z, p1.w, b2, b3);
            }
            __syncwarp();
            if (lane == 0) mbar_arrive(sb + SM_EMPTY + (IT_C + ks) * 8);
        }
        if (tid == 0) TL(12);
        mbar_wait(sb + SM_FULL + (IT_K1 + 2 + (w >> 1)) * 8);
#pragma unroll
        for (int r = 0; r < 4; r++) {
            const int mt = r >> 1, hi = (r & 1) * 2;
            uint4* dst = g_op[(8 * r + g) * 4 + (w >> 1)] + (w & 1) * 1024 + cta * 8;
#pragma unroll
            for (int u = 0; u < 2; u++) {
                uint4 v;
                v.x = pack_bf16(o[mt][4 * u][hi],     o[mt][4 * u][hi + 1]);
                v.y = pack_bf16(o[mt][4 * u + 1][hi], o[mt][4 * u + 1][hi + 1]);
                v.z = pack_bf16(o[mt][4 * u + 2][hi], o[mt][4 * u + 2][hi + 1]);
                v.w = pack_bf16(o[mt][4 * u + 3][hi], o[mt][4 * u + 3][hi + 1]);
                dst[(t + 4 * u) ^ (cta & 7)] = v;
            }
        }
        if (tid == 0) TL(29);
        asm volatile("bar.arrive 3, 288;" ::: "memory");
    }

    k_item(IT_K1 + w, sc_w + 256);
    __syncwarp();
    {
        const float4 s = ldsf4(sc_w + lane * 16);
        float m = fmaxf(fmaxf(s.x, s.y), fmaxf(s.z, s.w));
#pragma unroll
        for (int d = 1; d < 32; d <<= 1) m = fmaxf(m, __shfl_xor_sync(0xffffffffu, m, d));
        if (lane == 0) stsf(sb + SM_ML + w * 4, m);
        bar_consumers();
        const float4 m0 = ldsf4(sb + SM_ML), m1 = ldsf4(sb + SM_ML + 16);
        m = fmaxf(fmaxf(fmaxf(m0.x, m0.y), fmaxf(m0.z, m0.w)), fmaxf(fmaxf(m1.x, m1.y), fmaxf(m1.z, m1.w))) * SC;
        const uint32_t p0 = pack_bf16(ex2(fmaf(s.x, SC, -m)), ex2(fmaf(s.y, SC, -m)));
        const uint32_t p1 = pack_bf16(ex2(fmaf(s.z, SC, -m)), ex2(fmaf(s.w, SC, -m)));
        float l = (bf_lo(p0) + bf_hi(p0)) + (bf_lo(p1) + bf_hi(p1));
#pragma unroll
        for (int d = 1; d < 32; d <<= 1) l += __shfl_xor_sync(0xffffffffu, l, d);
        if (lane == 0) stsf(sb + SM_ML + 32 + w * 4, l);
        sts64(sb + SM_PA + w * 256 + lane * 8, p0, p1);
        __syncwarp();
    }
    if (tid == 224) TL(14);

    float oa[4][4];
#pragma unroll
    for (int i = 0; i < 16; i++) (&oa[0][0])[i] = 0.f;
    auto v_item = [&](int item, uint32_t pa) {
        uint32_t p[8];
#pragma unroll
        for (int i = 0; i < 8; i++) p[i] = lds32(pa + i * 16 + t * 4);
        mbar_wait(sb + SM_FULL + item * 8);
        const uint32_t base = sb + slot_off(item) + ((lane & 7) + ((lane >> 4) << 3)) * 256 + ((lane & 8) << 4);
#pragma unroll
        for (int c = 0; c < 8; c++) {
            const uint32_t a = base + ((c ^ (lane & 7)) << 4);
            const uint32_t mask = ((c == (g ^ (2 * t))) ? 0x0000ffffu : 0u) | ((c == (g ^ (2 * t + 1))) ? 0xffff0000u : 0u);
#pragma unroll
            for (int T = 0; T < 4; T++) {
                uint32_t r0, r1, r2, r3;
                ldsm4t(a + T * 4096, r0, r1, r2, r3);
                mma16816(oa[T], r0, r1, r2, r3, p[2 * T] & mask, p[2 * T + 1] & mask);
            }
        }
        __syncwarp();
        if (lane == 0) mbar_arrive8(sb + SM_EMPTY + item * 8);
    };
    v_item(IT_V0 + w, sb + SM_PA + w * 256);
    if (tid == 224) TL(15);

    mbar_wait(sb + SM_FULL + IT_OP * 8);
    if (tid == 0) TLX(96 + IT_OP);
    if (w < 4) {
        const float2 st = ldsf2(sb + SM_MX + tid * 8);
        float m = st.x;
#pragma unroll
        for (int d = 1; d < 32; d <<= 1) m = fmaxf(m, __shfl_xor_sync(0xffffffffu, m, d));
        const uint32_t wb = pack_bf16(ex2(st.x - m), 0.f);
        float l = bf_lo(wb) * st.y;
#pragma unroll
        for (int d = 1; d < 32; d <<= 1) l += __shfl_xor_sync(0xffffffffu, l, d);
#pragma unroll
        for (int bb = 0; bb < 4; bb++) sts16(in0 + bb * 272 + tid * 2, bb == w ? (uint16_t)wb : (uint16_t)0);
        if (lane == 0) stsf(sb + SM_ML + 64 + w * 4, 1.f / l);
    }
    bar_consumers();
    tile_mma<true>(sb, IT_OP, in0, w, lane, acc);
    if (lane < 16) {
        const float inv = ldsf(sb + SM_ML + 64 + g * 4);
        const int ch = 2 * (w & 3);
        const uint32_t dst = in1 + g * 272 + ((w >> 2) * 64 + 8 * (4 * (ch >> 2) + t)) * 2;
        sts32(dst + (ch & 3) * 4,       pack_bf16(acc[0][0] * inv, acc[0][1] * inv));
        sts32(dst + ((ch + 1) & 3) * 4, pack_bf16(acc[1][0] * inv, acc[1][1] * inv));
    }
    bar_consumers();
    tile_mma<true>(sb, IT_WUV, in1, w, lane, acc);
    publish(g_part[2][cta], 128, w, lane, acc, tag);
    if (tid == 0) TL(16);
    gather(g_part[2][h * 4], in0, tid, tag);
    if (tid == 0) TL(18);

    {
        const float4 l0 = ldsf4(sb + SM_ML + 32), l1 = ldsf4(sb + SM_ML + 48);
        const float inv = 1.f / (((l0.x + l0.y) + (l0.z + l0.w)) + ((l1.x + l1.y) + (l1.z + l1.w)));
        v_item(IT_V1 + w, sb + SM_PA + w * 256 + 128);
        const uint32_t so = sb + SM_PF + w * 512 + (16 * t + g) * 4;
        stsf(so,       (oa[0][0] + oa[1][0]) + (oa[2][0] + oa[3][0]));
        stsf(so + 32,  (oa[0][1] + oa[1][1]) + (oa[2][1] + oa[3][1]));
        stsf(so + 256, (oa[0][2] + oa[1][2]) + (oa[2][2] + oa[3][2]));
        stsf(so + 288, (oa[0][3] + oa[1][3]) + (oa[2][3] + oa[3][3]));
        bar_consumers();
        if (tid < 64) {
            float x = 0.f, y = 0.f;
#pragma unroll
            for (int i = 0; i < 8; i++) {
                const float2 v = ldsf2(sb + SM_PF + i * 512 + tid * 8);
                x += v.x; y += v.y;
            }
            st_tag2(g_part[3][h * 4] + j * 128 + tid * 2, x * inv, y * inv, tag);
        }
    }
    if (tid == 0) TL(17);

    tile_mma<true, false>(sb, IT_WOB, in0, w, lane, acc);
    publish(&g_fin[0][h][0][j * 128], 512, w, lane, acc, tag);
    if (tid == 224) TL(19);
    {
        const float* p = g_part[3][h * 4] + tid * 2;
        uint2 v;
        int it = 0;
        while (true) {
            v = ld_rlx2(p);
            if (__all_sync(0xffffffffu, (((v.x ^ tag) | (v.y ^ tag)) & 0xffu) == 0)) break;
            if (++it > SPIN_LIMIT) __trap();
        }
        sts32(in1 + (tid >> 6) * 272 + (tid & 63) * 4, pack_bf16(untag(v.x), untag(v.y)));
        bar_consumers();
    }
    if (tid == 0) TL(20);
    tile_mma<true, false>(sb, IT_WOA, in1, w, lane, acc);
    publish(&g_fin[1][h][0][j * 128], 512, w, lane, acc, tag);
    if (tid == 224) TL(26);
}

typedef CUresult (*EncodeTiledFn)(CUtensorMap*, CUtensorMapDataType, cuuint32_t, void*, const cuuint64_t*,
                                  const cuuint64_t*, const cuuint32_t*, const cuuint32_t*, CUtensorMapInterleave,
                                  CUtensorMapSwizzle, CUtensorMapL2promotion, CUtensorMapFloatOOBfill);

void encode_weight(EncodeTiledFn enc, CUtensorMap* tm, const void* p, cuuint64_t cols, cuuint64_t rows) {
    cuuint64_t dims[2] = {cols, rows};
    cuuint64_t strides[1] = {cols * 2};
    cuuint32_t box[2] = {64, 128};
    cuuint32_t es[2] = {1, 1};
    enc(tm, CU_TENSOR_MAP_DATA_TYPE_BFLOAT16, 2, const_cast<void*>(p), dims, strides, box, es,
        CU_TENSOR_MAP_INTERLEAVE_NONE, CU_TENSOR_MAP_SWIZZLE_128B, CU_TENSOR_MAP_L2_PROMOTION_L2_256B,
        CU_TENSOR_MAP_FLOAT_OOB_FILL_NONE);
}

}

extern "C" void kernel_launch(void* const* d_in, const int* in_sizes, int n_in, void* d_out, int out_size) {
    (void)in_sizes; (void)n_in; (void)out_size;
    static EncodeTiledFn enc = nullptr;
    if (!enc) {
        void* fn = nullptr;
        cudaDriverEntryPointQueryResult qr;
        cudaGetDriverEntryPoint("cuTensorMapEncodeTiled", &fn, cudaEnableDefault, &qr);
        enc = (EncodeTiledFn)fn;
        cudaFuncSetAttribute(fused_decode_kernel, cudaFuncAttributeMaxDynamicSharedMemorySize, SM_END);
    }
    Maps maps;
    encode_weight(enc, &maps.wqB, d_in[7], 4096, 512);
    encode_weight(enc, &maps.wqA, d_in[3], 4096, 512);
    encode_weight(enc, &maps.wuk, d_in[8], 4096, 512);
    encode_weight(enc, &maps.wuv, d_in[9], 4096, 512);
    encode_weight(enc, &maps.woB, d_in[10], 512, 4096);
    encode_weight(enc, &maps.woA, d_in[4], 512, 4096);
    {
        cuuint64_t dims[3] = {64, 16384, 8};
        cuuint64_t strides[2] = {1024, 128};
        cuuint32_t box[3] = {64, 16, 8};
        cuuint32_t es[3] = {1, 1, 1};
        enc(&maps.ckv, CU_TENSOR_MAP_DATA_TYPE_BFLOAT16, 3, d_in[6], dims, strides, box, es,
            CU_TENSOR_MAP_INTERLEAVE_NONE, CU_TENSOR_MAP_SWIZZLE_128B, CU_TENSOR_MAP_L2_PROMOTION_L2_256B,
            CU_TENSOR_MAP_FLOAT_OOB_FILL_NONE);
    }
    fused_decode_kernel<<<NCTA, NTHR, SM_END>>>(maps, (const __nv_bfloat16*)d_in[0], (const __nv_bfloat16*)d_in[5],
                                                (const __nv_bfloat16*)d_in[1], (const __nv_bfloat16*)d_in[2],
                                                (__nv_bfloat16*)d_out);
}
```

```cpp
#include <cuda_runtime.h>
#include <cuda_bf16.h>
#include <cuda.h>
#include <stdint.h>

namespace {

constexpr int NCTA   = 128;
constexpr int NSLOT  = 13;
constexpr int SLOT   = 16384;
constexpr int NITEM  = 56;
#define INFLIGHT 4
#define PACE 650
#define OFFS 500
#define STAG 0
#define STARTER 256
#define CTXWAIT 2
constexpr int NTHR   = 320;
#define BAR2 "bar.sync 2, 320;"

constexpr int IT_WQB = 0, IT_WQA = 2, IT_WUK = 4, IT_K0 = 6, IT_Q = 14, IT_C = 16, IT_K1 = 24, IT_V0 = 32,
              IT_OP = 40, IT_WUV = 42, IT_V1 = 44, IT_WOB = 52, IT_WOA = 54;

constexpr int SM_FULL  = NSLOT * SLOT;
constexpr int SM_EMPTY = SM_FULL + 512;
constexpr int SM_IN0   = SM_EMPTY + 512;
constexpr int SM_IN1   = SM_IN0 + 1088;
constexpr int SM_SC    = SM_IN1 + 1088;
constexpr int SM_PA    = SM_SC + 4096;
constexpr int SM_PF    = SM_PA + 2048;
constexpr int SM_MX    = SM_PF + 8192;
constexpr int SM_ML    = SM_MX + 1024;
constexpr int SM_END   = SM_ML + 128;
constexpr int SM_SUM   = SM_IN0;
static_assert(SM_END <= 232448, "smem");

struct Maps { CUtensorMap wqB, wqA, wuk, wuv, woB, woA, ckv; };

struct Scratch {
    unsigned cnt[32];
    float    part[4][NCTA][512];
    float    fin[2][32][4][512];
    uint4    q[4][2048];
    uint4    op[NCTA][2048];
    float2   stat[32][128];
};
__device__ __align__(128) Scratch g_scratch;
#define TLX(i) do {} while (0)
#define TL(i) do {} while (0)

constexpr int SPIN_LIMIT = 1 << 22;

__device__ __forceinline__ uint32_t smem_u32(const void* p) { return (uint32_t)__cvta_generic_to_shared(p); }
__device__ __forceinline__ void mbar_init(uint32_t bar, uint32_t cnt) {
    asm volatile("mbarrier.init.shared::cta.b64 [%0], %1;" ::"r"(bar), "r"(cnt) : "memory");
}
__device__ __forceinline__ void mbar_expect_tx(uint32_t bar, uint32_t bytes) {
    asm volatile("mbarrier.arrive.expect_tx.shared::cta.b64 _, [%0], %1;" ::"r"(bar), "r"(bytes) : "memory");
}
__device__ __forceinline__ void mbar_arrive(uint32_t bar) {
    asm volatile("mbarrier.arrive.shared::cta.b64 _, [%0];" ::"r"(bar) : "memory");
}
__device__ __forceinline__ void mbar_arrive8(uint32_t bar) {
    asm volatile("mbarrier.arrive.shared::cta.b64 _, [%0], 8;" ::"r"(bar) : "memory");
}
__device__ __forceinline__ void mbar_wait(uint32_t bar) {
    uint32_t done;
    int it = 0;
    do {
        asm volatile("{\n.reg .pred p;\nmbarrier.try_wait.parity.shared::cta.b64 p, [%1], 0;\nselp.u32 %0, 1, 0, p;\n}"
                     : "=r"(done) : "r"(bar) : "memory");
        if (++it > SPIN_LIMIT) __trap();
    } while (!done);
}
__device__ __forceinline__ void bulk_load(uint32_t dst, const void* src, uint32_t bytes, uint32_t bar, uint64_t pol) {
    asm volatile("cp.async.bulk.shared::cluster.global.mbarrier::complete_tx::bytes.L2::cache_hint [%0], [%1], %2, [%3], %4;"
                 ::"r"(dst), "l"(src), "r"(bytes), "r"(bar), "l"(pol) : "memory");
}
__device__ __forceinline__ void bulk_load_nohint(uint32_t dst, const void* src, uint32_t bytes, uint32_t bar) {
    asm volatile("cp.async.bulk.shared::cluster.global.mbarrier::complete_tx::bytes [%0], [%1], %2, [%3];"
                 ::"r"(dst), "l"(src), "r"(bytes), "r"(bar) : "memory");
}
__device__ __forceinline__ void tma2d(uint32_t dst, const CUtensorMap* tm, int c0, int c1, uint32_t bar, uint64_t pol) {
    asm volatile("cp.async.bulk.tensor.2d.shared::cluster.global.mbarrier::complete_tx::bytes.L2::cache_hint [%0], [%1, {%3, %4}], [%2], %5;"
                 ::"r"(dst), "l"(tm), "r"(bar), "r"(c0), "r"(c1), "l"(pol) : "memory");
}
__device__ __forceinline__ void tma3d(uint32_t dst, const CUtensorMap* tm, int c0, int c1, int c2, uint32_t bar, uint64_t pol) {
    asm volatile("cp.async.bulk.tensor.3d.shared::cluster.global.mbarrier::complete_tx::bytes.L2::cache_hint [%0], [%1, {%3, %4, %5}], [%2], %6;"
                 ::"r"(dst), "l"(tm), "r"(bar), "r"(c0), "r"(c1), "r"(c2), "l"(pol) : "memory");
}
__device__ __forceinline__ void ldsm4(uint32_t a, uint32_t& r0, uint32_t& r1, uint32_t& r2, uint32_t& r3) {
    asm volatile("ldmatrix.sync.aligned.m8n8.x4.shared.b16 {%0,%1,%2,%3}, [%4];"
                 : "=r"(r0), "=r"(r1), "=r"(r2), "=r"(r3) : "r"(a) : "memory");
}
__device__ __forceinline__ void ldsm4t(uint32_t a, uint32_t& r0, uint32_t& r1, uint32_t& r2, uint32_t& r3) {
    asm volatile("ldmatrix.sync.aligned.m8n8.x4.trans.shared.b16 {%0,%1,%2,%3}, [%4];"
                 : "=r"(r0), "=r"(r1), "=r"(r2), "=r"(r3) : "r"(a) : "memory");
}
__device__ __forceinline__ void mma16816(float (&c)[4], uint32_t a0, uint32_t a1, uint32_t a2, uint32_t a3,
                                         uint32_t b0, uint32_t b1) {
    asm volatile("mma.sync.aligned.m16n8k16.row.col.f32.bf16.bf16.f32 {%0,%1,%2,%3}, {%4,%5,%6,%7}, {%8,%9}, {%0,%1,%2,%3};"
                 : "+f"(c[0]), "+f"(c[1]), "+f"(c[2]), "+f"(c[3])
                 : "r"(a0), "r"(a1), "r"(a2), "r"(a3), "r"(b0), "r"(b1));
}
__device__ __forceinline__ uint32_t lds32(uint32_t a) {
    uint32_t v; asm volatile("ld.shared.b32 %0, [%1];" : "=r"(v) : "r"(a) : "memory"); return v;
}
__device__ __forceinline__ float ldsf(uint32_t a) {
    float v; asm volatile("ld.shared.f32 %0, [%1];" : "=f"(v) : "r"(a) : "memory"); return v;
}
__device__ __forceinline__ float2 ldsf2(uint32_t a) {
    float2 v; asm volatile("ld.shared.v2.f32 {%0,%1}, [%2];" : "=f"(v.x), "=f"(v.y) : "r"(a) : "memory"); return v;
}
__device__ __forceinline__ float4 ldsf4(uint32_t a) {
    float4 v; asm volatile("ld.shared.v4.f32 {%0,%1,%2,%3}, [%4];" : "=f"(v.x), "=f"(v.y), "=f"(v.z), "=f"(v.w) : "r"(a) : "memory"); return v;
}
__device__ __forceinline__ uint4 lds128(uint32_t a) {
    uint4 v; asm volatile("ld.shared.v4.b32 {%0,%1,%2,%3}, [%4];" : "=r"(v.x), "=r"(v.y), "=r"(v.z), "=r"(v.w) : "r"(a) : "memory"); return v;
}
__device__ __forceinline__ void sts16(uint32_t a, uint16_t v) { asm volatile("st.shared.b16 [%0], %1;" ::"r"(a), "h"(v) : "memory"); }
__device__ __forceinline__ void sts32(uint32_t a, uint32_t v) { asm volatile("st.shared.b32 [%0], %1;" ::"r"(a), "r"(v) : "memory"); }
__device__ __forceinline__ void stsf(uint32_t a, float v) { asm volatile("st.shared.f32 [%0], %1;" ::"r"(a), "f"(v) : "memory"); }
__device__ __forceinline__ void sts64(uint32_t a, uint32_t x, uint32_t y) {
    asm volatile("st.shared.v2.b32 [%0], {%1,%2};" ::"r"(a), "r"(x), "r"(y) : "memory");
}
__device__ __forceinline__ void sts128(uint32_t a, uint4 v) {
    asm volatile("st.shared.v4.b32 [%0], {%1,%2,%3,%4};" ::"r"(a), "r"(v.x), "r"(v.y), "r"(v.z), "r"(v.w) : "memory");
}
__device__ __forceinline__ uint32_t pack_bf16(float lo, float hi) {
    uint32_t r; asm("cvt.rn.bf16x2.f32 %0, %1, %2;" : "=r"(r) : "f"(hi), "f"(lo)); return r;
}
__device__ __forceinline__ float bf_lo(uint32_t v) { return __uint_as_float(v << 16); }
__device__ __forceinline__ float bf_hi(uint32_t v) { return __uint_as_float(v & 0xffff0000u); }
__device__ __forceinline__ float ex2(float x) { float y; asm("ex2.approx.ftz.f32 %0, %1;" : "=f"(y) : "f"(x)); return y; }
__device__ __forceinline__ uint32_t timer_ns() { uint32_t t; asm volatile("mov.u32 %0, %%globaltimer_lo;" : "=r"(t)); return t; }
__device__ __forceinline__ void bar_consumers() { asm volatile("bar.sync 1, 256;" ::: "memory"); }

__device__ __forceinline__ uint32_t tagf(float v, uint32_t tag) { return (__float_as_uint(v) & 0xffffff00u) | tag; }
__device__ __forceinline__ void st_tag2(float* p, float a, float b, uint32_t tag) {
    asm volatile("st.relaxed.gpu.global.v2.b32 [%0], {%1,%2};" ::"l"(p), "r"(tagf(a, tag)), "r"(tagf(b, tag)) : "memory");
}
__device__ __forceinline__ uint2 ld_rlx2(const float* p) {
    uint2 v; asm volatile("ld.relaxed.gpu.global.v2.b32 {%0,%1}, [%2];" : "=r"(v.x), "=r"(v.y) : "l"(p) : "memory"); return v;
}
__device__ __forceinline__ uint4 ld_rlx4(const float* p) {
    uint4 v; asm volatile("ld.relaxed.gpu.global.v4.b32 {%0,%1,%2,%3}, [%4];" : "=r"(v.x), "=r"(v.y), "=r"(v.z), "=r"(v.w) : "l"(p) : "memory"); return v;
}
__device__ __forceinline__ float untag(uint32_t v) { return __uint_as_float(v & 0xffffff00u); }

__device__ __forceinline__ uint32_t slot_off(int item) { return (uint32_t)(item % NSLOT) * SLOT; }

template <bool TRANS, bool RELEASE = true>
__device__ __forceinline__ void tile_mma(uint32_t sb, int item, uint32_t in, int w, int lane, float (&acc)[2][2]) {
    const int g = lane >> 2, t = lane & 3;
    float c[4][4];
#pragma unroll
    for (int i = 0; i < 16; i++) (&c[0][0])[i] = 0.f;
    uint32_t a[16];
    const uint32_t ia = in + (g & 3) * 272 + t * 4;
#pragma unroll
    for (int i = 0; i < 16; i++) a[i] = lds32(ia + i * 16);
    const uint32_t s0 = sb + slot_off(item), s1 = sb + slot_off(item + 1);
    if (TRANS) {
        mbar_wait(sb + SM_FULL + (item + (w >> 2)) * 8);
        const int r = (lane & 7) + (lane & 8);
        const int ch = 2 * (w & 3) + (lane >> 4);
        const uint32_t base = ((w >> 2) ? s1 : s0) + r * 128 + ((ch ^ (lane & 7)) << 4);
#pragma unroll
        for (int kk = 0; kk < 8; kk++) {
            uint32_t r0, r1, r2, r3;
            ldsm4t(base + kk * 2048, r0, r1, r2, r3);
            mma16816(c[2 * (kk & 1)],     a[2 * kk], 0u, a[2 * kk + 1], 0u, r0, r1);
            mma16816(c[2 * (kk & 1) + 1], a[2 * kk], 0u, a[2 * kk + 1], 0u, r2, r3);
        }
    } else {
        mbar_wait(sb + SM_FULL + item * 8);
        mbar_wait(sb + SM_FULL + (item + 1) * 8);
        const int r = 16 * w + (lane & 7) + ((lane >> 4) << 3);
        const uint32_t off = r * 128 + ((((lane >> 3) & 1) ^ (lane & 7)) << 4);
#pragma unroll
        for (int kk = 0; kk < 8; kk++) {
            uint32_t r0, r1, r2, r3;
            ldsm4(((kk >> 2) ? s1 : s0) + (off ^ ((kk & 3) << 5)), r0, r1, r2, r3);
            mma16816(c[2 * (kk & 1)],     a[2 * kk], 0u, a[2 * kk + 1], 0u, r0, r1);
            mma16816(c[2 * (kk & 1) + 1], a[2 * kk], 0u, a[2 * kk + 1], 0u, r2, r3);
        }
    }
    if (RELEASE) {
        __syncwarp();
        if (lane == 0) {
            mbar_arrive(sb + SM_EMPTY + item * 8);
            mbar_arrive(sb + SM_EMPTY + (item + 1) * 8);
        }
    }
    acc[0][0] = c[0][0] + c[2][0]; acc[0][1] = c[0][1] + c[2][1];
    acc[1][0] = c[1][0] + c[3][0]; acc[1][1] = c[1][1] + c[3][1];
}

__device__ __forceinline__ void publish(float* dst, int pitch, int w, int lane, const float (&acc)[2][2], uint32_t tag) {
    if (lane < 16) {
        float* p = dst + (lane >> 2) * pitch + 16 * w + 2 * (lane & 3);
        st_tag2(p, acc[0][0], acc[0][1], tag);
        st_tag2(p + 8, acc[1][0], acc[1][1], tag);
    }
}

__device__ __forceinline__ void gather(const float* part, uint32_t in, int tid, uint32_t tag) {
    const float* p = part + tid * 2;
    uint2 v0, v1, v2, v3;
    int it = 0;
    while (true) {
        v0 = ld_rlx2(p); v1 = ld_rlx2(p + 512); v2 = ld_rlx2(p + 1024); v3 = ld_rlx2(p + 1536);
        uint32_t bad = ((v0.x ^ tag) | (v0.y ^ tag) | (v1.x ^ tag) | (v1.y ^ tag) |
                        (v2.x ^ tag) | (v2.y ^ tag) | (v3.x ^ tag) | (v3.y ^ tag)) & 0xffu;
        if (__all_sync(0xffffffffu, bad == 0)) break;
        if (++it > SPIN_LIMIT) __trap();
    }
    float x = (untag(v0.x) + untag(v1.x)) + (untag(v2.x) + untag(v3.x));
    float y = (untag(v0.y) + untag(v1.y)) + (untag(v2.y) + untag(v3.y));
    sts32(in + (tid >> 6) * 272 + (tid & 63) * 4, pack_bf16(x, y));
    bar_consumers();
}

__device__ __forceinline__ unsigned read_counter(const unsigned* cnt) {
    unsigned v;
    asm volatile("ld.relaxed.gpu.global.u32 %0, [%1];" : "=r"(v) : "l"(cnt) : "memory");
    return v;
}
__device__ __forceinline__ unsigned epoch_of(unsigned cnt) {
    asm volatile("" : "+r"(cnt) :: "memory");
    return cnt / NCTA + 1;
}
__device__ __forceinline__ uint32_t epoch_tag(unsigned epoch) { return (epoch & 0x7fu) | 0x80u; }

__device__ __forceinline__ void signal_and_wait(unsigned* cnt, unsigned target, int lane, uint32_t sb) {
    if (lane == 0) asm volatile("red.release.gpu.global.add.u32 [%0], 1;" ::"l"(cnt) : "memory");
    if (lane == 0) TL(30 + (((size_t)cnt >> 2) & 1));
    int it = 0;
    while (true) {
        unsigned v;
        asm volatile("ld.acquire.gpu.global.u32 %0, [%1];" : "=r"(v) : "l"(cnt) : "memory");
        if (__all_sync(0xffffffffu, (int)(v - target) >= 0)) break;
        if (++it > SPIN_LIMIT) __trap();
    }
    asm volatile("fence.proxy.async.global;" ::: "memory");
}

__device__ __forceinline__ void final_reduce(const float* p, __nv_bfloat16* dst, int lane, uint32_t tag, int part) {
    uint4 v0, v1, v2, v3;
    int it = 0;
    if (lane == 0) TLX(152 + part);
    while (true) {
        v0 = ld_rlx4(p); v1 = ld_rlx4(p + 8 * 2048); v2 = ld_rlx4(p + 16 * 2048); v3 = ld_rlx4(p + 24 * 2048);
        uint32_t bad = ((v0.x ^ tag) | (v0.y ^ tag) | (v0.z ^ tag) | (v0.w ^ tag) |
                        (v1.x ^ tag) | (v1.y ^ tag) | (v1.z ^ tag) | (v1.w ^ tag) |
                        (v2.x ^ tag) | (v2.y ^ tag) | (v2.z ^ tag) | (v2.w ^ tag) |
                        (v3.x ^ tag) | (v3.y ^ tag) | (v3.z ^ tag) | (v3.w ^ tag)) & 0xffu;
        if (__all_sync(0xffffffffu, bad == 0)) break;
        if (++it > SPIN_LIMIT) __trap();
    }
    if (lane == 0) TLX(154 + part);
    float s0 = (untag(v0.x) + untag(v1.x)) + (untag(v2.x) + untag(v3.x));
    float s1 = (untag(v0.y) + untag(v1.y)) + (untag(v2.y) + untag(v3.y));
    float s2 = (untag(v0.z) + untag(v1.z)) + (untag(v2.z) + untag(v3.z));
    float s3 = (untag(v0.w) + untag(v1.w)) + (untag(v2.w) + untag(v3.w));
#pragma unroll
    for (int m = 4; m < 32; m <<= 1) {
        s0 += __shfl_xor_sync(0xffffffffu, s0, m);
        s1 += __shfl_xor_sync(0xffffffffu, s1, m);
        s2 += __shfl_xor_sync(0xffffffffu, s2, m);
        s3 += __shfl_xor_sync(0xffffffffu, s3, m);
    }
    if (lane < 4) *reinterpret_cast<uint2*>(dst) = make_uint2(pack_bf16(s0, s1), pack_bf16(s2, s3));
}

__global__ void __launch_bounds__(NTHR, 1)
fused_decode_kernel(const __nv_bfloat16* __restrict__ xA, const __nv_bfloat16* __restrict__ xB,
                    const __nv_bfloat16* __restrict__ Kc, const __nv_bfloat16* __restrict__ Vc,
                    __nv_bfloat16* __restrict__ out, Scratch* gs, const __grid_constant__ Maps maps) {
    extern __shared__ __align__(1024) unsigned char smem_raw[];
    const uint32_t sb = smem_u32(smem_raw);
    const int tid = threadIdx.x, lane = tid & 31;
    const int cta = blockIdx.x, h = cta >> 2, j = cta & 3;
    const size_t kv_off = ((size_t)(j * 32 + h) * 4096 + 3072) * 128;
    uint64_t pol;
    asm volatile("createpolicy.fractional.L2::evict_first.b64 %0, 1.0;" : "=l"(pol));
    const unsigned cnt1 = read_counter(&gs->cnt[1]);
    uint4 xv;
    if (tid < 128) {
        const __nv_bfloat16* x = (tid < 64 ? xB : xA) + ((tid >> 4) & 3) * 512 + j * 128 + (tid & 15) * 8;
        xv = __ldg(reinterpret_cast<const uint4*>(x));
    }
    if (tid == STARTER) {
        TLX(0);
        asm volatile("cp.async.bulk.prefetch.L2.global [%0], %1;" ::"l"(Kc + kv_off), "r"(SLOT) : "memory");
#pragma unroll
        for (int i = 0; i < 2; i++) mbar_init(sb + SM_FULL + i * 8, 1);
        asm volatile("fence.mbarrier_init.release.cluster;" ::: "memory");
#pragma unroll
        for (int i = 0; i < 2; i++) {
            TLX(32 + i);
            mbar_expect_tx(sb + SM_FULL + i * 8, SLOT);
            tma2d(sb + i * SLOT, &maps.wqB, h * 128 + i * 64, j * 128, sb + SM_FULL + i * 8, pol);
        }
    }
    uint32_t tnext = timer_ns() + 3 * PACE - OFFS + STAG * cta * PACE / NCTA;
    if (tid == 0) TLX(21);
    const int w = __shfl_sync(0xffffffffu, tid >> 5, 0);

    if (w >= 8) {
        if (w == 8) {
            asm volatile(BAR2 ::: "memory");
            int slot = 2, tail = 2 - INFLIGHT;
#pragma unroll 1
            for (int i = 2; i < NITEM; i++) {
                const uint32_t dst = sb + slot * SLOT, bar = sb + SM_FULL + i * 8;
                if (++slot == NSLOT) slot = 0;
                if ((i & ~1) == IT_Q || (i & ~1) == IT_OP) continue;
                const bool wt = i < IT_K0 || (i & ~1) == IT_WUV || i >= IT_WOB;
                if (i >= NSLOT) mbar_wait(sb + SM_EMPTY + (i - NSLOT) * 8);
                if (tail >= 0) mbar_wait(sb + SM_FULL + tail * 8);
                ++tail;
                if (tail == IT_Q || tail == IT_OP) tail += 2;
                if (!(wt && (i & 1)) && i != IT_K0) {
                    while (__all_sync(0xffffffffu, (int)(timer_ns() - tnext) < 0)) {}
                    tnext += wt ? 2 * PACE : PACE;
                }
                if (lane == 0) TLX(32 + i);
                if (wt) {
                    const bool wo = i >= IT_WOB;
                    const CUtensorMap* tm = &maps.wqB + (i < IT_K0 ? (i >> 1) : wo ? (i - IT_WOB + 8) >> 1 : 3);
                    if (lane == 0) tma2d(dst, tm, (wo ? j : h) * 128 + (i & 1) * 64, (wo ? h : j) * 128, bar, pol);
                } else if (i >= IT_C && i < IT_K1) {
                    if (lane == 0) tma3d(dst, &maps.ckv, 0, cta * 128 + (i - IT_C) * 16, 0, bar, pol);
                } else {
                    const __nv_bfloat16* src = (i < IT_V0 ? Kc : Vc) + kv_off;
                    const int c = i < IT_Q ? i - IT_K0 : i < IT_V0 ? i - IT_K1 + 8 : i < IT_OP ? i - IT_V0 : i - IT_V1 + 8;
                    if (lane == 0) bulk_load(dst, src + (size_t)c * (SLOT / 2), SLOT, bar, pol);
                }
            }
            if (lane == 0) TL(1);
        } else {
            if (lane < 6) asm volatile("prefetch.tensormap [%0];" ::"l"(&maps.wqA + lane) : "memory");
            asm volatile(BAR2 ::: "memory");
            asm volatile("bar.sync 3, 288;" ::: "memory");
            const unsigned epoch = epoch_of(cnt1);
            if (lane == 0) TL(9);
            signal_and_wait(&gs->cnt[0], epoch * NCTA, lane, sb);
            if (lane == 0) {
                TL(2);
                const uint4* q = gs->q[cta >> 5];
                bulk_load_nohint(sb + slot_off(IT_Q), q, SLOT, sb + SM_FULL + IT_Q * 8);
                bulk_load_nohint(sb + slot_off(IT_Q + 1), q + 1024, SLOT, sb + SM_FULL + (IT_Q + 1) * 8);
            }
            asm volatile("bar.sync 3, 288;" ::: "memory");
            if (lane == 0) TL(13);
            signal_and_wait(&gs->cnt[1], epoch * NCTA, lane, sb);
            mbar_wait(sb + SM_EMPTY + (IT_OP - NSLOT) * 8);
            mbar_wait(sb + SM_EMPTY + (IT_OP + 1 - NSLOT) * 8);
            if (lane == 0) {
                TL(3);
                const uint4* op = gs->op[cta];
                bulk_load_nohint(sb + SM_MX, gs->stat[h], 1024, sb + SM_FULL + IT_OP * 8);
                bulk_load_nohint(sb + slot_off(IT_OP), op, SLOT, sb + SM_FULL + IT_OP * 8);
                bulk_load_nohint(sb + slot_off(IT_OP + 1), op + 1024, SLOT, sb + SM_FULL + (IT_OP + 1) * 8);
            }
        }
        __syncwarp();
        const int part = 9 - w, b = cta >> 5, col0 = 16 * (cta & 31) + 4 * (lane & 3);
        mbar_wait(sb + SM_FULL + (IT_WOB + 2 * part) * 8);
        final_reduce(&gs->fin[part][lane >> 2][b][col0], out + b * 1024 + (part == 0 ? 512 : 0) + col0, lane, epoch_tag(epoch_of(cnt1)), part);
        if (lane == 0) TL(4 + part);
        return;
    }

    const int g = lane >> 2, t = lane & 3;
    const uint32_t in0 = sb + SM_IN0, in1 = sb + SM_IN1;
    {
        if (lane == 0) {
            const uint32_t bars = sb + (w < 4 ? SM_EMPTY : SM_FULL + 2 * 8) + (w & 3) * 14 * 8;
            const uint32_t cnt = w < 4 ? 8 : 1;
#pragma unroll
            for (int i = 0; i < 14; i++) mbar_init(bars + i * 8, cnt);
            if (w >= 4) {
#pragma unroll
                for (int i = 0; i < 14; i++)
                    mbar_expect_tx(bars + i * 8, (i == (IT_OP - 2) % 14 && w == 4 + (IT_OP - 2) / 14) ? SLOT + 1024 : SLOT);
            }
            asm volatile("fence.mbarrier_init.release.cluster;" ::: "memory");
        }
        if (tid == 0) TL(22);
        asm volatile(BAR2 ::: "memory");
        const float zero[2][2] = {{0.f, 0.f}, {0.f, 0.f}};
        publish(gs->part[0][cta], 128, w, lane, zero, 0u);
        publish(gs->part[1][cta], 128, w, lane, zero, 0u);
        publish(gs->part[2][cta], 128, w, lane, zero, 0u);
        publish(&gs->fin[0][h][0][j * 128], 512, w, lane, zero, 0u);
        publish(&gs->fin[1][h][0][j * 128], 512, w, lane, zero, 0u);
        if (tid < 64) st_tag2(gs->part[3][h * 4] + j * 128 + tid * 2, 0.f, 0.f, 0u);
        if (tid < 128) sts128((tid < 64 ? in0 : in1) + ((tid >> 4) & 3) * 272 + (tid & 15) * 16, xv);
    }
    bar_consumers();
    const uint32_t tag = epoch_tag(epoch_of(cnt1));
    if (tid == 0) TL(23);

    float acc[2][2];
    tile_mma<true>(sb, IT_WQB, in0, w, lane, acc);
    if (tid == 0) TL(24);
    publish(gs->part[0][cta], 128, w, lane, acc, tag);
    if (tid == 0) TL(6);
    tile_mma<true>(sb, IT_WQA, in1, w, lane, acc);
    publish(gs->part[1][cta], 128, w, lane, acc, tag);
    if (tid == 0) TL(7);
    bar_consumers();

    const float SC = 0.08838834764831845f * 1.4426950408889634f;
    gather(gs->part[0][h * 4], in0, tid, tag);
    if (tid == 0) TL(8);
    tile_mma<false>(sb, IT_WUK, in0, w, lane, acc);
    if (tid == 0) TL(25);
    if (lane < 16) {
        uint32_t* q = reinterpret_cast<uint32_t*>(gs->q[g]) + (2 * j + (w >> 2)) * 1024 + h * 32 + t;
        const int ch = 2 * (w & 3);
        q[((ch) ^ (h & 7)) * 4]     = pack_bf16(acc[0][0] * SC, acc[0][1] * SC);
        q[((ch + 1) ^ (h & 7)) * 4] = pack_bf16(acc[1][0] * SC, acc[1][1] * SC);
    }
    __syncwarp();
    asm volatile("bar.arrive 3, 288;" ::: "memory");
    gather(gs->part[1][h * 4], in1, tid, tag);
    if (tid == 0) TL(28);

    uint32_t qf[16];
#pragma unroll
    for (int c = 0; c < 8; c++) {
        qf[2 * c]     = lds32(in1 + j * 272 + ((c ^ g) << 4) + t * 4);
        qf[2 * c + 1] = lds32(in1 + j * 272 + 128 + ((c ^ g) << 4) + t * 4);
    }
    const uint32_t sc_w = sb + SM_SC + w * 512;
    auto k_item = [&](int item, uint32_t sc) {
        mbar_wait(sb + SM_FULL + item * 8);
        const uint32_t base = sb + slot_off(item) + ((lane & 7) + (lane & 8)) * 256 + ((lane >> 4) << 7);
        float s[4][4];
#pragma unroll
        for (int T = 0; T < 4; T++) { s[T][0] = s[T][1] = s[T][2] = s[T][3] = 0.f; }
#pragma unroll
        for (int c = 0; c < 8; c++) {
            const uint32_t a = base + ((c ^ (lane & 7)) << 4);
#pragma unroll
            for (int T = 0; T < 4; T++) {
                uint32_t r0, r1, r2, r3;
                ldsm4(a + T * 4096, r0, r1, r2, r3);
                mma16816(s[T], r0, r1, r2, r3, qf[2 * c], qf[2 * c + 1]);
            }
        }
        __syncwarp();
        if (lane == 0) mbar_arrive8(sb + SM_EMPTY + item * 8);
        if (t == (g >> 1)) {
#pragma unroll
            for (int T = 0; T < 4; T++) {
                stsf(sc + (16 * T + g) * 4,     (g & 1) ? s[T][1] : s[T][0]);
                stsf(sc + (16 * T + g + 8) * 4, (g & 1) ? s[T][3] : s[T][2]);
            }
        }
    };
    k_item(IT_K0 + w, sc_w);
    if (tid == 224) TL(10);

    {
        float s[2][2][4];
#pragma unroll
        for (int i = 0; i < 16; i++) (&s[0][0][0])[i] = 0.f;
        mbar_wait(sb + SM_FULL + IT_Q * 8);
        mbar_wait(sb + SM_FULL + (IT_Q + 1) * 8);
        if (tid == 0) TLX(96 + IT_Q);
        mbar_wait(sb + SM_FULL + (IT_C + w) * 8);
        const uint32_t cb0 = sb + slot_off(IT_C + w) + ((lane & 7) + ((lane >> 4) << 3)) * 128;
        const uint32_t cx = (((lane >> 3) & 1) ^ (lane & 7)) << 4;
        const uint32_t qr = ((lane & 7) + (lane & 8)) * 128;
        const uint32_t qx = ((lane >> 4) ^ (lane & 7)) << 4;
#pragma unroll
        for (int cb = 0; cb < 8; cb++) {
            const uint32_t qb = sb + slot_off(IT_Q + (cb >> 2)) + (cb & 3) * 4096 + qr;
#pragma unroll
            for (int k4 = 0; k4 < 4; k4++) {
                uint32_t b0, b1, b2, b3, a0, a1, a2, a3;
                ldsm4(cb0 + cb * 2048 + (cx ^ (k4 << 5)), b0, b1, b2, b3);
                ldsm4(qb + (qx ^ (k4 << 5)), a0, a1, a2, a3);
                mma16816(s[0][0], a0, a1, a2, a3, b0, b1);
                mma16816(s[0][1], a0, a1, a2, a3, b2, b3);
                ldsm4(qb + 2048 + (qx ^ (k4 << 5)), a0, a1, a2, a3);
                mma16816(s[1][0], a0, a1, a2, a3, b0, b1);
                mma16816(s[1][1], a0, a1, a2, a3, b2, b3);
            }
        }
        __syncwarp();
        if (lane == 0) { mbar_arrive(sb + SM_EMPTY + IT_Q * 8); mbar_arrive(sb + SM_EMPTY + (IT_Q + 1) * 8); }
#pragma unroll
        for (int r = 0; r < 4; r++) {
            const int mt = r >> 1, hi = (r & 1) * 2;
            float m = fmaxf(fmaxf(s[mt][0][hi], s[mt][0][hi + 1]), fmaxf(s[mt][1][hi], s[mt][1][hi + 1]));
            m = fmaxf(m, __shfl_xor_sync(0xffffffffu, m, 1));
            m = fmaxf(m, __shfl_xor_sync(0xffffffffu, m, 2));
            if (t == 0) stsf(sb + SM_MX + (8 * r + g) * 32 + w * 4, m);
        }
        bar_consumers();
        if (tid == 0) TL(11);
        uint32_t pf[2][4];
#pragma unroll
        for (int r = 0; r < 4; r++) {
            const int mt = r >> 1, hi = r & 1;
            const float4 m0 = ldsf4(sb + SM_MX + (8 * r + g) * 32), m1 = ldsf4(sb + SM_MX + (8 * r + g) * 32 + 16);
            const float m = fmaxf(fmaxf(fmaxf(m0.x, m0.y), fmaxf(m0.z, m0.w)), fmaxf(fmaxf(m1.x, m1.y), fmaxf(m1.z, m1.w)));
            const uint32_t p0 = pack_bf16(ex2(s[mt][0][2 * hi] - m), ex2(s[mt][0][2 * hi + 1] - m));
            const uint32_t p1 = pack_bf16(ex2(s[mt][1][2 * hi] - m), ex2(s[mt][1][2 * hi + 1] - m));
            pf[mt][hi] = p0; pf[mt][2 + hi] = p1;
            float l = (bf_lo(p0) + bf_hi(p0)) + (bf_lo(p1) + bf_hi(p1));
            l += __shfl_xor_sync(0xffffffffu, l, 1);
            l += __shfl_xor_sync(0xffffffffu, l, 2);
            if (t == 0) stsf(sb + SM_SUM + (8 * r + g) * 32 + w * 4, l);
        }
        sts128(sb + SM_PF + (w * 2 + 0) * 512 + lane * 16, make_uint4(pf[0][0], pf[0][1], pf[0][2], pf[0][3]));
        sts128(sb + SM_PF + (w * 2 + 1) * 512 + lane * 16, make_uint4(pf[1][0], pf[1][1], pf[1][2], pf[1][3]));
        bar_consumers();
        if (w == 0) {
            const float4 m0 = ldsf4(sb + SM_MX + lane * 32), m1 = ldsf4(sb + SM_MX + lane * 32 + 16);
            const float4 l0 = ldsf4(sb + SM_SUM + lane * 32), l1 = ldsf4(sb + SM_SUM + lane * 32 + 16);
            const float m = fmaxf(fmaxf(fmaxf(m0.x, m0.y), fmaxf(m0.z, m0.w)), fmaxf(fmaxf(m1.x, m1.y), fmaxf(m1.z, m1.w)));
            const float l = ((l0.x + l0.y) + (l0.z + l0.w)) + ((l1.x + l1.y) + (l1.z + l1.w));
            gs->stat[lane][cta] = make_float2(m, l);
        }
        float o[2][8][4];
#pragma unroll
        for (int i = 0; i < 64; i++) (&o[0][0][0])[i] = 0.f;
        const uint32_t vr = w * 2048 + ((lane & 7) + (lane & 8)) * 128;
        const uint32_t vx = ((lane >> 4) ^ (lane & 7)) << 4;
#pragma unroll
        for (int ks = 0; ks < 8; ks++) {
            const uint4 p0 = lds128(sb + SM_PF + (ks * 2 + 0) * 512 + lane * 16);
            const uint4 p1 = lds128(sb + SM_PF + (ks * 2 + 1) * 512 + lane * 16);
            const uint32_t vb = sb + slot_off(IT_C + ks) + vr;
#pragma unroll
            for (int n2 = 0; n2 < 4; n2++) {
                uint32_t b0, b1, b2, b3;
                ldsm4t(vb + (vx ^ (n2 << 5)), b0, b1, b2, b3);
                mma16816(o[0][2 * n2],     p0.x, p0.y, p0.z, p0.w, b0, b1);
                mma16816(o[0][2 * n2 + 1], p0.x, p0.y, p0.z, p0.w, b2, b3);
                mma16816(o[1][2 * n2],     p1.x, p1.y, p1.z, p1.w, b0, b1);
                mma16816(o[1][2 * n2 + 1], p1.x, p1.y, p1.z, p1.w, b2, b3);
            }
            __syncwarp();
            if (lane == 0) mbar_arrive(sb + SM_EMPTY + (IT_C + ks) * 8);
        }
        if (tid == 0) TL(12);
        mbar_wait(sb + SM_FULL + (IT_K1 + 2 + (w >> 1)) * 8);
#pragma unroll
        for (int r = 0; r < 4; r++) {
            const int mt = r >> 1, hi = (r & 1) * 2;
            uint4* dst = gs->op[(8 * r + g) * 4 + (w >> 1)] + (w & 1) * 1024 + cta * 8;
#pragma unroll
            for (int u = 0; u < 2; u++) {
                uint4 v;
                v.x = pack_bf16(o[mt][4 * u][hi],     o[mt][4 * u][hi + 1]);
                v.y = pack_bf16(o[mt][4 * u + 1][hi], o[mt][4 * u + 1][hi + 1]);
                v.z = pack_bf16(o[mt][4 * u + 2][hi], o[mt][4 * u + 2][hi + 1]);
                v.w = pack_bf16(o[mt][4 * u + 3][hi], o[mt][4 * u + 3][hi + 1]);
                dst[(t + 4 * u) ^ (cta & 7)] = v;
            }
        }
        if (tid == 0) TL(29);
        asm volatile("bar.arrive 3, 288;" ::: "memory");
    }

    k_item(IT_K1 + w, sc_w + 256);
    __syncwarp();
    {
        const float4 s = ldsf4(sc_w + lane * 16);
        float m = fmaxf(fmaxf(s.x, s.y), fmaxf(s.z, s.w));
#pragma unroll
        for (int d = 1; d < 32; d <<= 1) m = fmaxf(m, __shfl_xor_sync(0xffffffffu, m, d));
        if (lane == 0) stsf(sb + SM_ML + w * 4, m);
        bar_consumers();
        const float4 m0 = ldsf4(sb + SM_ML), m1 = ldsf4(sb + SM_ML + 16);
        m = fmaxf(fmaxf(fmaxf(m0.x, m0.y), fmaxf(m0.z, m0.w)), fmaxf(fmaxf(m1.x, m1.y), fmaxf(m1.z, m1.w))) * SC;
        const uint32_t p0 = pack_bf16(ex2(fmaf(s.x, SC, -m)), ex2(fmaf(s.y, SC, -m)));
        const uint32_t p1 = pack_bf16(ex2(fmaf(s.z, SC, -m)), ex2(fmaf(s.w, SC, -m)));
        float l = (bf_lo(p0) + bf_hi(p0)) + (bf_lo(p1) + bf_hi(p1));
#pragma unroll
        for (int d = 1; d < 32; d <<= 1) l += __shfl_xor_sync(0xffffffffu, l, d);
        if (lane == 0) stsf(sb + SM_ML + 32 + w * 4, l);
        sts64(sb + SM_PA + w * 256 + lane * 8, p0, p1);
        __syncwarp();
    }
    if (tid == 224) TL(14);

    float oa[4][4];
#pragma unroll
    for (int i = 0; i < 16; i++) (&oa[0][0])[i] = 0.f;
    auto v_item = [&](int item, uint32_t pa) {
        uint32_t p[8];
#pragma unroll
        for (int i = 0; i < 8; i++) p[i] = lds32(pa + i * 16 + t * 4);
        mbar_wait(sb + SM_FULL + item * 8);
        const uint32_t base = sb + slot_off(item) + ((lane & 7) + ((lane >> 4) << 3)) * 256 + ((lane & 8) << 4);
#pragma unroll
        for (int c = 0; c < 8; c++) {
            const uint32_t a = base + ((c ^ (lane & 7)) << 4);
            const uint32_t mask = ((c == (g ^ (2 * t))) ? 0x0000ffffu : 0u) | ((c == (g ^ (2 * t + 1))) ? 0xffff0000u : 0u);
#pragma unroll
            for (int T = 0; T < 4; T++) {
                uint32_t r0, r1, r2, r3;
                ldsm4t(a + T * 4096, r0, r1, r2, r3);
                mma16816(oa[T], r0, r1, r2, r3, p[2 * T] & mask, p[2 * T + 1] & mask);
            }
        }
        __syncwarp();
        if (lane == 0) mbar_arrive8(sb + SM_EMPTY + item * 8);
    };
    v_item(IT_V0 + w, sb + SM_PA + w * 256);
    if (tid == 224) TL(15);

    mbar_wait(sb + SM_FULL + IT_OP * 8);
    if (tid == 0) TLX(96 + IT_OP);
    if (w < 4) {
        const float2 st = ldsf2(sb + SM_MX + tid * 8);
        float m = st.x;
#pragma unroll
        for (int d = 1; d < 32; d <<= 1) m = fmaxf(m, __shfl_xor_sync(0xffffffffu, m, d));
        const uint32_t wb = pack_bf16(ex2(st.x - m), 0.f);
        float l = bf_lo(wb) * st.y;
#pragma unroll
        for (int d = 1; d < 32; d <<= 1) l += __shfl_xor_sync(0xffffffffu, l, d);
#pragma unroll
        for (int bb = 0; bb < 4; bb++) sts16(in0 + bb * 272 + tid * 2, bb == w ? (uint16_t)wb : (uint16_t)0);
        if (lane == 0) stsf(sb + SM_ML + 64 + w * 4, 1.f / l);
    }
    bar_consumers();
    tile_mma<true>(sb, IT_OP, in0, w, lane, acc);
    if (lane < 16) {
        const float inv = ldsf(sb + SM_ML + 64 + g * 4);
        const int ch = 2 * (w & 3);
        const uint32_t dst = in1 + g * 272 + ((w >> 2) * 64 + 8 * (4 * (ch >> 2) + t)) * 2;
        sts32(dst + (ch & 3) * 4,       pack_bf16(acc[0][0] * inv, acc[0][1] * inv));
        sts32(dst + ((ch + 1) & 3) * 4, pack_bf16(acc[1][0] * inv, acc[1][1] * inv));
    }
    bar_consumers();
    tile_mma<true>(sb, IT_WUV, in1, w, lane, acc);
    publish(gs->part[2][cta], 128, w, lane, acc, tag);
    if (tid == 0) TL(16);
    mbar_wait(sb + SM_FULL + (IT_V1 + CTXWAIT) * 8);
    if (tid == 0) TLX(27);
    gather(gs->part[2][h * 4], in0, tid, tag);
    if (tid == 0) TL(18);

    {
        const float4 l0 = ldsf4(sb + SM_ML + 32), l1 = ldsf4(sb + SM_ML + 48);
        const float inv = 1.f / (((l0.x + l0.y) + (l0.z + l0.w)) + ((l1.x + l1.y) + (l1.z + l1.w)));
        v_item(IT_V1 + w, sb + SM_PA + w * 256 + 128);
        const uint32_t so = sb + SM_PF + w * 512 + (16 * t + g) * 4;
        stsf(so,       (oa[0][0] + oa[1][0]) + (oa[2][0] + oa[3][0]));
        stsf(so + 32,  (oa[0][1] + oa[1][1]) + (oa[2][1] + oa[3][1]));
        stsf(so + 256, (oa[0][2] + oa[1][2]) + (oa[2][2] + oa[3][2]));
        stsf(so + 288, (oa[0][3] + oa[1][3]) + (oa[2][3] + oa[3][3]));
        bar_consumers();
        if (tid < 64) {
            float x = 0.f, y = 0.f;
#pragma unroll
            for (int i = 0; i < 8; i++) {
                const float2 v = ldsf2(sb + SM_PF + i * 512 + tid * 8);
                x += v.x; y += v.y;
            }
            st_tag2(gs->part[3][h * 4] + j * 128 + tid * 2, x * inv, y * inv, tag);
        }
    }
    if (tid == 0) TL(17);

    tile_mma<true, false>(sb, IT_WOB, in0, w, lane, acc);
    publish(&gs->fin[0][h][0][j * 128], 512, w, lane, acc, tag);
    if (tid == 224) TL(19);
    {
        const float* p = gs->part[3][h * 4] + tid * 2;
        uint2 v;
        int it = 0;
        while (true) {
            v = ld_rlx2(p);
            if (__all_sync(0xffffffffu, (((v.x ^ tag) | (v.y ^ tag)) & 0xffu) == 0)) break;
            if (++it > SPIN_LIMIT) __trap();
        }
        sts32(in1 + (tid >> 6) * 272 + (tid & 63) * 4, pack_bf16(untag(v.x), untag(v.y)));
        bar_consumers();
    }
    if (tid == 0) TL(20);
    tile_mma<true, false>(sb, IT_WOA, in1, w, lane, acc);
    publish(&gs->fin[1][h][0][j * 128], 512, w, lane, acc, tag);
    if (tid == 224) TL(26);
}

typedef CUresult (*EncodeTiledFn)(CUtensorMap*, CUtensorMapDataType, cuuint32_t, void*, const cuuint64_t*,
                                  const cuuint64_t*, const cuuint32_t*, const cuuint32_t*, CUtensorMapInterleave,
                                  CUtensorMapSwizzle, CUtensorMapL2promotion, CUtensorMapFloatOOBfill);

void encode_weight(EncodeTiledFn enc, CUtensorMap* tm, const void* p, cuuint64_t cols, cuuint64_t rows) {
    cuuint64_t dims[2] = {cols, rows};
    cuuint64_t strides[1] = {cols * 2};
    cuuint32_t box[2] = {64, 128};
    cuuint32_t es[2] = {1, 1};
    enc(tm, CU_TENSOR_MAP_DATA_TYPE_BFLOAT16, 2, const_cast<void*>(p), dims, strides, box, es,
        CU_TENSOR_MAP_INTERLEAVE_NONE, CU_TENSOR_MAP_SWIZZLE_128B, CU_TENSOR_MAP_L2_PROMOTION_L2_256B,
        CU_TENSOR_MAP_FLOAT_OOB_FILL_NONE);
}

}

extern "C" void kernel_launch(void* const* d_in, const int* in_sizes, int n_in, void* d_out, int out_size) {
    (void)in_sizes; (void)n_in; (void)out_size;
    static EncodeTiledFn enc = nullptr;
    static Scratch* gs = nullptr;
    if (!enc) {
        cudaGetSymbolAddress((void**)&gs, g_scratch);
        void* fn = nullptr;
        cudaDriverEntryPointQueryResult qr;
        cudaGetDriverEntryPoint("cuTensorMapEncodeTiled", &fn, cudaEnableDefault, &qr);
        enc = (EncodeTiledFn)fn;
        cudaFuncSetAttribute(fused_decode_kernel, cudaFuncAttributeMaxDynamicSharedMemorySize, SM_END);
    }
    Maps maps;
    encode_weight(enc, &maps.wqB, d_in[7], 4096, 512);
    encode_weight(enc, &maps.wqA, d_in[3], 4096, 512);
    encode_weight(enc, &maps.wuk, d_in[8], 4096, 512);
    encode_weight(enc, &maps.wuv, d_in[9], 4096, 512);
    encode_weight(enc, &maps.woB, d_in[10], 512, 4096);
    encode_weight(enc, &maps.woA, d_in[4], 512, 4096);
    {
        cuuint64_t dims[3] = {64, 16384, 8};
        cuuint64_t strides[2] = {1024, 128};
        cuuint32_t box[3] = {64, 16, 8};
        cuuint32_t es[3] = {1, 1, 1};
        enc(&maps.ckv, CU_TENSOR_MAP_DATA_TYPE_BFLOAT16, 3, d_in[6], dims, strides, box, es,
            CU_TENSOR_MAP_INTERLEAVE_NONE, CU_TENSOR_MAP_SWIZZLE_128B, CU_TENSOR_MAP_L2_PROMOTION_L2_256B,
            CU_TENSOR_MAP_FLOAT_OOB_FILL_NONE);
    }
    fused_decode_kernel<<<NCTA, NTHR, SM_END>>>((const __nv_bfloat16*)d_in[0], (const __nv_bfloat16*)d_in[5],
                                                (const __nv_bfloat16*)d_in[1], (const __nv_bfloat16*)d_in[2],
                                                (__nv_bfloat16*)d_out, gs, maps);
}
```

```cpp
#include <cuda_runtime.h>
#include <cuda_bf16.h>
#include <cuda.h>
#include <stdint.h>

namespace {

constexpr int NCTA   = 128;
constexpr int NSLOT  = 13;
constexpr int SLOT   = 16384;
constexpr int NITEM  = 56;
#define INFLIGHT 4
#define PACE 650
#define OFFS 500
#define STAG 0
#define OWAIT 0
#define FINMODE 1
#define FINDELAY 0
#define NFIRST 2
#define STARTER 256
#define CTXWAIT 2
constexpr int NTHR   = 320;
#define BAR2 "bar.sync 2, 320;"

constexpr int IT_WQB = 0, IT_WQA = 2, IT_WUK = 4, IT_K0 = 6, IT_Q = 14, IT_C = 16, IT_K1 = 24, IT_V0 = 32,
              IT_OP = 40, IT_WUV = 42, IT_V1 = 44, IT_WOB = 52, IT_WOA = 54;

constexpr int SM_FULL  = NSLOT * SLOT;
constexpr int SM_EMPTY = SM_FULL + 512;
constexpr int SM_IN0   = SM_EMPTY + 512;
constexpr int SM_IN1   = SM_IN0 + 1088;
constexpr int SM_SC    = SM_IN1 + 1088;
constexpr int SM_PA    = SM_SC + 4096;
constexpr int SM_PF    = SM_PA + 2048;
constexpr int SM_MX    = SM_PF + 8192;
constexpr int SM_ML    = SM_MX + 1024;
constexpr int SM_END   = SM_ML + 128;
constexpr int SM_SUM   = SM_IN0;
static_assert(SM_END <= 232448, "smem");

struct Maps { CUtensorMap wqB, wqA, wuk, wuv, woB, woA, ckv; };

struct Scratch {
    unsigned cnt[32];
    float    part[4][NCTA][512];
    float    fin[2][32][4][512];
    uint4    q[4][2048];
    uint4    op[NCTA][2048];
    float2   stat[32][128];
};
__device__ __align__(128) Scratch g_scratch;
#define TLX(i) do {} while (0)
#define TL(i) do {} while (0)

constexpr int SPIN_LIMIT = 1 << 22;

__device__ __forceinline__ uint32_t smem_u32(const void* p) { return (uint32_t)__cvta_generic_to_shared(p); }
__device__ __forceinline__ void mbar_init(uint32_t bar, uint32_t cnt) {
    asm volatile("mbarrier.init.shared::cta.b64 [%0], %1;" ::"r"(bar), "r"(cnt) : "memory");
}
__device__ __forceinline__ void mbar_expect_tx(uint32_t bar, uint32_t bytes) {
    asm volatile("mbarrier.arrive.expect_tx.shared::cta.b64 _, [%0], %1;" ::"r"(bar), "r"(bytes) : "memory");
}
__device__ __forceinline__ void mbar_arrive(uint32_t bar) {
    asm volatile("mbarrier.arrive.shared::cta.b64 _, [%0];" ::"r"(bar) : "memory");
}
__device__ __forceinline__ void mbar_arrive8(uint32_t bar) {
    asm volatile("mbarrier.arrive.shared::cta.b64 _, [%0], 8;" ::"r"(bar) : "memory");
}
__device__ __forceinline__ void mbar_wait(uint32_t bar) {
    uint32_t done;
    int it = 0;
    do {
        asm volatile("{\n.reg .pred p;\nmbarrier.try_wait.parity.shared::cta.b64 p, [%1], 0;\nselp.u32 %0, 1, 0, p;\n}"
                     : "=r"(done) : "r"(bar) : "memory");
        if (++it > SPIN_LIMIT) __trap();
    } while (!done);
}
__device__ __forceinline__ void bulk_load(uint32_t dst, const void* src, uint32_t bytes, uint32_t bar, uint64_t pol) {
    asm volatile("cp.async.bulk.shared::cluster.global.mbarrier::complete_tx::bytes.L2::cache_hint [%0], [%1], %2, [%3], %4;"
                 ::"r"(dst), "l"(src), "r"(bytes), "r"(bar), "l"(pol) : "memory");
}
__device__ __forceinline__ void bulk_load_nohint(uint32_t dst, const void* src, uint32_t bytes, uint32_t bar) {
    asm volatile("cp.async.bulk.shared::cluster.global.mbarrier::complete_tx::bytes [%0], [%1], %2, [%3];"
                 ::"r"(dst), "l"(src), "r"(bytes), "r"(bar) : "memory");
}
__device__ __forceinline__ void tma3d(uint32_t dst, const CUtensorMap* tm, int c0, int c1, int c2, uint32_t bar, uint64_t pol) {
    asm volatile("cp.async.bulk.tensor.3d.shared::cluster.global.mbarrier::complete_tx::bytes.L2::cache_hint [%0], [%1, {%3, %4, %5}], [%2], %6;"
                 ::"r"(dst), "l"(tm), "r"(bar), "r"(c0), "r"(c1), "r"(c2), "l"(pol) : "memory");
}
__device__ __forceinline__ void ldsm4(uint32_t a, uint32_t& r0, uint32_t& r1, uint32_t& r2, uint32_t& r3) {
    asm volatile("ldmatrix.sync.aligned.m8n8.x4.shared.b16 {%0,%1,%2,%3}, [%4];"
                 : "=r"(r0), "=r"(r1), "=r"(r2), "=r"(r3) : "r"(a) : "memory");
}
__device__ __forceinline__ void ldsm4t(uint32_t a, uint32_t& r0, uint32_t& r1, uint32_t& r2, uint32_t& r3) {
    asm volatile("ldmatrix.sync.aligned.m8n8.x4.trans.shared.b16 {%0,%1,%2,%3}, [%4];"
                 : "=r"(r0), "=r"(r1), "=r"(r2), "=r"(r3) : "r"(a) : "memory");
}
__device__ __forceinline__ void mma16816(float (&c)[4], uint32_t a0, uint32_t a1, uint32_t a2, uint32_t a3,
                                         uint32_t b0, uint32_t b1) {
    asm volatile("mma.sync.aligned.m16n8k16.row.col.f32.bf16.bf16.f32 {%0,%1,%2,%3}, {%4,%5,%6,%7}, {%8,%9}, {%0,%1,%2,%3};"
                 : "+f"(c[0]), "+f"(c[1]), "+f"(c[2]), "+f"(c[3])
                 : "r"(a0), "r"(a1), "r"(a2), "r"(a3), "r"(b0), "r"(b1));
}
__device__ __forceinline__ uint32_t lds32(uint32_t a) {
    uint32_t v; asm volatile("ld.shared.b32 %0, [%1];" : "=r"(v) : "r"(a) : "memory"); return v;
}
__device__ __forceinline__ float ldsf(uint32_t a) {
    float v; asm volatile("ld.shared.f32 %0, [%1];" : "=f"(v) : "r"(a) : "memory"); return v;
}
__device__ __forceinline__ float2 ldsf2(uint32_t a) {
    float2 v; asm volatile("ld.shared.v2.f32 {%0,%1}, [%2];" : "=f"(v.x), "=f"(v.y) : "r"(a) : "memory"); return v;
}
__device__ __forceinline__ float4 ldsf4(uint32_t a) {
    float4 v; asm volatile("ld.shared.v4.f32 {%0,%1,%2,%3}, [%4];" : "=f"(v.x), "=f"(v.y), "=f"(v.z), "=f"(v.w) : "r"(a) : "memory"); return v;
}
__device__ __forceinline__ uint4 lds128(uint32_t a) {
    uint4 v; asm volatile("ld.shared.v4.b32 {%0,%1,%2,%3}, [%4];" : "=r"(v.x), "=r"(v.y), "=r"(v.z), "=r"(v.w) : "r"(a) : "memory"); return v;
}
__device__ __forceinline__ void sts16(uint32_t a, uint16_t v) { asm volatile("st.shared.b16 [%0], %1;" ::"r"(a), "h"(v) : "memory"); }
__device__ __forceinline__ void sts32(uint32_t a, uint32_t v) { asm volatile("st.shared.b32 [%0], %1;" ::"r"(a), "r"(v) : "memory"); }
__device__ __forceinline__ void stsf(uint32_t a, float v) { asm volatile("st.shared.f32 [%0], %1;" ::"r"(a), "f"(v) : "memory"); }
__device__ __forceinline__ void sts64(uint32_t a, uint32_t x, uint32_t y) {
    asm volatile("st.shared.v2.b32 [%0], {%1,%2};" ::"r"(a), "r"(x), "r"(y) : "memory");
}
__device__ __forceinline__ void sts128(uint32_t a, uint4 v) {
    asm volatile("st.shared.v4.b32 [%0], {%1,%2,%3,%4};" ::"r"(a), "r"(v.x), "r"(v.y), "r"(v.z), "r"(v.w) : "memory");
}
__device__ __forceinline__ uint32_t pack_bf16(float lo, float hi) {
    uint32_t r; asm("cvt.rn.bf16x2.f32 %0, %1, %2;" : "=r"(r) : "f"(hi), "f"(lo)); return r;
}
__device__ __forceinline__ float bf_lo(uint32_t v) { return __uint_as_float(v << 16); }
__device__ __forceinline__ float bf_hi(uint32_t v) { return __uint_as_float(v & 0xffff0000u); }
__device__ __forceinline__ float ex2(float x) { float y; asm("ex2.approx.ftz.f32 %0, %1;" : "=f"(y) : "f"(x)); return y; }
__device__ __forceinline__ uint32_t timer_ns() { uint32_t t; asm volatile("mov.u32 %0, %%globaltimer_lo;" : "=r"(t)); return t; }
__device__ __forceinline__ void bar_consumers() { asm volatile("bar.sync 1, 256;" ::: "memory"); }

__device__ __forceinline__ uint32_t tagf(float v, uint32_t tag) { return (__float_as_uint(v) & 0xffffff00u) | tag; }
__device__ __forceinline__ void st_tag2(float* p, float a, float b, uint32_t tag) {
    asm volatile("st.relaxed.gpu.global.v2.b32 [%0], {%1,%2};" ::"l"(p), "r"(tagf(a, tag)), "r"(tagf(b, tag)) : "memory");
}
__device__ __forceinline__ uint2 ld_rlx2(const float* p) {
    uint2 v; asm volatile("ld.relaxed.gpu.global.v2.b32 {%0,%1}, [%2];" : "=r"(v.x), "=r"(v.y) : "l"(p) : "memory"); return v;
}
__device__ __forceinline__ uint4 ld_rlx4(const float* p) {
    uint4 v; asm volatile("ld.relaxed.gpu.global.v4.b32 {%0,%1,%2,%3}, [%4];" : "=r"(v.x), "=r"(v.y), "=r"(v.z), "=r"(v.w) : "l"(p) : "memory"); return v;
}
__device__ __forceinline__ float untag(uint32_t v) { return __uint_as_float(v & 0xffffff00u); }

__device__ __forceinline__ uint32_t slot_off(int item) { return (uint32_t)(item % NSLOT) * SLOT; }

template <bool TRANS, bool RELEASE = true>
__device__ __forceinline__ void tile_mma(uint32_t sb, int item, uint32_t in, int w, int lane, float (&acc)[2][2]) {
    const int g = lane >> 2, t = lane & 3;
    float c[4][4];
#pragma unroll
    for (int i = 0; i < 16; i++) (&c[0][0])[i] = 0.f;
    uint32_t a[16];
    const uint32_t ia = in + (g & 3) * 272 + t * 4;
#pragma unroll
    for (int i = 0; i < 16; i++) a[i] = lds32(ia + i * 16);
    const uint32_t s0 = sb + slot_off(item), s1 = sb + slot_off(item + 1);
    if (TRANS) {
        const int r = (lane & 7) + (lane & 8);
        const int ch = 2 * (w & 3) + (lane >> 4);
        const uint32_t off = (w >> 2) * 8192 + r * 128 + ((ch ^ (lane & 7)) << 4);
#pragma unroll
        for (int kk = 0; kk < 8; kk++) {
            if ((kk & 3) == 0) mbar_wait(sb + SM_FULL + (item + (kk >> 2)) * 8);
            uint32_t r0, r1, r2, r3;
            ldsm4t(((kk >> 2) ? s1 : s0) + off + (kk & 3) * 2048, r0, r1, r2, r3);
            mma16816(c[2 * (kk & 1)],     a[2 * kk], 0u, a[2 * kk + 1], 0u, r0, r1);
            mma16816(c[2 * (kk & 1) + 1], a[2 * kk], 0u, a[2 * kk + 1], 0u, r2, r3);
        }
    } else {
        mbar_wait(sb + SM_FULL + (item + (w >> 2)) * 8);
        const int r = 16 * (w & 3) + (lane & 7) + ((lane >> 4) << 3);
        const uint32_t base = ((w >> 2) ? s1 : s0) + r * 128 + ((((lane >> 3) & 1) ^ (lane & 7)) << 4);
#pragma unroll
        for (int kk = 0; kk < 8; kk++) {
            uint32_t r0, r1, r2, r3;
            ldsm4((base ^ ((kk & 3) << 5)) + (kk >> 2) * 8192, r0, r1, r2, r3);
            mma16816(c[2 * (kk & 1)],     a[2 * kk], 0u, a[2 * kk + 1], 0u, r0, r1);
            mma16816(c[2 * (kk & 1) + 1], a[2 * kk], 0u, a[2 * kk + 1], 0u, r2, r3);
        }
    }
    if (RELEASE) {
        __syncwarp();
        if (lane == 0) {
            mbar_arrive(sb + SM_EMPTY + item * 8);
            mbar_arrive(sb + SM_EMPTY + (item + 1) * 8);
        }
    }
    acc[0][0] = c[0][0] + c[2][0]; acc[0][1] = c[0][1] + c[2][1];
    acc[1][0] = c[1][0] + c[3][0]; acc[1][1] = c[1][1] + c[3][1];
}

__device__ __forceinline__ void publish(float* dst, int w, int lane, const float (&acc)[2][2], uint32_t tag) {
    if (lane < 16)
        asm volatile("st.relaxed.gpu.global.v4.b32 [%0], {%1,%2,%3,%4};" ::"l"(dst + w * 64 + lane * 4),
                     "r"(tagf(acc[0][0], tag)), "r"(tagf(acc[0][1], tag)), "r"(tagf(acc[1][0], tag)), "r"(tagf(acc[1][1], tag)) : "memory");
}

__device__ __forceinline__ void gather(const float* part, uint32_t in, int tid, uint32_t tag) {
    const float* p = part + tid * 2;
    uint2 v0, v1, v2, v3;
    int it = 0;
    while (true) {
        v0 = ld_rlx2(p); v1 = ld_rlx2(p + 512); v2 = ld_rlx2(p + 1024); v3 = ld_rlx2(p + 1536);
        uint32_t bad = ((v0.x ^ tag) | (v0.y ^ tag) | (v1.x ^ tag) | (v1.y ^ tag) |
                        (v2.x ^ tag) | (v2.y ^ tag) | (v3.x ^ tag) | (v3.y ^ tag)) & 0xffu;
        if (__all_sync(0xffffffffu, bad == 0)) break;
        if (++it > SPIN_LIMIT) __trap();
    }
    float x = (untag(v0.x) + untag(v1.x)) + (untag(v2.x) + untag(v3.x));
    float y = (untag(v0.y) + untag(v1.y)) + (untag(v2.y) + untag(v3.y));
    sts32(in + ((tid >> 3) & 3) * 272 + (tid >> 5) * 32 + (tid & 1) * 16 + (tid & 6) * 2, pack_bf16(x, y));
    bar_consumers();
}

__device__ __forceinline__ uint32_t tag_bad(const uint4& v, uint32_t tag) {
    return ((v.x ^ tag) | (v.y ^ tag) | (v.z ^ tag) | (v.w ^ tag)) & 0xffu;
}
__device__ __forceinline__ void gather_warp(const float* part, uint32_t in, int lane, uint32_t tag) {
    const float* p = part + lane * 4;
    uint4 v[16];
    int it = 0;
    while (true) {
        uint32_t bad = 0;
#pragma unroll
        for (int i = 0; i < 16; i++) v[i] = ld_rlx4(p + i * 128);
#pragma unroll
        for (int i = 0; i < 16; i++) bad |= tag_bad(v[i], tag);
        if (__all_sync(0xffffffffu, bad == 0)) break;
        if (++it > SPIN_LIMIT) __trap();
    }
    const uint32_t dst = in + ((lane >> 2) & 3) * 272 + (lane >> 4) * 32 + (lane & 3) * 4;
#pragma unroll
    for (int q = 0; q < 4; q++) {
        sts32(dst + q * 64, pack_bf16((untag(v[q].x) + untag(v[q + 4].x)) + (untag(v[q + 8].x) + untag(v[q + 12].x)),
                                      (untag(v[q].y) + untag(v[q + 4].y)) + (untag(v[q + 8].y) + untag(v[q + 12].y))));
        sts32(dst + q * 64 + 16, pack_bf16((untag(v[q].z) + untag(v[q + 4].z)) + (untag(v[q + 8].z) + untag(v[q + 12].z)),
                                           (untag(v[q].w) + untag(v[q + 4].w)) + (untag(v[q + 8].w) + untag(v[q + 12].w))));
    }
}

__device__ __forceinline__ unsigned read_counter(const unsigned* cnt) {
    unsigned v;
    asm volatile("ld.relaxed.gpu.global.u32 %0, [%1];" : "=r"(v) : "l"(cnt) : "memory");
    return v;
}
__device__ __forceinline__ unsigned epoch_of(unsigned cnt) {
    asm volatile("" : "+r"(cnt) :: "memory");
    return cnt / NCTA + 1;
}
__device__ __forceinline__ uint32_t epoch_tag(unsigned epoch) { return (epoch & 0x7fu) | 0x80u; }

__device__ __forceinline__ void signal_and_wait(unsigned* cnt, unsigned target, int lane, uint32_t sb) {
    if (lane == 0) asm volatile("red.release.gpu.global.add.u32 [%0], 1;" ::"l"(cnt) : "memory");
    if (lane == 0) TL(30 + (((size_t)cnt >> 2) & 1));
    int it = 0;
    while (true) {
        unsigned v;
        asm volatile("ld.acquire.gpu.global.u32 %0, [%1];" : "=r"(v) : "l"(cnt) : "memory");
        if (__all_sync(0xffffffffu, (int)(v - target) >= 0)) break;
        if (++it > SPIN_LIMIT) __trap();
    }
    asm volatile("fence.proxy.async.global;" ::: "memory");
}

__device__ __forceinline__ void final_reduce(const float* p, __nv_bfloat16* dst, int lane, uint32_t tag, int part) {
    uint4 v0, v1, v2, v3;
    int it = 0;
    if (lane == 0) TLX(152 + part);
    while (true) {
        v0 = ld_rlx4(p); v1 = ld_rlx4(p + 8 * 2048); v2 = ld_rlx4(p + 16 * 2048); v3 = ld_rlx4(p + 24 * 2048);
        uint32_t bad = ((v0.x ^ tag) | (v0.y ^ tag) | (v0.z ^ tag) | (v0.w ^ tag) |
                        (v1.x ^ tag) | (v1.y ^ tag) | (v1.z ^ tag) | (v1.w ^ tag) |
                        (v2.x ^ tag) | (v2.y ^ tag) | (v2.z ^ tag) | (v2.w ^ tag) |
                        (v3.x ^ tag) | (v3.y ^ tag) | (v3.z ^ tag) | (v3.w ^ tag)) & 0xffu;
        if (__all_sync(0xffffffffu, bad == 0)) break;
        if (++it > SPIN_LIMIT) __trap();
    }
    if (lane == 0) TLX(154 + part);
    float s0 = (untag(v0.x) + untag(v1.x)) + (untag(v2.x) + untag(v3.x));
    float s1 = (untag(v0.y) + untag(v1.y)) + (untag(v2.y) + untag(v3.y));
    float s2 = (untag(v0.z) + untag(v1.z)) + (untag(v2.z) + untag(v3.z));
    float s3 = (untag(v0.w) + untag(v1.w)) + (untag(v2.w) + untag(v3.w));
#pragma unroll
    for (int m = 4; m < 32; m <<= 1) {
        s0 += __shfl_xor_sync(0xffffffffu, s0, m);
        s1 += __shfl_xor_sync(0xffffffffu, s1, m);
        s2 += __shfl_xor_sync(0xffffffffu, s2, m);
        s3 += __shfl_xor_sync(0xffffffffu, s3, m);
    }
    if (lane < 8) *reinterpret_cast<uint32_t*>(dst + (lane & 4) * 2) = lane < 4 ? pack_bf16(s0, s1) : pack_bf16(s2, s3);
}

__global__ void __launch_bounds__(NTHR, 1)
fused_decode_kernel(const __nv_bfloat16* __restrict__ xA, const __nv_bfloat16* __restrict__ xB,
                    const __nv_bfloat16* __restrict__ Kc, const __nv_bfloat16* __restrict__ Vc,
                    __nv_bfloat16* __restrict__ out, Scratch* gs, const __grid_constant__ Maps maps) {
    extern __shared__ __align__(1024) unsigned char smem_raw[];
    const uint32_t sb = smem_u32(smem_raw);
    const int tid = threadIdx.x, lane = tid & 31;
    const int cta = blockIdx.x, h = cta >> 2, j = cta & 3;
    const size_t kv_off = ((size_t)(j * 32 + h) * 4096 + 3072) * 128;
    uint64_t pol;
    asm volatile("createpolicy.fractional.L2::evict_first.b64 %0, 1.0;" : "=l"(pol));
    const unsigned cnt1 = read_counter(&gs->cnt[1]);
    uint4 xv;
    if (tid < 128) {
        const __nv_bfloat16* x = (tid < 64 ? xB : xA) + ((tid >> 4) & 3) * 512 + j * 128 + (tid & 15) * 8;
        xv = __ldg(reinterpret_cast<const uint4*>(x));
    }
    if (tid == STARTER) {
        TLX(0);
        asm volatile("cp.async.bulk.prefetch.L2.global [%0], %1;" ::"l"(Kc + kv_off), "r"(SLOT) : "memory");
#pragma unroll
        for (int i = 0; i < NFIRST; i++) mbar_init(sb + SM_FULL + i * 8, 1);
        asm volatile("fence.mbarrier_init.release.cluster;" ::: "memory");
#pragma unroll
        for (int i = 0; i < NFIRST; i++) {
            TLX(32 + i);
            mbar_expect_tx(sb + SM_FULL + i * 8, SLOT);
            tma3d(sb + i * SLOT, &maps.wqB, 0, j * 128 + i * 64, h * 2, sb + SM_FULL + i * 8, pol);
        }
    }
    uint32_t tnext = timer_ns() + (NFIRST + 1) * PACE - OFFS + STAG * cta * PACE / NCTA;
    if (tid == 0) TLX(21);
    const int w = __shfl_sync(0xffffffffu, tid >> 5, 0);

    if (w >= 8) {
        if (w == 8) {
            asm volatile(BAR2 ::: "memory");
            int slot = NFIRST, tail = NFIRST - INFLIGHT;
#pragma unroll 1
            for (int i = NFIRST; i < NITEM; i++) {
                const uint32_t dst = sb + slot * SLOT, bar = sb + SM_FULL + i * 8;
                if (++slot == NSLOT) slot = 0;
                if ((i & ~1) == IT_Q || (i & ~1) == IT_OP) continue;
                const bool ckv = i >= IT_C && i < IT_K1, wo = i >= IT_WOB;
                const bool tiled = ckv || wo || i < IT_K0 || (i & ~1) == IT_WUV;
                const CUtensorMap* tm = &maps.wqB + (i < IT_K0 ? (i >> 1) : ckv ? 6 : wo ? (i - IT_WOB + 8) >> 1 : 3);
                const int c1 = ckv ? cta * 128 + (i - IT_C) * 16 : (wo ? h : j) * 128 + (i & 1) * 64;
                const int c2 = ckv ? 0 : (wo ? j : h) * 2;
                const int c = i < IT_Q ? i - IT_K0 : i < IT_V0 ? i - IT_K1 + 8 : i < IT_OP ? i - IT_V0 : i - IT_V1 + 8;
                const __nv_bfloat16* src = (i < IT_V0 ? Kc : Vc) + kv_off + (size_t)c * (SLOT / 2);
                if (i >= NSLOT) mbar_wait(sb + SM_EMPTY + (i - NSLOT) * 8);
                if (tail >= 0) mbar_wait(sb + SM_FULL + tail * 8);
                ++tail;
                if (tail == IT_Q || tail == IT_OP) tail += 2;
                if (i != IT_K0) {
                    while (__all_sync(0xffffffffu, (int)(timer_ns() - tnext) < 0)) {}
                    tnext += PACE;
                }
                if (lane == 0) {
                    TLX(32 + i);
                    if (tiled) tma3d(dst, tm, 0, c1, c2, bar, pol);
                    else bulk_load(dst, src, SLOT, bar, pol);
                }
            }
            if (lane == 0) TL(1);
        } else {
            if (lane < 6) asm volatile("prefetch.tensormap [%0];" ::"l"(&maps.wqA + lane) : "memory");
            asm volatile(BAR2 ::: "memory");
            asm volatile("bar.sync 3, 288;" ::: "memory");
            const unsigned epoch = epoch_of(cnt1);
            if (lane == 0) TL(9);
            signal_and_wait(&gs->cnt[0], epoch * NCTA, lane, sb);
            if (lane == 0) {
                TL(2);
                const uint4* q = gs->q[cta >> 5];
                bulk_load_nohint(sb + slot_off(IT_Q), q, SLOT, sb + SM_FULL + IT_Q * 8);
                bulk_load_nohint(sb + slot_off(IT_Q + 1), q + 1024, SLOT, sb + SM_FULL + (IT_Q + 1) * 8);
            }
            asm volatile("bar.sync 3, 288;" ::: "memory");
            if (lane == 0) TL(13);
            signal_and_wait(&gs->cnt[1], epoch * NCTA, lane, sb);
            mbar_wait(sb + SM_EMPTY + (IT_OP - NSLOT) * 8);
            mbar_wait(sb + SM_EMPTY + (IT_OP + 1 - NSLOT) * 8);
            if (lane == 0) {
                TL(3);
                const uint4* op = gs->op[cta];
                bulk_load_nohint(sb + SM_MX, gs->stat[h], 1024, sb + SM_FULL + IT_OP * 8);
                bulk_load_nohint(sb + slot_off(IT_OP), op, SLOT, sb + SM_FULL + IT_OP * 8);
                bulk_load_nohint(sb + slot_off(IT_OP + 1), op + 1024, SLOT, sb + SM_FULL + (IT_OP + 1) * 8);
            }
            const uint32_t tag = epoch_tag(epoch);
            asm volatile("bar.sync 3, 288;" ::: "memory");
            mbar_wait(sb + SM_FULL + (IT_V1 + CTXWAIT) * 8);
            if (lane == 0) TLX(27);
            gather_warp(gs->part[2][h * 4], sb + SM_IN0, lane, tag);
            if (lane == 0) TLX(18);
            asm volatile("bar.arrive 4, 288;" ::: "memory");
            asm volatile("bar.sync 3, 288;" ::: "memory");
            mbar_wait(sb + SM_FULL + (IT_WOB + OWAIT) * 8);
            {
                const float* p = gs->part[3][h * 4] + lane * 4;
                uint4 v[4];
                int it = 0;
                while (true) {
#pragma unroll
                    for (int i = 0; i < 4; i++) v[i] = ld_rlx4(p + i * 128);
                    if (__all_sync(0xffffffffu, (tag_bad(v[0], tag) | tag_bad(v[1], tag) | tag_bad(v[2], tag) | tag_bad(v[3], tag)) == 0)) break;
                    if (++it > SPIN_LIMIT) __trap();
                }
#pragma unroll
                for (int i = 0; i < 4; i++)
                    sts64(sb + SM_IN1 + i * 272 + lane * 8, pack_bf16(untag(v[i].x), untag(v[i].y)), pack_bf16(untag(v[i].z), untag(v[i].w)));
            }
            if (lane == 0) TLX(20);
            asm volatile("bar.arrive 5, 288;" ::: "memory");
        }
        __syncwarp();
        const int part = 9 - w;
        mbar_wait(sb + SM_FULL + (IT_WOA + part) * 8);
        final_reduce(&gs->fin[part][lane >> 2][0][cta * 16 + (lane & 3) * 4], out + j * 1024 + (part == 0 ? 512 : 0) + h * 16 + 2 * (lane & 3), lane, epoch_tag(epoch_of(cnt1)), part);
        if (lane == 0) TL(4 + part);
        return;
    }

    const int g = lane >> 2, t = lane & 3;
    const uint32_t in0 = sb + SM_IN0, in1 = sb + SM_IN1;
    {
        if (lane == 0) {
            const uint32_t bars = sb + (w < 4 ? SM_EMPTY : SM_FULL + NFIRST * 8) + (w & 3) * 14 * 8;
            const uint32_t cnt = w < 4 ? 8 : 1;
#pragma unroll
            for (int i = 0; i < 14; i++) mbar_init(bars + i * 8, cnt);
            if (w >= 4) {
#pragma unroll
                for (int i = 0; i < 14; i++)
                    mbar_expect_tx(bars + i * 8, (i == (IT_OP - NFIRST) % 14 && w == 4 + (IT_OP - NFIRST) / 14) ? SLOT + 1024 : SLOT);
            }
            asm volatile("fence.mbarrier_init.release.cluster;" ::: "memory");
        }
        if (tid == 0) TL(22);
        asm volatile(BAR2 ::: "memory");
        const float zero[2][2] = {{0.f, 0.f}, {0.f, 0.f}};
        publish(gs->part[0][cta], w, lane, zero, 0u);
        publish(gs->part[1][cta], w, lane, zero, 0u);
        publish(gs->part[2][cta], w, lane, zero, 0u);
        publish(gs->fin[0][h][j], w, lane, zero, 0u);
        publish(gs->fin[1][h][j], w, lane, zero, 0u);
        if (tid < 64) st_tag2(gs->part[3][h * 4] + j * 128 + tid * 2, 0.f, 0.f, 0u);
        if (tid < 128) sts128((tid < 64 ? in0 : in1) + ((tid >> 4) & 3) * 272 + (tid & 15) * 16, xv);
    }
    bar_consumers();
    const uint32_t tag = epoch_tag(epoch_of(cnt1));
    if (tid == 0) TL(23);

    float acc[2][2];
    tile_mma<true>(sb, IT_WQB, in0, w, lane, acc);
    if (tid == 0) TL(24);
    publish(gs->part[0][cta], w, lane, acc, tag);
    if (tid == 0) TL(6);
    tile_mma<true>(sb, IT_WQA, in1, w, lane, acc);
    publish(gs->part[1][cta], w, lane, acc, tag);
    if (tid == 0) TL(7);
    bar_consumers();

    const float SC = 0.08838834764831845f * 1.4426950408889634f;
    gather(gs->part[0][h * 4], in0, tid, tag);
    if (tid == 0) TL(8);
    tile_mma<false>(sb, IT_WUK, in0, w, lane, acc);
    if (tid == 0) TL(25);
    if (lane < 16) {
        uint32_t* q = reinterpret_cast<uint32_t*>(gs->q[g]) + (2 * j + (w >> 2)) * 1024 + h * 32 + t;
        const int ch = 2 * (w & 3);
        q[((ch) ^ (h & 7)) * 4]     = pack_bf16(acc[0][0] * SC, acc[0][1] * SC);
        q[((ch + 1) ^ (h & 7)) * 4] = pack_bf16(acc[1][0] * SC, acc[1][1] * SC);
    }
    __syncwarp();
    asm volatile("bar.arrive 3, 288;" ::: "memory");
    gather(gs->part[1][h * 4], in1, tid, tag);
    if (tid == 0) TL(28);

    uint32_t qf[16];
#pragma unroll
    for (int c = 0; c < 8; c++) {
        qf[2 * c]     = lds32(in1 + j * 272 + ((c ^ g) << 4) + t * 4);
        qf[2 * c + 1] = lds32(in1 + j * 272 + 128 + ((c ^ g) << 4) + t * 4);
    }
    const uint32_t sc_w = sb + SM_SC + w * 512;
    auto k_item = [&](int item, uint32_t sc) {
        mbar_wait(sb + SM_FULL + item * 8);
        const uint32_t base = sb + slot_off(item) + ((lane & 7) + (lane & 8)) * 256 + ((lane >> 4) << 7);
        float s[4][4];
#pragma unroll
        for (int T = 0; T < 4; T++) { s[T][0] = s[T][1] = s[T][2] = s[T][3] = 0.f; }
#pragma unroll
        for (int c = 0; c < 8; c++) {
            const uint32_t a = base + ((c ^ (lane & 7)) << 4);
#pragma unroll
            for (int T = 0; T < 4; T++) {
                uint32_t r0, r1, r2, r3;
                ldsm4(a + T * 4096, r0, r1, r2, r3);
                mma16816(s[T], r0, r1, r2, r3, qf[2 * c], qf[2 * c + 1]);
            }
        }
        __syncwarp();
        if (lane == 0) mbar_arrive8(sb + SM_EMPTY + item * 8);
        if (t == (g >> 1)) {
#pragma unroll
            for (int T = 0; T < 4; T++) {
                stsf(sc + (16 * T + g) * 4,     (g & 1) ? s[T][1] : s[T][0]);
                stsf(sc + (16 * T + g + 8) * 4, (g & 1) ? s[T][3] : s[T][2]);
            }
        }
    };
    k_item(IT_K0 + w, sc_w);
    if (tid == 224) TL(10);

    {
        float s[2][2][4];
#pragma unroll
        for (int i = 0; i < 16; i++) (&s[0][0][0])[i] = 0.f;
        mbar_wait(sb + SM_FULL + IT_Q * 8);
        mbar_wait(sb + SM_FULL + (IT_Q + 1) * 8);
        if (tid == 0) TLX(96 + IT_Q);
        mbar_wait(sb + SM_FULL + (IT_C + w) * 8);
        const uint32_t cb0 = sb + slot_off(IT_C + w) + ((lane & 7) + ((lane >> 4) << 3)) * 128;
        const uint32_t cx = (((lane >> 3) & 1) ^ (lane & 7)) << 4;
        const uint32_t qr = ((lane & 7) + (lane & 8)) * 128;
        const uint32_t qx = ((lane >> 4) ^ (lane & 7)) << 4;
#pragma unroll
        for (int cb = 0; cb < 8; cb++) {
            const uint32_t qb = sb + slot_off(IT_Q + (cb >> 2)) + (cb & 3) * 4096 + qr;
#pragma unroll
            for (int k4 = 0; k4 < 4; k4++) {
                uint32_t b0, b1, b2, b3, a0, a1, a2, a3;
                ldsm4(cb0 + cb * 2048 + (cx ^ (k4 << 5)), b0, b1, b2, b3);
                ldsm4(qb + (qx ^ (k4 << 5)), a0, a1, a2, a3);
                mma16816(s[0][0], a0, a1, a2, a3, b0, b1);
                mma16816(s[0][1], a0, a1, a2, a3, b2, b3);
                ldsm4(qb + 2048 + (qx ^ (k4 << 5)), a0, a1, a2, a3);
                mma16816(s[1][0], a0, a1, a2, a3, b0, b1);
                mma16816(s[1][1], a0, a1, a2, a3, b2, b3);
            }
        }
        __syncwarp();
        if (lane == 0) { mbar_arrive(sb + SM_EMPTY + IT_Q * 8); mbar_arrive(sb + SM_EMPTY + (IT_Q + 1) * 8); }
#pragma unroll
        for (int r = 0; r < 4; r++) {
            const int mt = r >> 1, hi = (r & 1) * 2;
            float m = fmaxf(fmaxf(s[mt][0][hi], s[mt][0][hi + 1]), fmaxf(s[mt][1][hi], s[mt][1][hi + 1]));
            m = fmaxf(m, __shfl_xor_sync(0xffffffffu, m, 1));
            m = fmaxf(m, __shfl_xor_sync(0xffffffffu, m, 2));
            if (t == 0) stsf(sb + SM_MX + (8 * r + g) * 32 + w * 4, m);
        }
        bar_consumers();
        if (tid == 0) TL(11);
        uint32_t pf[2][4];
#pragma unroll
        for (int r = 0; r < 4; r++) {
            const int mt = r >> 1, hi = r & 1;
            const float4 m0 = ldsf4(sb + SM_MX + (8 * r + g) * 32), m1 = ldsf4(sb + SM_MX + (8 * r + g) * 32 + 16);
            const float m = fmaxf(fmaxf(fmaxf(m0.x, m0.y), fmaxf(m0.z, m0.w)), fmaxf(fmaxf(m1.x, m1.y), fmaxf(m1.z, m1.w)));
            const uint32_t p0 = pack_bf16(ex2(s[mt][0][2 * hi] - m), ex2(s[mt][0][2 * hi + 1] - m));
            const uint32_t p1 = pack_bf16(ex2(s[mt][1][2 * hi] - m), ex2(s[mt][1][2 * hi + 1] - m));
            pf[mt][hi] = p0; pf[mt][2 + hi] = p1;
            float l = (bf_lo(p0) + bf_hi(p0)) + (bf_lo(p1) + bf_hi(p1));
            l += __shfl_xor_sync(0xffffffffu, l, 1);
            l += __shfl_xor_sync(0xffffffffu, l, 2);
            if (t == 0) stsf(sb + SM_SUM + (8 * r + g) * 32 + w * 4, l);
        }
        sts128(sb + SM_PF + (w * 2 + 0) * 512 + lane * 16, make_uint4(pf[0][0], pf[0][1], pf[0][2], pf[0][3]));
        sts128(sb + SM_PF + (w * 2 + 1) * 512 + lane * 16, make_uint4(pf[1][0], pf[1][1], pf[1][2], pf[1][3]));
        bar_consumers();
        if (w == 0) {
            const float4 m0 = ldsf4(sb + SM_MX + lane * 32), m1 = ldsf4(sb + SM_MX + lane * 32 + 16);
            const float4 l0 = ldsf4(sb + SM_SUM + lane * 32), l1 = ldsf4(sb + SM_SUM + lane * 32 + 16);
            const float m = fmaxf(fmaxf(fmaxf(m0.x, m0.y), fmaxf(m0.z, m0.w)), fmaxf(fmaxf(m1.x, m1.y), fmaxf(m1.z, m1.w)));
            const float l = ((l0.x + l0.y) + (l0.z + l0.w)) + ((l1.x + l1.y) + (l1.z + l1.w));
            gs->stat[lane][cta] = make_float2(m, l);
        }
        float o[2][8][4];
#pragma unroll
        for (int i = 0; i < 64; i++) (&o[0][0][0])[i] = 0.f;
        const uint32_t vr = w * 2048 + ((lane & 7) + (lane & 8)) * 128;
        const uint32_t vx = ((lane >> 4) ^ (lane & 7)) << 4;
#pragma unroll
        for (int ks = 0; ks < 8; ks++) {
            const uint4 p0 = lds128(sb + SM_PF + (ks * 2 + 0) * 512 + lane * 16);
            const uint4 p1 = lds128(sb + SM_PF + (ks * 2 + 1) * 512 + lane * 16);
            const uint32_t vb = sb + slot_off(IT_C + ks) + vr;
#pragma unroll
            for (int n2 = 0; n2 < 4; n2++) {
                uint32_t b0, b1, b2, b3;
                ldsm4t(vb + (vx ^ (n2 << 5)), b0, b1, b2, b3);
                mma16816(o[0][2 * n2],     p0.x, p0.y, p0.z, p0.w, b0, b1);
                mma16816(o[0][2 * n2 + 1], p0.x, p0.y, p0.z, p0.w, b2, b3);
                mma16816(o[1][2 * n2],     p1.x, p1.y, p1.z, p1.w, b0, b1);
                mma16816(o[1][2 * n2 + 1], p1.x, p1.y, p1.z, p1.w, b2, b3);
            }
            __syncwarp();
            if (lane == 0) mbar_arrive(sb + SM_EMPTY + (IT_C + ks) * 8);
        }
        if (tid == 0) TL(12);
        mbar_wait(sb + SM_FULL + (IT_K1 + 2 + (w >> 1)) * 8);
#pragma unroll
        for (int r = 0; r < 4; r++) {
            const int mt = r >> 1, hi = (r & 1) * 2;
            uint4* dst = gs->op[(8 * r + g) * 4 + (w >> 1)] + (cta >> 6) * 1024 + (w & 1) * 512 + (cta & 63) * 8;
#pragma unroll
            for (int u = 0; u < 2; u++) {
                uint4 v;
                v.x = pack_bf16(o[mt][4 * u][hi],     o[mt][4 * u][hi + 1]);
                v.y = pack_bf16(o[mt][4 * u + 1][hi], o[mt][4 * u + 1][hi + 1]);
                v.z = pack_bf16(o[mt][4 * u + 2][hi], o[mt][4 * u + 2][hi + 1]);
                v.w = pack_bf16(o[mt][4 * u + 3][hi], o[mt][4 * u + 3][hi + 1]);
                dst[(t + 4 * u) ^ (cta & 7)] = v;
            }
        }
        if (tid == 0) TL(29);
        asm volatile("bar.arrive 3, 288;" ::: "memory");
    }

    k_item(IT_K1 + w, sc_w + 256);
    __syncwarp();
    {
        const float4 s = ldsf4(sc_w + lane * 16);
        float m = fmaxf(fmaxf(s.x, s.y), fmaxf(s.z, s.w));
#pragma unroll
        for (int d = 1; d < 32; d <<= 1) m = fmaxf(m, __shfl_xor_sync(0xffffffffu, m, d));
        if (lane == 0) stsf(sb + SM_ML + w * 4, m);
        bar_consumers();
        const float4 m0 = ldsf4(sb + SM_ML), m1 = ldsf4(sb + SM_ML + 16);
        m = fmaxf(fmaxf(fmaxf(m0.x, m0.y), fmaxf(m0.z, m0.w)), fmaxf(fmaxf(m1.x, m1.y), fmaxf(m1.z, m1.w))) * SC;
        const uint32_t p0 = pack_bf16(ex2(fmaf(s.x, SC, -m)), ex2(fmaf(s.y, SC, -m)));
        const uint32_t p1 = pack_bf16(ex2(fmaf(s.z, SC, -m)), ex2(fmaf(s.w, SC, -m)));
        float l = (bf_lo(p0) + bf_hi(p0)) + (bf_lo(p1) + bf_hi(p1));
#pragma unroll
        for (int d = 1; d < 32; d <<= 1) l += __shfl_xor_sync(0xffffffffu, l, d);
        if (lane == 0) stsf(sb + SM_ML + 32 + w * 4, l);
        sts64(sb + SM_PA + w * 256 + lane * 8, p0, p1);
        __syncwarp();
    }
    if (tid == 224) TL(14);

    float oa[4][4];
#pragma unroll
    for (int i = 0; i < 16; i++) (&oa[0][0])[i] = 0.f;
    auto v_item = [&](int item, uint32_t pa) {
        uint32_t p[8];
#pragma unroll
        for (int i = 0; i < 8; i++) p[i] = lds32(pa + i * 16 + t * 4);
        mbar_wait(sb + SM_FULL + item * 8);
        const uint32_t base = sb + slot_off(item) + ((lane & 7) + ((lane >> 4) << 3)) * 256 + ((lane & 8) << 4);
#pragma unroll
        for (int c = 0; c < 8; c++) {
            const uint32_t a = base + ((c ^ (lane & 7)) << 4);
            const uint32_t mask = ((c == (g ^ (2 * t))) ? 0x0000ffffu : 0u) | ((c == (g ^ (2 * t + 1))) ? 0xffff0000u : 0u);
#pragma unroll
            for (int T = 0; T < 4; T++) {
                uint32_t r0, r1, r2, r3;
                ldsm4t(a + T * 4096, r0, r1, r2, r3);
                mma16816(oa[T], r0, r1, r2, r3, p[2 * T] & mask, p[2 * T + 1] & mask);
            }
        }
        __syncwarp();
        if (lane == 0) mbar_arrive8(sb + SM_EMPTY + item * 8);
    };
    v_item(IT_V0 + w, sb + SM_PA + w * 256);
    if (tid == 224) TL(15);

    mbar_wait(sb + SM_FULL + IT_OP * 8);
    if (tid == 0) TLX(96 + IT_OP);
    if (w < 4) {
        const float2 st = ldsf2(sb + SM_MX + tid * 8);
        float m = st.x;
#pragma unroll
        for (int d = 1; d < 32; d <<= 1) m = fmaxf(m, __shfl_xor_sync(0xffffffffu, m, d));
        const uint32_t wb = pack_bf16(ex2(st.x - m), 0.f);
        float l = bf_lo(wb) * st.y;
#pragma unroll
        for (int d = 1; d < 32; d <<= 1) l += __shfl_xor_sync(0xffffffffu, l, d);
#pragma unroll
        for (int bb = 0; bb < 4; bb++) sts16(in0 + bb * 272 + tid * 2, bb == w ? (uint16_t)wb : (uint16_t)0);
        if (lane == 0) stsf(sb + SM_ML + 64 + w * 4, 1.f / l);
    }
    bar_consumers();
    tile_mma<true>(sb, IT_OP, in0, w, lane, acc);
    if (lane < 16) {
        const float inv = ldsf(sb + SM_ML + 64 + g * 4);
        const int ch = 2 * (w & 3);
        const uint32_t dst = in1 + g * 272 + ((w >> 2) * 64 + 8 * (4 * (ch >> 2) + t)) * 2;
        sts32(dst + (ch & 3) * 4,       pack_bf16(acc[0][0] * inv, acc[0][1] * inv));
        sts32(dst + ((ch + 1) & 3) * 4, pack_bf16(acc[1][0] * inv, acc[1][1] * inv));
    }
    bar_consumers();
    tile_mma<true>(sb, IT_WUV, in1, w, lane, acc);
    publish(gs->part[2][cta], w, lane, acc, tag);
    if (tid == 0) TL(16);
    asm volatile("bar.arrive 3, 288;" ::: "memory");

    {
        const float4 l0 = ldsf4(sb + SM_ML + 32), l1 = ldsf4(sb + SM_ML + 48);
        const float inv = 1.f / (((l0.x + l0.y) + (l0.z + l0.w)) + ((l1.x + l1.y) + (l1.z + l1.w)));
        v_item(IT_V1 + w, sb + SM_PA + w * 256 + 128);
        const uint32_t so = sb + SM_PF + w * 512 + (16 * t + g) * 4;
        stsf(so,       (oa[0][0] + oa[1][0]) + (oa[2][0] + oa[3][0]));
        stsf(so + 32,  (oa[0][1] + oa[1][1]) + (oa[2][1] + oa[3][1]));
        stsf(so + 256, (oa[0][2] + oa[1][2]) + (oa[2][2] + oa[3][2]));
        stsf(so + 288, (oa[0][3] + oa[1][3]) + (oa[2][3] + oa[3][3]));
        bar_consumers();
        if (tid < 64) {
            float x = 0.f, y = 0.f;
#pragma unroll
            for (int i = 0; i < 8; i++) {
                const float2 v = ldsf2(sb + SM_PF + i * 512 + tid * 8);
                x += v.x; y += v.y;
            }
            st_tag2(gs->part[3][h * 4] + j * 128 + tid * 2, x * inv, y * inv, tag);
        }
    }
    if (tid == 0) TL(17);
    asm volatile("bar.arrive 3, 288;" ::: "memory");

    asm volatile("bar.sync 4, 288;" ::: "memory");
    tile_mma<true, false>(sb, IT_WOB, in0, w, lane, acc);
    publish(gs->fin[0][h][j], w, lane, acc, tag);
    if (tid == 224) TL(19);
    asm volatile("bar.sync 5, 288;" ::: "memory");
    tile_mma<true, false>(sb, IT_WOA, in1, w, lane, acc);
    publish(gs->fin[1][h][j], w, lane, acc, tag);
    if (tid == 224) TL(26);
}

typedef CUresult (*EncodeTiledFn)(CUtensorMap*, CUtensorMapDataType, cuuint32_t, void*, const cuuint64_t*,
                                  const cuuint64_t*, const cuuint32_t*, const cuuint32_t*, CUtensorMapInterleave,
                                  CUtensorMapSwizzle, CUtensorMapL2promotion, CUtensorMapFloatOOBfill);

void encode_map(EncodeTiledFn enc, CUtensorMap* tm, const void* p, cuuint64_t cols, cuuint64_t rows,
                cuuint32_t brows, cuuint32_t bblk) {
    cuuint64_t dims[3] = {64, rows, cols / 64};
    cuuint64_t strides[2] = {cols * 2, 128};
    cuuint32_t box[3] = {64, brows, bblk};
    cuuint32_t es[3] = {1, 1, 1};
    enc(tm, CU_TENSOR_MAP_DATA_TYPE_BFLOAT16, 3, const_cast<void*>(p), dims, strides, box, es,
        CU_TENSOR_MAP_INTERLEAVE_NONE, CU_TENSOR_MAP_SWIZZLE_128B, CU_TENSOR_MAP_L2_PROMOTION_L2_256B,
        CU_TENSOR_MAP_FLOAT_OOB_FILL_NONE);
}

}

extern "C" void kernel_launch(void* const* d_in, const int* in_sizes, int n_in, void* d_out, int out_size) {
    (void)in_sizes; (void)n_in; (void)out_size;
    static EncodeTiledFn enc = nullptr;
    static Scratch* gs = nullptr;
    if (!enc) {
        cudaGetSymbolAddress((void**)&gs, g_scratch);
        void* fn = nullptr;
        cudaDriverEntryPointQueryResult qr;
        cudaGetDriverEntryPoint("cuTensorMapEncodeTiled", &fn, cudaEnableDefault, &qr);
        enc = (EncodeTiledFn)fn;
        cudaFuncSetAttribute(fused_decode_kernel, cudaFuncAttributeMaxDynamicSharedMemorySize, SM_END);
    }
    Maps maps;
    encode_map(enc, &maps.wqB, d_in[7], 4096, 512, 64, 2);
    encode_map(enc, &maps.wqA, d_in[3], 4096, 512, 64, 2);
    encode_map(enc, &maps.wuk, d_in[8], 4096, 512, 64, 2);
    encode_map(enc, &maps.wuv, d_in[9], 4096, 512, 64, 2);
    encode_map(enc, &maps.woB, d_in[10], 512, 4096, 64, 2);
    encode_map(enc, &maps.woA, d_in[4], 512, 4096, 64, 2);
    encode_map(enc, &maps.ckv, d_in[6], 512, 16384, 16, 8);
    fused_decode_kernel<<<NCTA, NTHR, SM_END>>>((const __nv_bfloat16*)d_in[0], (const __nv_bfloat16*)d_in[5],
                                                (const __nv_bfloat16*)d_in[1], (const __nv_bfloat16*)d_in[2],
                                                (__nv_bfloat16*)d_out, gs, maps);
}
```

```cpp
#include <cuda_runtime.h>
#include <cuda_bf16.h>
#include <cuda.h>
#include <stdint.h>

namespace {

constexpr int NCTA   = 128;
constexpr int NSLOT  = 13;
constexpr int SLOT   = 16384;
constexpr int NITEM  = 56;
#define INFLIGHT 4
#define PACE 650
#define OFFS 500
#define STAG 0
#define OWAIT 0
#define FINMODE 1
#define FINDELAY 0
#define NFIRST 2
#define STARTER 256
#define CTXWAIT 0
#define GLEAD 150
#define AWAIT 0
#define NPOLL 4
#define FGAP 170
#define FDEL 0
constexpr int NTHR   = 320;
#define BAR2 "bar.sync 2, 320;"

constexpr int IT_WQB = 0, IT_WQA = 2, IT_WUK = 4, IT_K0 = 6, IT_Q = 14, IT_C = 16, IT_K1 = 24, IT_V0 = 32,
              IT_OP = 40, IT_V1 = 42, IT_WUV = 50, IT_WOA = 52, IT_WOB = 54;

constexpr int SM_FULL  = NSLOT * SLOT;
constexpr int SM_EMPTY = SM_FULL + 512;
constexpr int SM_IN0   = SM_EMPTY + 512;
constexpr int SM_IN1   = SM_IN0 + 1088;
constexpr int SM_SC    = SM_IN1 + 1088;
constexpr int SM_PA    = SM_SC + 4096;
constexpr int SM_PF    = SM_PA + 2048;
constexpr int SM_MX    = SM_PF + 8192;
constexpr int SM_ML    = SM_MX + 1024;
constexpr int SM_END   = SM_ML + 128;
constexpr int SM_SUM   = SM_IN0;
static_assert(SM_END <= 232448, "smem");

struct Maps { CUtensorMap wqB, wqA, wuk, wuv, woA, woB, ckv; };

struct Scratch {
    unsigned cnt[32];
    float    part[4][NCTA][512];
    float    fin[2][32][4][512];
    uint4    q[4][2048];
    uint4    op[NCTA][2048];
    float2   stat[32][128];
};
__device__ __align__(128) Scratch g_scratch;
#define TLX(i) do {} while (0)
#define TL(i) do {} while (0)

constexpr int SPIN_LIMIT = 1 << 22;

__device__ __forceinline__ uint32_t smem_u32(const void* p) { return (uint32_t)__cvta_generic_to_shared(p); }
__device__ __forceinline__ void mbar_init(uint32_t bar, uint32_t cnt) {
    asm volatile("mbarrier.init.shared::cta.b64 [%0], %1;" ::"r"(bar), "r"(cnt) : "memory");
}
__device__ __forceinline__ void mbar_expect_tx(uint32_t bar, uint32_t bytes) {
    asm volatile("mbarrier.arrive.expect_tx.shared::cta.b64 _, [%0], %1;" ::"r"(bar), "r"(bytes) : "memory");
}
__device__ __forceinline__ void mbar_arrive(uint32_t bar) {
    asm volatile("mbarrier.arrive.shared::cta.b64 _, [%0];" ::"r"(bar) : "memory");
}
__device__ __forceinline__ void mbar_arrive8(uint32_t bar) {
    asm volatile("mbarrier.arrive.shared::cta.b64 _, [%0], 8;" ::"r"(bar) : "memory");
}
__device__ __forceinline__ void mbar_wait(uint32_t bar) {
    uint32_t done;
    int it = 0;
    do {
        asm volatile("{\n.reg .pred p;\nmbarrier.try_wait.parity.shared::cta.b64 p, [%1], 0;\nselp.u32 %0, 1, 0, p;\n}"
                     : "=r"(done) : "r"(bar) : "memory");
        if (++it > SPIN_LIMIT) __trap();
    } while (!done);
}
__device__ __forceinline__ void bulk_load(uint32_t dst, const void* src, uint32_t bytes, uint32_t bar, uint64_t pol) {
    asm volatile("cp.async.bulk.shared::cluster.global.mbarrier::complete_tx::bytes.L2::cache_hint [%0], [%1], %2, [%3], %4;"
                 ::"r"(dst), "l"(src), "r"(bytes), "r"(bar), "l"(pol) : "memory");
}
__device__ __forceinline__ void bulk_load_nohint(uint32_t dst, const void* src, uint32_t bytes, uint32_t bar) {
    asm volatile("cp.async.bulk.shared::cluster.global.mbarrier::complete_tx::bytes [%0], [%1], %2, [%3];"
                 ::"r"(dst), "l"(src), "r"(bytes), "r"(bar) : "memory");
}
__device__ __forceinline__ void tma3d(uint32_t dst, const CUtensorMap* tm, int c0, int c1, int c2, uint32_t bar, uint64_t pol) {
    asm volatile("cp.async.bulk.tensor.3d.shared::cluster.global.mbarrier::complete_tx::bytes.L2::cache_hint [%0], [%1, {%3, %4, %5}], [%2], %6;"
                 ::"r"(dst), "l"(tm), "r"(bar), "r"(c0), "r"(c1), "r"(c2), "l"(pol) : "memory");
}
__device__ __forceinline__ void ldsm4(uint32_t a, uint32_t& r0, uint32_t& r1, uint32_t& r2, uint32_t& r3) {
    asm volatile("ldmatrix.sync.aligned.m8n8.x4.shared.b16 {%0,%1,%2,%3}, [%4];"
                 : "=r"(r0), "=r"(r1), "=r"(r2), "=r"(r3) : "r"(a) : "memory");
}
__device__ __forceinline__ void ldsm4t(uint32_t a, uint32_t& r0, uint32_t& r1, uint32_t& r2, uint32_t& r3) {
    asm volatile("ldmatrix.sync.aligned.m8n8.x4.trans.shared.b16 {%0,%1,%2,%3}, [%4];"
                 : "=r"(r0), "=r"(r1), "=r"(r2), "=r"(r3) : "r"(a) : "memory");
}
__device__ __forceinline__ void mma16816(float (&c)[4], uint32_t a0, uint32_t a1, uint32_t a2, uint32_t a3,
                                         uint32_t b0, uint32_t b1) {
    asm volatile("mma.sync.aligned.m16n8k16.row.col.f32.bf16.bf16.f32 {%0,%1,%2,%3}, {%4,%5,%6,%7}, {%8,%9}, {%0,%1,%2,%3};"
                 : "+f"(c[0]), "+f"(c[1]), "+f"(c[2]), "+f"(c[3])
                 : "r"(a0), "r"(a1), "r"(a2), "r"(a3), "r"(b0), "r"(b1));
}
__device__ __forceinline__ uint32_t lds32(uint32_t a) {
    uint32_t v; asm volatile("ld.shared.b32 %0, [%1];" : "=r"(v) : "r"(a) : "memory"); return v;
}
__device__ __forceinline__ float ldsf(uint32_t a) {
    float v; asm volatile("ld.shared.f32 %0, [%1];" : "=f"(v) : "r"(a) : "memory"); return v;
}
__device__ __forceinline__ float2 ldsf2(uint32_t a) {
    float2 v; asm volatile("ld.shared.v2.f32 {%0,%1}, [%2];" : "=f"(v.x), "=f"(v.y) : "r"(a) : "memory"); return v;
}
__device__ __forceinline__ float4 ldsf4(uint32_t a) {
    float4 v; asm volatile("ld.shared.v4.f32 {%0,%1,%2,%3}, [%4];" : "=f"(v.x), "=f"(v.y), "=f"(v.z), "=f"(v.w) : "r"(a) : "memory"); return v;
}
__device__ __forceinline__ uint4 lds128(uint32_t a) {
    uint4 v; asm volatile("ld.shared.v4.b32 {%0,%1,%2,%3}, [%4];" : "=r"(v.x), "=r"(v.y), "=r"(v.z), "=r"(v.w) : "r"(a) : "memory"); return v;
}
__device__ __forceinline__ void sts16(uint32_t a, uint16_t v) { asm volatile("st.shared.b16 [%0], %1;" ::"r"(a), "h"(v) : "memory"); }
__device__ __forceinline__ void sts32(uint32_t a, uint32_t v) { asm volatile("st.shared.b32 [%0], %1;" ::"r"(a), "r"(v) : "memory"); }
__device__ __forceinline__ void stsf(uint32_t a, float v) { asm volatile("st.shared.f32 [%0], %1;" ::"r"(a), "f"(v) : "memory"); }
__device__ __forceinline__ void sts64(uint32_t a, uint32_t x, uint32_t y) {
    asm volatile("st.shared.v2.b32 [%0], {%1,%2};" ::"r"(a), "r"(x), "r"(y) : "memory");
}
__device__ __forceinline__ void sts128(uint32_t a, uint4 v) {
    asm volatile("st.shared.v4.b32 [%0], {%1,%2,%3,%4};" ::"r"(a), "r"(v.x), "r"(v.y), "r"(v.z), "r"(v.w) : "memory");
}
__device__ __forceinline__ uint32_t pack_bf16(float lo, float hi) {
    uint32_t r; asm("cvt.rn.bf16x2.f32 %0, %1, %2;" : "=r"(r) : "f"(hi), "f"(lo)); return r;
}
__device__ __forceinline__ float bf_lo(uint32_t v) { return __uint_as_float(v << 16); }
__device__ __forceinline__ float bf_hi(uint32_t v) { return __uint_as_float(v & 0xffff0000u); }
__device__ __forceinline__ float ex2(float x) { float y; asm("ex2.approx.ftz.f32 %0, %1;" : "=f"(y) : "f"(x)); return y; }
__device__ __forceinline__ uint32_t timer_ns() { uint32_t t; asm volatile("mov.u32 %0, %%globaltimer_lo;" : "=r"(t)); return t; }
__device__ __forceinline__ void bar_consumers() { asm volatile("bar.sync 1, 256;" ::: "memory"); }

__device__ __forceinline__ uint32_t tagf(float v, uint32_t tag) { return (__float_as_uint(v) & 0xffffff00u) | tag; }
__device__ __forceinline__ void st_tag2(float* p, float a, float b, uint32_t tag) {
    asm volatile("st.relaxed.gpu.global.v2.b32 [%0], {%1,%2};" ::"l"(p), "r"(tagf(a, tag)), "r"(tagf(b, tag)) : "memory");
}
__device__ __forceinline__ uint2 ld_rlx2(const float* p) {
    uint2 v; asm volatile("ld.relaxed.gpu.global.v2.b32 {%0,%1}, [%2];" : "=r"(v.x), "=r"(v.y) : "l"(p) : "memory"); return v;
}
__device__ __forceinline__ uint4 ld_rlx4(const float* p) {
    uint4 v; asm volatile("ld.relaxed.gpu.global.v4.b32 {%0,%1,%2,%3}, [%4];" : "=r"(v.x), "=r"(v.y), "=r"(v.z), "=r"(v.w) : "l"(p) : "memory"); return v;
}
__device__ __forceinline__ float untag(uint32_t v) { return __uint_as_float(v & 0xffffff00u); }

__device__ __forceinline__ uint32_t slot_off(int item) { return (uint32_t)(item % NSLOT) * SLOT; }

template <bool TRANS, bool RELEASE = true>
__device__ __forceinline__ void tile_mma(uint32_t sb, int item, uint32_t in, int w, int lane, float (&acc)[2][2]) {
    const int g = lane >> 2, t = lane & 3;
    float c[4][4];
#pragma unroll
    for (int i = 0; i < 16; i++) (&c[0][0])[i] = 0.f;
    uint32_t a[16];
    const uint32_t ia = in + (g & 3) * 272 + t * 4;
#pragma unroll
    for (int i = 0; i < 16; i++) a[i] = lds32(ia + i * 16);
    const uint32_t s0 = sb + slot_off(item), s1 = sb + slot_off(item + 1);
    if (TRANS) {
        const int r = (lane & 7) + (lane & 8);
        const int ch = 2 * (w & 3) + (lane >> 4);
        const uint32_t off = (w >> 2) * 8192 + r * 128 + ((ch ^ (lane & 7)) << 4);
#pragma unroll
        for (int kk = 0; kk < 8; kk++) {
            if ((kk & 3) == 0) mbar_wait(sb + SM_FULL + (item + (kk >> 2)) * 8);
            uint32_t r0, r1, r2, r3;
            ldsm4t(((kk >> 2) ? s1 : s0) + off + (kk & 3) * 2048, r0, r1, r2, r3);
            mma16816(c[2 * (kk & 1)],     a[2 * kk], 0u, a[2 * kk + 1], 0u, r0, r1);
            mma16816(c[2 * (kk & 1) + 1], a[2 * kk], 0u, a[2 * kk + 1], 0u, r2, r3);
        }
    } else {
        mbar_wait(sb + SM_FULL + (item + (w >> 2)) * 8);
        const int r = 16 * (w & 3) + (lane & 7) + ((lane >> 4) << 3);
        const uint32_t base = ((w >> 2) ? s1 : s0) + r * 128 + ((((lane >> 3) & 1) ^ (lane & 7)) << 4);
#pragma unroll
        for (int kk = 0; kk < 8; kk++) {
            uint32_t r0, r1, r2, r3;
            ldsm4((base ^ ((kk & 3) << 5)) + (kk >> 2) * 8192, r0, r1, r2, r3);
            mma16816(c[2 * (kk & 1)],     a[2 * kk], 0u, a[2 * kk + 1], 0u, r0, r1);
            mma16816(c[2 * (kk & 1) + 1], a[2 * kk], 0u, a[2 * kk + 1], 0u, r2, r3);
        }
    }
    if (RELEASE) {
        __syncwarp();
        if (lane == 0) {
            mbar_arrive(sb + SM_EMPTY + item * 8);
            mbar_arrive(sb + SM_EMPTY + (item + 1) * 8);
        }
    }
    acc[0][0] = c[0][0] + c[2][0]; acc[0][1] = c[0][1] + c[2][1];
    acc[1][0] = c[1][0] + c[3][0]; acc[1][1] = c[1][1] + c[3][1];
}

__device__ __forceinline__ void publish(float* dst, int w, int lane, const float (&acc)[2][2], uint32_t tag) {
    if (lane < 16)
        asm volatile("st.relaxed.gpu.global.v4.b32 [%0], {%1,%2,%3,%4};" ::"l"(dst + w * 64 + lane * 4),
                     "r"(tagf(acc[0][0], tag)), "r"(tagf(acc[0][1], tag)), "r"(tagf(acc[1][0], tag)), "r"(tagf(acc[1][1], tag)) : "memory");
}

__device__ __forceinline__ void gather(const float* part, uint32_t in, int tid, uint32_t tag) {
    const float* p = part + tid * 2;
    uint2 v0, v1, v2, v3;
    int it = 0;
    while (true) {
        v0 = ld_rlx2(p); v1 = ld_rlx2(p + 512); v2 = ld_rlx2(p + 1024); v3 = ld_rlx2(p + 1536);
        uint32_t bad = ((v0.x ^ tag) | (v0.y ^ tag) | (v1.x ^ tag) | (v1.y ^ tag) |
                        (v2.x ^ tag) | (v2.y ^ tag) | (v3.x ^ tag) | (v3.y ^ tag)) & 0xffu;
        if (__all_sync(0xffffffffu, bad == 0)) break;
        if (++it > SPIN_LIMIT) __trap();
    }
    float x = (untag(v0.x) + untag(v1.x)) + (untag(v2.x) + untag(v3.x));
    float y = (untag(v0.y) + untag(v1.y)) + (untag(v2.y) + untag(v3.y));
    sts32(in + ((tid >> 3) & 3) * 272 + (tid >> 5) * 32 + (tid & 1) * 16 + (tid & 6) * 2, pack_bf16(x, y));
    bar_consumers();
}

__device__ __forceinline__ uint32_t tag_bad(const uint4& v, uint32_t tag) {
    return ((v.x ^ tag) | (v.y ^ tag) | (v.z ^ tag) | (v.w ^ tag)) & 0xffu;
}
__device__ __forceinline__ void gather_issue(const float* part, int lane, uint4 (&v)[16]) {
#pragma unroll
    for (int i = 0; i < 16; i++) v[i] = ld_rlx4(part + lane * 4 + i * 128);
}
__device__ __forceinline__ void gather_finish(const float* part, uint32_t in, int lane, uint32_t tag, uint4 (&v)[16]) {
    int it = 0;
    while (true) {
        uint32_t bad = 0;
#pragma unroll
        for (int i = 0; i < 16; i++) bad |= tag_bad(v[i], tag);
        if (__all_sync(0xffffffffu, bad == 0)) break;
        gather_issue(part, lane, v);
        if (++it > SPIN_LIMIT) __trap();
    }
    const uint32_t dst = in + ((lane >> 2) & 3) * 272 + (lane >> 4) * 32 + (lane & 3) * 4;
#pragma unroll
    for (int q = 0; q < 4; q++) {
        sts32(dst + q * 64, pack_bf16((untag(v[q].x) + untag(v[q + 4].x)) + (untag(v[q + 8].x) + untag(v[q + 12].x)),
                                      (untag(v[q].y) + untag(v[q + 4].y)) + (untag(v[q + 8].y) + untag(v[q + 12].y))));
        sts32(dst + q * 64 + 16, pack_bf16((untag(v[q].z) + untag(v[q + 4].z)) + (untag(v[q + 8].z) + untag(v[q + 12].z)),
                                           (untag(v[q].w) + untag(v[q + 4].w)) + (untag(v[q + 8].w) + untag(v[q + 12].w))));
    }
}

__device__ __forceinline__ unsigned read_counter(const unsigned* cnt) {
    unsigned v;
    asm volatile("ld.relaxed.gpu.global.u32 %0, [%1];" : "=r"(v) : "l"(cnt) : "memory");
    return v;
}
__device__ __forceinline__ unsigned epoch_of(unsigned cnt) {
    asm volatile("" : "+r"(cnt) :: "memory");
    return cnt / NCTA + 1;
}
__device__ __forceinline__ uint32_t epoch_tag(unsigned epoch) { return (epoch & 0x7fu) | 0x80u; }

__device__ __forceinline__ void signal_and_wait(unsigned* cnt, unsigned target, int lane, uint32_t sb) {
    if (lane == 0) asm volatile("red.release.gpu.global.add.u32 [%0], 1;" ::"l"(cnt) : "memory");
    if (lane == 0) TL(30 + (((size_t)cnt >> 2) & 1));
    int it = 0;
    while (true) {
        unsigned v;
        asm volatile("ld.acquire.gpu.global.u32 %0, [%1];" : "=r"(v) : "l"(cnt) : "memory");
        if (__all_sync(0xffffffffu, (int)(v - target) >= 0)) break;
        if (++it > SPIN_LIMIT) __trap();
    }
    asm volatile("fence.proxy.async.global;" ::: "memory");
}

__device__ __forceinline__ void ld_rlx4_if(uint4& v, const float* p, uint32_t need) {
    asm volatile("{\n.reg .pred p;\nsetp.ne.u32 p, %5, 0;\n@p ld.relaxed.gpu.global.v4.b32 {%0,%1,%2,%3}, [%4];\n}"
                 : "+r"(v.x), "+r"(v.y), "+r"(v.z), "+r"(v.w) : "l"(p), "r"(need) : "memory");
}
template <bool RACE>
__device__ __forceinline__ void final_reduce(const float* p, __nv_bfloat16* dst, int lane, uint32_t tag, int part, uint32_t done) {
    uint4 v0 = ld_rlx4(p), v1 = ld_rlx4(p + 8 * 2048), v2 = ld_rlx4(p + 16 * 2048), v3 = ld_rlx4(p + 24 * 2048);
    int it = 0;
    while (true) {
        const uint32_t b0 = tag_bad(v0, tag), b1 = tag_bad(v1, tag), b2 = tag_bad(v2, tag), b3 = tag_bad(v3, tag);
        if (RACE && __any_sync(0xffffffffu, lds32(done) != 0)) return;
        if (__all_sync(0xffffffffu, (b0 | b1 | b2 | b3) == 0)) break;
        ld_rlx4_if(v0, p, b0); ld_rlx4_if(v1, p + 8 * 2048, b1); ld_rlx4_if(v2, p + 16 * 2048, b2); ld_rlx4_if(v3, p + 24 * 2048, b3);
        if (++it > SPIN_LIMIT) __trap();
    }
    if (RACE) sts32(done, 1u);
    if (lane == 0) TLX(154 + part);
    float s0 = (untag(v0.x) + untag(v1.x)) + (untag(v2.x) + untag(v3.x));
    float s1 = (untag(v0.y) + untag(v1.y)) + (untag(v2.y) + untag(v3.y));
    float s2 = (untag(v0.z) + untag(v1.z)) + (untag(v2.z) + untag(v3.z));
    float s3 = (untag(v0.w) + untag(v1.w)) + (untag(v2.w) + untag(v3.w));
#pragma unroll
    for (int m = 4; m < 32; m <<= 1) {
        s0 += __shfl_xor_sync(0xffffffffu, s0, m);
        s1 += __shfl_xor_sync(0xffffffffu, s1, m);
        s2 += __shfl_xor_sync(0xffffffffu, s2, m);
        s3 += __shfl_xor_sync(0xffffffffu, s3, m);
    }
    if (lane < 8) *reinterpret_cast<uint32_t*>(dst + (lane & 4) * 2) = lane < 4 ? pack_bf16(s0, s1) : pack_bf16(s2, s3);
}

__global__ void __launch_bounds__(NTHR, 1)
fused_decode_kernel(const __nv_bfloat16* __restrict__ xA, const __nv_bfloat16* __restrict__ xB,
                    const __nv_bfloat16* __restrict__ Kc, const __nv_bfloat16* __restrict__ Vc,
                    __nv_bfloat16* __restrict__ out, Scratch* gs, const __grid_constant__ Maps maps) {
    extern __shared__ __align__(1024) unsigned char smem_raw[];
    const uint32_t sb = smem_u32(smem_raw);
    const int tid = threadIdx.x, lane = tid & 31;
    const int cta = blockIdx.x, h = cta >> 2, j = cta & 3;
    const size_t kv_off = ((size_t)(j * 32 + h) * 4096 + 3072) * 128;
    uint64_t pol;
    asm volatile("createpolicy.fractional.L2::evict_first.b64 %0, 1.0;" : "=l"(pol));
    const unsigned cnt1 = read_counter(&gs->cnt[1]);
    uint4 xv;
    if (tid < 128) {
        const __nv_bfloat16* x = (tid < 64 ? xB : xA) + ((tid >> 4) & 3) * 512 + j * 128 + (tid & 15) * 8;
        xv = __ldg(reinterpret_cast<const uint4*>(x));
    }
    if (tid == STARTER) {
        TLX(0);
        asm volatile("cp.async.bulk.prefetch.L2.global [%0], %1;" ::"l"(Kc + kv_off), "r"(SLOT) : "memory");
#pragma unroll
        for (int i = 0; i < NFIRST; i++) mbar_init(sb + SM_FULL + i * 8, 1);
        asm volatile("fence.mbarrier_init.release.cluster;" ::: "memory");
#pragma unroll
        for (int i = 0; i < NFIRST; i++) {
            TLX(32 + i);
            mbar_expect_tx(sb + SM_FULL + i * 8, SLOT);
            tma3d(sb + i * SLOT, &maps.wqB, 0, j * 128 + i * 64, h * 2, sb + SM_FULL + i * 8, pol);
        }
    }
    uint32_t tnext = timer_ns() + (NFIRST + 1) * PACE - OFFS + STAG * cta * PACE / NCTA;
    if (tid == 0) TLX(21);
    const int w = __shfl_sync(0xffffffffu, tid >> 5, 0);

    if (w >= 8) {
        if (w == 8) {
            asm volatile(BAR2 ::: "memory");
            int slot = NFIRST, tail = NFIRST - INFLIGHT;
#pragma unroll 1
            for (int i = NFIRST; i < NITEM - 1; i++) {
                const uint32_t dst = sb + slot * SLOT, bar = sb + SM_FULL + i * 8;
                if (++slot == NSLOT) slot = 0;
                if ((i & ~1) == IT_Q || (i & ~1) == IT_OP) continue;
                const bool ckv = i >= IT_C && i < IT_K1, wo = i >= IT_WOA;
                const bool tiled = ckv || i < IT_K0 || i >= IT_WUV;
                const CUtensorMap* tm = &maps.wqB + (i < IT_K0 ? (i >> 1) : ckv ? 6 : (i - IT_WUV + 6) >> 1);
                const int c1 = ckv ? cta * 128 + (i - IT_C) * 16 : (wo ? h : j) * 128 + (i & 1) * 64;
                const int c2 = ckv ? 0 : (wo ? j : h) * 2;
                const int c = i < IT_Q ? i - IT_K0 : i < IT_V0 ? i - IT_K1 + 8 : i < IT_OP ? i - IT_V0 : i - IT_V1 + 8;
                const __nv_bfloat16* src = (i < IT_V0 ? Kc : Vc) + kv_off + (size_t)c * (SLOT / 2);
                if (i >= NSLOT) mbar_wait(sb + SM_EMPTY + (i - NSLOT) * 8);
                if (tail >= 0) mbar_wait(sb + SM_FULL + tail * 8);
                ++tail;
                if (tail == IT_Q || tail == IT_OP) tail += 2;
                if (i != IT_K0) {
                    while (__all_sync(0xffffffffu, (int)(timer_ns() - tnext) < 0)) {}
                    tnext += PACE;
                }
                if (lane == 0) {
                    TLX(32 + i);
                    if (tiled) tma3d(dst, tm, 0, c1, c2, bar, pol);
                    else bulk_load(dst, src, SLOT, bar, pol);
                }
            }
            uint4 v[16];
            mbar_wait(sb + SM_EMPTY + (NITEM - 1 - NSLOT) * 8);
            while (__all_sync(0xffffffffu, (int)(timer_ns() - (tnext - GLEAD)) < 0)) {}
            if (lane == 0) TLX(27);
            gather_issue(gs->part[2][h * 4], lane, v);
            mbar_wait(sb + SM_FULL + (NITEM - 1 - INFLIGHT) * 8);
            while (__all_sync(0xffffffffu, (int)(timer_ns() - tnext) < 0)) {}
            if (lane == 0) {
                TLX(32 + NITEM - 1);
                tma3d(sb + slot_off(NITEM - 1), &maps.woB, 0, h * 128 + 64, j * 2, sb + SM_FULL + (NITEM - 1) * 8, pol);
            }
            asm volatile("bar.sync 6, 288;" ::: "memory");
            gather_finish(gs->part[2][h * 4], sb + SM_IN1, lane, epoch_tag(epoch_of(cnt1)), v);
            if (lane == 0) TLX(18);
            asm volatile("bar.arrive 4, 288;" ::: "memory");
        } else {
            if (lane < 6) asm volatile("prefetch.tensormap [%0];" ::"l"(&maps.wqA + lane) : "memory");
            asm volatile(BAR2 ::: "memory");
            asm volatile("bar.sync 3, 288;" ::: "memory");
            const unsigned epoch = epoch_of(cnt1);
            if (lane == 0) TL(9);
            signal_and_wait(&gs->cnt[0], epoch * NCTA, lane, sb);
            if (lane == 0) {
                TL(2);
                const uint4* q = gs->q[cta >> 5];
                bulk_load_nohint(sb + slot_off(IT_Q), q, SLOT, sb + SM_FULL + IT_Q * 8);
                bulk_load_nohint(sb + slot_off(IT_Q + 1), q + 1024, SLOT, sb + SM_FULL + (IT_Q + 1) * 8);
            }
            asm volatile("bar.sync 3, 288;" ::: "memory");
            if (lane == 0) TL(13);
            signal_and_wait(&gs->cnt[1], epoch * NCTA, lane, sb);
            mbar_wait(sb + SM_EMPTY + (IT_OP - NSLOT) * 8);
            mbar_wait(sb + SM_EMPTY + (IT_OP + 1 - NSLOT) * 8);
            if (lane == 0) {
                TL(3);
                const uint4* op = gs->op[cta];
                bulk_load_nohint(sb + SM_MX, gs->stat[h], 1024, sb + SM_FULL + IT_OP * 8);
                bulk_load_nohint(sb + slot_off(IT_OP), op, SLOT, sb + SM_FULL + IT_OP * 8);
                bulk_load_nohint(sb + slot_off(IT_OP + 1), op + 1024, SLOT, sb + SM_FULL + (IT_OP + 1) * 8);
            }
            const uint32_t tag = epoch_tag(epoch);
            asm volatile("bar.sync 3, 288;" ::: "memory");
            mbar_wait(sb + SM_FULL + (IT_WUV + OWAIT) * 8);
            {
                const float* p = gs->part[3][h * 4] + lane * 4;
                uint4 v[4];
                int it = 0;
                while (true) {
#pragma unroll
                    for (int i = 0; i < 4; i++) v[i] = ld_rlx4(p + i * 128);
                    if (__all_sync(0xffffffffu, (tag_bad(v[0], tag) | tag_bad(v[1], tag) | tag_bad(v[2], tag) | tag_bad(v[3], tag)) == 0)) break;
                    if (++it > SPIN_LIMIT) __trap();
                }
#pragma unroll
                for (int i = 0; i < 4; i++)
                    sts64(sb + SM_IN0 + i * 272 + lane * 8, pack_bf16(untag(v[i].x), untag(v[i].y)), pack_bf16(untag(v[i].z), untag(v[i].w)));
            }
            if (lane == 0) TLX(20);
            asm volatile("bar.arrive 5, 288;" ::: "memory");
        }
        if (w == 9) {
            mbar_wait(sb + SM_FULL + (IT_WOB + AWAIT) * 8);
            final_reduce<false>(&gs->fin[1][lane >> 2][0][cta * 16 + (lane & 3) * 4], out + j * 1024 + h * 16 + 2 * (lane & 3), lane, epoch_tag(epoch_of(cnt1)), 1, 0);
            if (lane == 0) TL(5);
        }
        return;
    }

    const int g = lane >> 2, t = lane & 3;
    const uint32_t in0 = sb + SM_IN0, in1 = sb + SM_IN1;
    {
        if (lane == 0) {
            const uint32_t bars = sb + (w < 4 ? SM_EMPTY : SM_FULL + NFIRST * 8) + (w & 3) * 14 * 8;
            const uint32_t cnt = w < 4 ? 8 : 1;
#pragma unroll
            for (int i = 0; i < 14; i++) mbar_init(bars + i * 8, cnt);
            if (w >= 4) {
#pragma unroll
                for (int i = 0; i < 14; i++)
                    mbar_expect_tx(bars + i * 8, (i == (IT_OP - NFIRST) % 14 && w == 4 + (IT_OP - NFIRST) / 14) ? SLOT + 1024 : SLOT);
            }
            asm volatile("fence.mbarrier_init.release.cluster;" ::: "memory");
        }
        if (tid == 0) TL(22);
        asm volatile(BAR2 ::: "memory");
        const float zero[2][2] = {{0.f, 0.f}, {0.f, 0.f}};
        publish(gs->part[0][cta], w, lane, zero, 0u);
        publish(gs->part[1][cta], w, lane, zero, 0u);
        publish(gs->part[2][cta], w, lane, zero, 0u);
        publish(gs->fin[0][h][j], w, lane, zero, 0u);
        publish(gs->fin[1][h][j], w, lane, zero, 0u);
        if (tid < 64) st_tag2(gs->part[3][h * 4] + j * 128 + tid * 2, 0.f, 0.f, 0u);
        if (tid == 128) sts32(sb + SM_ML + 80, 0u);
        if (tid < 128) sts128((tid < 64 ? in0 : in1) + ((tid >> 4) & 3) * 272 + (tid & 15) * 16, xv);
    }
    bar_consumers();
    const uint32_t tag = epoch_tag(epoch_of(cnt1));
    if (tid == 0) TL(23);

    float acc[2][2];
    tile_mma<true>(sb, IT_WQB, in0, w, lane, acc);
    if (tid == 0) TL(24);
    publish(gs->part[0][cta], w, lane, acc, tag);
    if (tid == 0) TL(6);
    tile_mma<true>(sb, IT_WQA, in1, w, lane, acc);
    publish(gs->part[1][cta], w, lane, acc, tag);
    if (tid == 0) TL(7);
    bar_consumers();

    const float SC = 0.08838834764831845f * 1.4426950408889634f;
    gather(gs->part[0][h * 4], in0, tid, tag);
    if (tid == 0) TL(8);
    tile_mma<false>(sb, IT_WUK, in0, w, lane, acc);
    if (tid == 0) TL(25);
    if (lane < 16) {
        uint32_t* q = reinterpret_cast<uint32_t*>(gs->q[g]) + (2 * j + (w >> 2)) * 1024 + h * 32 + t;
        const int ch = 2 * (w & 3);
        q[((ch) ^ (h & 7)) * 4]     = pack_bf16(acc[0][0] * SC, acc[0][1] * SC);
        q[((ch + 1) ^ (h & 7)) * 4] = pack_bf16(acc[1][0] * SC, acc[1][1] * SC);
    }
    __syncwarp();
    asm volatile("bar.arrive 3, 288;" ::: "memory");
    gather(gs->part[1][h * 4], in1, tid, tag);
    if (tid == 0) TL(28);

    uint32_t qf[16];
#pragma unroll
    for (int c = 0; c < 8; c++) {
        qf[2 * c]     = lds32(in1 + j * 272 + ((c ^ g) << 4) + t * 4);
        qf[2 * c + 1] = lds32(in1 + j * 272 + 128 + ((c ^ g) << 4) + t * 4);
    }
    const uint32_t sc_w = sb + SM_SC + w * 512;
    auto k_item = [&](int item, uint32_t sc) {
        mbar_wait(sb + SM_FULL + item * 8);
        const uint32_t base = sb + slot_off(item) + ((lane & 7) + (lane & 8)) * 256 + ((lane >> 4) << 7);
        float s[4][4];
#pragma unroll
        for (int T = 0; T < 4; T++) { s[T][0] = s[T][1] = s[T][2] = s[T][3] = 0.f; }
#pragma unroll
        for (int c = 0; c < 8; c++) {
            const uint32_t a = base + ((c ^ (lane & 7)) << 4);
#pragma unroll
            for (int T = 0; T < 4; T++) {
                uint32_t r0, r1, r2, r3;
                ldsm4(a + T * 4096, r0, r1, r2, r3);
                mma16816(s[T], r0, r1, r2, r3, qf[2 * c], qf[2 * c + 1]);
            }
        }
        __syncwarp();
        if (lane == 0) mbar_arrive8(sb + SM_EMPTY + item * 8);
        if (t == (g >> 1)) {
#pragma unroll
            for (int T = 0; T < 4; T++) {
                stsf(sc + (16 * T + g) * 4,     (g & 1) ? s[T][1] : s[T][0]);
                stsf(sc + (16 * T + g + 8) * 4, (g & 1) ? s[T][3] : s[T][2]);
            }
        }
    };
    k_item(IT_K0 + w, sc_w);
    if (tid == 224) TL(10);

    {
        float s[2][2][4];
#pragma unroll
        for (int i = 0; i < 16; i++) (&s[0][0][0])[i] = 0.f;
        mbar_wait(sb + SM_FULL + IT_Q * 8);
        mbar_wait(sb + SM_FULL + (IT_Q + 1) * 8);
        if (tid == 0) TLX(96 + IT_Q);
        mbar_wait(sb + SM_FULL + (IT_C + w) * 8);
        const uint32_t cb0 = sb + slot_off(IT_C + w) + ((lane & 7) + ((lane >> 4) << 3)) * 128;
        const uint32_t cx = (((lane >> 3) & 1) ^ (lane & 7)) << 4;
        const uint32_t qr = ((lane & 7) + (lane & 8)) * 128;
        const uint32_t qx = ((lane >> 4) ^ (lane & 7)) << 4;
#pragma unroll
        for (int cb = 0; cb < 8; cb++) {
            const uint32_t qb = sb + slot_off(IT_Q + (cb >> 2)) + (cb & 3) * 4096 + qr;
#pragma unroll
            for (int k4 = 0; k4 < 4; k4++) {
                uint32_t b0, b1, b2, b3, a0, a1, a2, a3;
                ldsm4(cb0 + cb * 2048 + (cx ^ (k4 << 5)), b0, b1, b2, b3);
                ldsm4(qb + (qx ^ (k4 << 5)), a0, a1, a2, a3);
                mma16816(s[0][0], a0, a1, a2, a3, b0, b1);
                mma16816(s[0][1], a0, a1, a2, a3, b2, b3);
                ldsm4(qb + 2048 + (qx ^ (k4 << 5)), a0, a1, a2, a3);
                mma16816(s[1][0], a0, a1, a2, a3, b0, b1);
                mma16816(s[1][1], a0, a1, a2, a3, b2, b3);
            }
        }
        __syncwarp();
        if (lane == 0) { mbar_arrive(sb + SM_EMPTY + IT_Q * 8); mbar_arrive(sb + SM_EMPTY + (IT_Q + 1) * 8); }
#pragma unroll
        for (int r = 0; r < 4; r++) {
            const int mt = r >> 1, hi = (r & 1) * 2;
            float m = fmaxf(fmaxf(s[mt][0][hi], s[mt][0][hi + 1]), fmaxf(s[mt][1][hi], s[mt][1][hi + 1]));
            m = fmaxf(m, __shfl_xor_sync(0xffffffffu, m, 1));
            m = fmaxf(m, __shfl_xor_sync(0xffffffffu, m, 2));
            if (t == 0) stsf(sb + SM_MX + (8 * r + g) * 32 + w * 4, m);
        }
        bar_consumers();
        if (tid == 0) TL(11);
        uint32_t pf[2][4];
#pragma unroll
        for (int r = 0; r < 4; r++) {
            const int mt = r >> 1, hi = r & 1;
            const float4 m0 = ldsf4(sb + SM_MX + (8 * r + g) * 32), m1 = ldsf4(sb + SM_MX + (8 * r + g) * 32 + 16);
            const float m = fmaxf(fmaxf(fmaxf(m0.x, m0.y), fmaxf(m0.z, m0.w)), fmaxf(fmaxf(m1.x, m1.y), fmaxf(m1.z, m1.w)));
            const uint32_t p0 = pack_bf16(ex2(s[mt][0][2 * hi] - m), ex2(s[mt][0][2 * hi + 1] - m));
            const uint32_t p1 = pack_bf16(ex2(s[mt][1][2 * hi] - m), ex2(s[mt][1][2 * hi + 1] - m));
            pf[mt][hi] = p0; pf[mt][2 + hi] = p1;
            float l = (bf_lo(p0) + bf_hi(p0)) + (bf_lo(p1) + bf_hi(p1));
            l += __shfl_xor_sync(0xffffffffu, l, 1);
            l += __shfl_xor_sync(0xffffffffu, l, 2);
            if (t == 0) stsf(sb + SM_SUM + (8 * r + g) * 32 + w * 4, l);
        }
        sts128(sb + SM_PF + (w * 2 + 0) * 512 + lane * 16, make_uint4(pf[0][0], pf[0][1], pf[0][2], pf[0][3]));
        sts128(sb + SM_PF + (w * 2 + 1) * 512 + lane * 16, make_uint4(pf[1][0], pf[1][1], pf[1][2], pf[1][3]));
        bar_consumers();
        if (w == 0) {
            const float4 m0 = ldsf4(sb + SM_MX + lane * 32), m1 = ldsf4(sb + SM_MX + lane * 32 + 16);
            const float4 l0 = ldsf4(sb + SM_SUM + lane * 32), l1 = ldsf4(sb + SM_SUM + lane * 32 + 16);
            const float m = fmaxf(fmaxf(fmaxf(m0.x, m0.y), fmaxf(m0.z, m0.w)), fmaxf(fmaxf(m1.x, m1.y), fmaxf(m1.z, m1.w)));
            const float l = ((l0.x + l0.y) + (l0.z + l0.w)) + ((l1.x + l1.y) + (l1.z + l1.w));
            gs->stat[lane][cta] = make_float2(m, l);
        }
        float o[2][8][4];
#pragma unroll
        for (int i = 0; i < 64; i++) (&o[0][0][0])[i] = 0.f;
        const uint32_t vr = w * 2048 + ((lane & 7) + (lane & 8)) * 128;
        const uint32_t vx = ((lane >> 4) ^ (lane & 7)) << 4;
#pragma unroll
        for (int ks = 0; ks < 8; ks++) {
            const uint4 p0 = lds128(sb + SM_PF + (ks * 2 + 0) * 512 + lane * 16);
            const uint4 p1 = lds128(sb + SM_PF + (ks * 2 + 1) * 512 + lane * 16);
            const uint32_t vb = sb + slot_off(IT_C + ks) + vr;
#pragma unroll
            for (int n2 = 0; n2 < 4; n2++) {
                uint32_t b0, b1, b2, b3;
                ldsm4t(vb + (vx ^ (n2 << 5)), b0, b1, b2, b3);
                mma16816(o[0][2 * n2],     p0.x, p0.y, p0.z, p0.w, b0, b1);
                mma16816(o[0][2 * n2 + 1], p0.x, p0.y, p0.z, p0.w, b2, b3);
                mma16816(o[1][2 * n2],     p1.x, p1.y, p1.z, p1.w, b0, b1);
                mma16816(o[1][2 * n2 + 1], p1.x, p1.y, p1.z, p1.w, b2, b3);
            }
            __syncwarp();
            if (lane == 0) mbar_arrive(sb + SM_EMPTY + (IT_C + ks) * 8);
        }
        if (tid == 0) TL(12);
        mbar_wait(sb + SM_FULL + (IT_K1 + 2 + (w >> 1)) * 8);
#pragma unroll
        for (int r = 0; r < 4; r++) {
            const int mt = r >> 1, hi = (r & 1) * 2;
            uint4* dst = gs->op[(8 * r + g) * 4 + (w >> 1)] + (cta >> 6) * 1024 + (w & 1) * 512 + (cta & 63) * 8;
#pragma unroll
            for (int u = 0; u < 2; u++) {
                uint4 v;
                v.x = pack_bf16(o[mt][4 * u][hi],     o[mt][4 * u][hi + 1]);
                v.y = pack_bf16(o[mt][4 * u + 1][hi], o[mt][4 * u + 1][hi + 1]);
                v.z = pack_bf16(o[mt][4 * u + 2][hi], o[mt][4 * u + 2][hi + 1]);
                v.w = pack_bf16(o[mt][4 * u + 3][hi], o[mt][4 * u + 3][hi + 1]);
                dst[(t + 4 * u) ^ (cta & 7)] = v;
            }
        }
        if (tid == 0) TL(29);
        asm volatile("bar.arrive 3, 288;" ::: "memory");
    }

    k_item(IT_K1 + w, sc_w + 256);
    __syncwarp();
    {
        const float4 s = ldsf4(sc_w + lane * 16);
        float m = fmaxf(fmaxf(s.x, s.y), fmaxf(s.z, s.w));
#pragma unroll
        for (int d = 1; d < 32; d <<= 1) m = fmaxf(m, __shfl_xor_sync(0xffffffffu, m, d));
        if (lane == 0) stsf(sb + SM_ML + w * 4, m);
        bar_consumers();
        const float4 m0 = ldsf4(sb + SM_ML), m1 = ldsf4(sb + SM_ML + 16);
        m = fmaxf(fmaxf(fmaxf(m0.x, m0.y), fmaxf(m0.z, m0.w)), fmaxf(fmaxf(m1.x, m1.y), fmaxf(m1.z, m1.w))) * SC;
        const uint32_t p0 = pack_bf16(ex2(fmaf(s.x, SC, -m)), ex2(fmaf(s.y, SC, -m)));
        const uint32_t p1 = pack_bf16(ex2(fmaf(s.z, SC, -m)), ex2(fmaf(s.w, SC, -m)));
        float l = (bf_lo(p0) + bf_hi(p0)) + (bf_lo(p1) + bf_hi(p1));
#pragma unroll
        for (int d = 1; d < 32; d <<= 1) l += __shfl_xor_sync(0xffffffffu, l, d);
        if (lane == 0) stsf(sb + SM_ML + 32 + w * 4, l);
        sts64(sb + SM_PA + w * 256 + lane * 8, p0, p1);
        __syncwarp();
    }
    if (tid == 224) TL(14);

    float oa[4][4];
#pragma unroll
    for (int i = 0; i < 16; i++) (&oa[0][0])[i] = 0.f;
    auto v_item = [&](int item, uint32_t pa) {
        uint32_t p[8];
#pragma unroll
        for (int i = 0; i < 8; i++) p[i] = lds32(pa + i * 16 + t * 4);
        mbar_wait(sb + SM_FULL + item * 8);
        const uint32_t base = sb + slot_off(item) + ((lane & 7) + ((lane >> 4) << 3)) * 256 + ((lane & 8) << 4);
#pragma unroll
        for (int c = 0; c < 8; c++) {
            const uint32_t a = base + ((c ^ (lane & 7)) << 4);
            const uint32_t mask = ((c == (g ^ (2 * t))) ? 0x0000ffffu : 0u) | ((c == (g ^ (2 * t + 1))) ? 0xffff0000u : 0u);
#pragma unroll
            for (int T = 0; T < 4; T++) {
                uint32_t r0, r1, r2, r3;
                ldsm4t(a + T * 4096, r0, r1, r2, r3);
                mma16816(oa[T], r0, r1, r2, r3, p[2 * T] & mask, p[2 * T + 1] & mask);
            }
        }
        __syncwarp();
        if (lane == 0) mbar_arrive8(sb + SM_EMPTY + item * 8);
    };
    v_item(IT_V0 + w, sb + SM_PA + w * 256);
    if (tid == 224) TL(15);

    mbar_wait(sb + SM_FULL + IT_OP * 8);
    if (tid == 0) TLX(96 + IT_OP);
    if (w < 4) {
        const float2 st = ldsf2(sb + SM_MX + tid * 8);
        float m = st.x;
#pragma unroll
        for (int d = 1; d < 32; d <<= 1) m = fmaxf(m, __shfl_xor_sync(0xffffffffu, m, d));
        const uint32_t wb = pack_bf16(ex2(st.x - m), 0.f);
        float l = bf_lo(wb) * st.y;
#pragma unroll
        for (int d = 1; d < 32; d <<= 1) l += __shfl_xor_sync(0xffffffffu, l, d);
#pragma unroll
        for (int bb = 0; bb < 4; bb++) sts16(in0 + bb * 272 + tid * 2, bb == w ? (uint16_t)wb : (uint16_t)0);
        if (lane == 0) stsf(sb + SM_ML + 64 + w * 4, 1.f / l);
    }
    bar_consumers();
    tile_mma<true>(sb, IT_OP, in0, w, lane, acc);
    if (lane < 16) {
        const float inv = ldsf(sb + SM_ML + 64 + g * 4);
        const int ch = 2 * (w & 3);
        const uint32_t dst = in1 + g * 272 + ((w >> 2) * 64 + 8 * (4 * (ch >> 2) + t)) * 2;
        sts32(dst + (ch & 3) * 4,       pack_bf16(acc[0][0] * inv, acc[0][1] * inv));
        sts32(dst + ((ch + 1) & 3) * 4, pack_bf16(acc[1][0] * inv, acc[1][1] * inv));
    }

    {
        const float4 l0 = ldsf4(sb + SM_ML + 32), l1 = ldsf4(sb + SM_ML + 48);
        const float inv = 1.f / (((l0.x + l0.y) + (l0.z + l0.w)) + ((l1.x + l1.y) + (l1.z + l1.w)));
        v_item(IT_V1 + w, sb + SM_PA + w * 256 + 128);
        const uint32_t so = sb + SM_PF + w * 512 + (16 * t + g) * 4;
        stsf(so,       (oa[0][0] + oa[1][0]) + (oa[2][0] + oa[3][0]));
        stsf(so + 32,  (oa[0][1] + oa[1][1]) + (oa[2][1] + oa[3][1]));
        stsf(so + 256, (oa[0][2] + oa[1][2]) + (oa[2][2] + oa[3][2]));
        stsf(so + 288, (oa[0][3] + oa[1][3]) + (oa[2][3] + oa[3][3]));
        bar_consumers();
        if (tid < 64) {
            float x = 0.f, y = 0.f;
#pragma unroll
            for (int i = 0; i < 8; i++) {
                const float2 v = ldsf2(sb + SM_PF + i * 512 + tid * 8);
                x += v.x; y += v.y;
            }
            st_tag2(gs->part[3][h * 4] + j * 128 + tid * 2, x * inv, y * inv, tag);
        }
    }
    if (tid == 0) TL(17);
    asm volatile("bar.arrive 3, 288;" ::: "memory");

    tile_mma<true, false>(sb, IT_WUV, in1, w, lane, acc);
    publish(gs->part[2][cta], w, lane, acc, tag);
    if (tid == 0) TL(16);
    asm volatile("bar.arrive 6, 288;" ::: "memory");

    asm volatile("bar.sync 5, 288;" ::: "memory");
    tile_mma<true, false>(sb, IT_WOA, in0, w, lane, acc);
    publish(gs->fin[1][h][j], w, lane, acc, tag);
    if (tid == 224) TL(19);
    asm volatile("bar.sync 4, 288;" ::: "memory");
    tile_mma<true, false>(sb, IT_WOB, in1, w, lane, acc);
    publish(gs->fin[0][h][j], w, lane, acc, tag);
    if (tid == 224) TLX(26);
    if (w < NPOLL) {
        const uint32_t t0 = clock();
        while (__all_sync(0xffffffffu, (int)(clock() - t0) < w * FGAP + FDEL)) {}
        final_reduce<true>(&gs->fin[0][lane >> 2][0][cta * 16 + (lane & 3) * 4], out + j * 1024 + 512 + h * 16 + 2 * (lane & 3), lane, tag, 0, sb + SM_ML + 80);
        if (lane == 0) TLX(4);
    }
}

typedef CUresult (*EncodeTiledFn)(CUtensorMap*, CUtensorMapDataType, cuuint32_t, void*, const cuuint64_t*,
                                  const cuuint64_t*, const cuuint32_t*, const cuuint32_t*, CUtensorMapInterleave,
                                  CUtensorMapSwizzle, CUtensorMapL2promotion, CUtensorMapFloatOOBfill);

void encode_map(EncodeTiledFn enc, CUtensorMap* tm, const void* p, cuuint64_t cols, cuuint64_t rows,
                cuuint32_t brows, cuuint32_t bblk) {
    cuuint64_t dims[3] = {64, rows, cols / 64};
    cuuint64_t strides[2] = {cols * 2, 128};
    cuuint32_t box[3] = {64, brows, bblk};
    cuuint32_t es[3] = {1, 1, 1};
    enc(tm, CU_TENSOR_MAP_DATA_TYPE_BFLOAT16, 3, const_cast<void*>(p), dims, strides, box, es,
        CU_TENSOR_MAP_INTERLEAVE_NONE, CU_TENSOR_MAP_SWIZZLE_128B, CU_TENSOR_MAP_L2_PROMOTION_L2_256B,
        CU_TENSOR_MAP_FLOAT_OOB_FILL_NONE);
}

}

extern "C" void kernel_launch(void* const* d_in, const int* in_sizes, int n_in, void* d_out, int out_size) {
    (void)in_sizes; (void)n_in; (void)out_size;
    static EncodeTiledFn enc = nullptr;
    static Scratch* gs = nullptr;
    if (!enc) {
        cudaGetSymbolAddress((void**)&gs, g_scratch);
        void* fn = nullptr;
        cudaDriverEntryPointQueryResult qr;
        cudaGetDriverEntryPoint("cuTensorMapEncodeTiled", &fn, cudaEnableDefault, &qr);
        enc = (EncodeTiledFn)fn;
        cudaFuncSetAttribute(fused_decode_kernel, cudaFuncAttributeMaxDynamicSharedMemorySize, SM_END);
    }
    Maps maps;
    encode_map(enc, &maps.wqB, d_in[7], 4096, 512, 64, 2);
    encode_map(enc, &maps.wqA, d_in[3], 4096, 512, 64, 2);
    encode_map(enc, &maps.wuk, d_in[8], 4096, 512, 64, 2);
    encode_map(enc, &maps.wuv, d_in[9], 4096, 512, 64, 2);
    encode_map(enc, &maps.woB, d_in[10], 512, 4096, 64, 2);
    encode_map(enc, &maps.woA, d_in[4], 512, 4096, 64, 2);
    encode_map(enc, &maps.ckv, d_in[6], 512, 16384, 16, 8);
    fused_decode_kernel<<<NCTA, NTHR, SM_END>>>((const __nv_bfloat16*)d_in[0], (const __nv_bfloat16*)d_in[5],
                                                (const __nv_bfloat16*)d_in[1], (const __nv_bfloat16*)d_in[2],
                                                (__nv_bfloat16*)d_out, gs, maps);
}
```

```cpp
#include <cuda_runtime.h>
#include <cuda_bf16.h>
#include <cuda.h>
#include <stdint.h>

namespace {

constexpr int NCTA   = 128;
constexpr int NSLOT  = 13;
constexpr int SLOT   = 16384;
constexpr int NITEM  = 56;
#define INFLIGHT 4
#define PACE 650
#define OFFS 500
#define STAG 0
#define OWAIT 0
#define FINMODE 1
#define FINDELAY 0
#define NFIRST 2
#define STARTER 256
#define CTXWAIT 0
#define LATAT 45
#define TAPER 300
#define TAPER_AT 49
#define TAPER_N 1
#define STG_AT 2
#define STG_SH 1
#define GLEAD 150
#define AEARLY 0
#define BEARLY 0
#define DRAIN_AT 99
#define DRAIN 2
#define AWAIT 0
#define NPOLL 4
#define FGAP 170
#define FDEL 0
constexpr int NTHR   = 320;
#define BAR2 "bar.sync 2, 320;"

constexpr int IT_WQB = 0, IT_WQA = 2, IT_WUK = 4, IT_K0 = 6, IT_Q = 14, IT_C = 16, IT_K1 = 24, IT_V0 = 32,
              IT_OP = 40, IT_V1 = 42, IT_WUV = 50, IT_WO = 52;
constexpr int IT_X = 56;
constexpr int IT_W2 = 58;
constexpr int BAR_LAT = 56, BAR_FIN = 57, BAR_X = 59, BAR_PEER = 60;

constexpr int SM_FULL  = NSLOT * SLOT;
constexpr int SM_EMPTY = SM_FULL + 512;
constexpr int SM_IN0   = SM_EMPTY + 512;
constexpr int SM_IN1   = SM_IN0 + 1088;
constexpr int SM_SC    = SM_IN1 + 1088;
constexpr int SM_PA    = SM_SC + 4096;
constexpr int SM_PF    = SM_PA + 2048;
constexpr int SM_MX    = SM_PF + 8192;
constexpr int SM_ML    = SM_MX + 1024;
constexpr int SM_RCV   = SM_ML + 128;
constexpr int SM_END   = SM_RCV + 144;
constexpr int SM_LAT   = SM_PF + 4096;
constexpr int SM_FIN   = SM_SC;
constexpr int SM_SUM   = SM_IN0;
static_assert(SM_END <= 232448, "smem");

struct Maps { CUtensorMap wqB, wqA, wuk, wuv, woA, woB, ckv; };

struct Scratch {
    unsigned cnt[32];
    float    part[2][NCTA][512];
    uint32_t x[2][32][256];
    uint32_t lat[32][4][256];
    uint4    q[4][2048];
    uint4    op[NCTA][2048];
    float2   stat[32][128];
};
__device__ __align__(128) Scratch g_scratch;
#define TLX(i) do {} while (0)
#define TL(i) do {} while (0)

constexpr int SPIN_LIMIT = 1 << 22;

__device__ __forceinline__ uint32_t smem_u32(const void* p) { return (uint32_t)__cvta_generic_to_shared(p); }
__device__ __forceinline__ void mbar_init(uint32_t bar, uint32_t cnt) {
    asm volatile("mbarrier.init.shared::cta.b64 [%0], %1;" ::"r"(bar), "r"(cnt) : "memory");
}
__device__ __forceinline__ void mbar_expect_tx(uint32_t bar, uint32_t bytes) {
    asm volatile("mbarrier.arrive.expect_tx.shared::cta.b64 _, [%0], %1;" ::"r"(bar), "r"(bytes) : "memory");
}
__device__ __forceinline__ void mbar_arrive(uint32_t bar) {
    asm volatile("mbarrier.arrive.shared::cta.b64 _, [%0];" ::"r"(bar) : "memory");
}
__device__ __forceinline__ void mbar_arrive8(uint32_t bar) {
    asm volatile("mbarrier.arrive.shared::cta.b64 _, [%0], 8;" ::"r"(bar) : "memory");
}
__device__ __forceinline__ void mbar_wait(uint32_t bar) {
    uint32_t done;
    int it = 0;
    do {
        asm volatile("{\n.reg .pred p;\nmbarrier.try_wait.parity.shared::cta.b64 p, [%1], 0;\nselp.u32 %0, 1, 0, p;\n}"
                     : "=r"(done) : "r"(bar) : "memory");
        if (++it > SPIN_LIMIT) __trap();
    } while (!done);
}
__device__ __forceinline__ uint32_t map_cta(uint32_t a, uint32_t rank) {
    uint32_t r; asm("mapa.shared::cluster.u32 %0, %1, %2;" : "=r"(r) : "r"(a), "r"(rank)); return r;
}
__device__ __forceinline__ void st_async32(uint32_t a, uint32_t v, uint32_t bar) {
    asm volatile("st.async.shared::cluster.mbarrier::complete_tx::bytes.b32 [%0], %1, [%2];" ::"r"(a), "r"(v), "r"(bar) : "memory");
}
__device__ __forceinline__ void bulk_load(uint32_t dst, const void* src, uint32_t bytes, uint32_t bar, uint64_t pol) {
    asm volatile("cp.async.bulk.shared::cluster.global.mbarrier::complete_tx::bytes.L2::cache_hint [%0], [%1], %2, [%3], %4;"
                 ::"r"(dst), "l"(src), "r"(bytes), "r"(bar), "l"(pol) : "memory");
}
__device__ __forceinline__ void bulk_load_nohint(uint32_t dst, const void* src, uint32_t bytes, uint32_t bar) {
    asm volatile("cp.async.bulk.shared::cluster.global.mbarrier::complete_tx::bytes [%0], [%1], %2, [%3];"
                 ::"r"(dst), "l"(src), "r"(bytes), "r"(bar) : "memory");
}
__device__ __forceinline__ void bulk_load_pair(uint32_t dst, const void* src, uint32_t bytes, uint32_t bar) {
    asm volatile("cp.async.bulk.shared::cluster.global.mbarrier::complete_tx::bytes.multicast::cluster [%0], [%1], %2, [%3], %4;"
                 ::"r"(dst), "l"(src), "r"(bytes), "r"(bar), "h"((uint16_t)3) : "memory");
}
__device__ __forceinline__ void tma3d(uint32_t dst, const CUtensorMap* tm, int c0, int c1, int c2, uint32_t bar, uint64_t pol) {
    asm volatile("cp.async.bulk.tensor.3d.shared::cluster.global.mbarrier::complete_tx::bytes.L2::cache_hint [%0], [%1, {%3, %4, %5}], [%2], %6;"
                 ::"r"(dst), "l"(tm), "r"(bar), "r"(c0), "r"(c1), "r"(c2), "l"(pol) : "memory");
}
__device__ __forceinline__ void tma3d_pair(uint32_t dst, const CUtensorMap* tm, int c0, int c1, int c2, uint32_t bar, uint64_t pol) {
    asm volatile("cp.async.bulk.tensor.3d.shared::cluster.global.mbarrier::complete_tx::bytes.multicast::cluster.L2::cache_hint [%0], [%1, {%3, %4, %5}], [%2], %7, %6;"
                 ::"r"(dst), "l"(tm), "r"(bar), "r"(c0), "r"(c1), "r"(c2), "l"(pol), "h"((uint16_t)3) : "memory");
}
__device__ __forceinline__ void ldsm4(uint32_t a, uint32_t& r0, uint32_t& r1, uint32_t& r2, uint32_t& r3) {
    asm volatile("ldmatrix.sync.aligned.m8n8.x4.shared.b16 {%0,%1,%2,%3}, [%4];"
                 : "=r"(r0), "=r"(r1), "=r"(r2), "=r"(r3) : "r"(a) : "memory");
}
__device__ __forceinline__ void ldsm4t(uint32_t a, uint32_t& r0, uint32_t& r1, uint32_t& r2, uint32_t& r3) {
    asm volatile("ldmatrix.sync.aligned.m8n8.x4.trans.shared.b16 {%0,%1,%2,%3}, [%4];"
                 : "=r"(r0), "=r"(r1), "=r"(r2), "=r"(r3) : "r"(a) : "memory");
}
__device__ __forceinline__ void mma16816(float (&c)[4], uint32_t a0, uint32_t a1, uint32_t a2, uint32_t a3,
                                         uint32_t b0, uint32_t b1) {
    asm volatile("mma.sync.aligned.m16n8k16.row.col.f32.bf16.bf16.f32 {%0,%1,%2,%3}, {%4,%5,%6,%7}, {%8,%9}, {%0,%1,%2,%3};"
                 : "+f"(c[0]), "+f"(c[1]), "+f"(c[2]), "+f"(c[3])
                 : "r"(a0), "r"(a1), "r"(a2), "r"(a3), "r"(b0), "r"(b1));
}
__device__ __forceinline__ uint32_t lds32(uint32_t a) {
    uint32_t v; asm volatile("ld.shared.b32 %0, [%1];" : "=r"(v) : "r"(a) : "memory"); return v;
}
__device__ __forceinline__ float ldsf(uint32_t a) {
    float v; asm volatile("ld.shared.f32 %0, [%1];" : "=f"(v) : "r"(a) : "memory"); return v;
}
__device__ __forceinline__ float2 ldsf2(uint32_t a) {
    float2 v; asm volatile("ld.shared.v2.f32 {%0,%1}, [%2];" : "=f"(v.x), "=f"(v.y) : "r"(a) : "memory"); return v;
}
__device__ __forceinline__ float4 ldsf4(uint32_t a) {
    float4 v; asm volatile("ld.shared.v4.f32 {%0,%1,%2,%3}, [%4];" : "=f"(v.x), "=f"(v.y), "=f"(v.z), "=f"(v.w) : "r"(a) : "memory"); return v;
}
__device__ __forceinline__ uint4 lds128(uint32_t a) {
    uint4 v; asm volatile("ld.shared.v4.b32 {%0,%1,%2,%3}, [%4];" : "=r"(v.x), "=r"(v.y), "=r"(v.z), "=r"(v.w) : "r"(a) : "memory"); return v;
}
__device__ __forceinline__ uint4 lds128_if(uint32_t a, bool on) {
    uint4 v;
    asm volatile("{\n.reg .pred p;\nsetp.ne.u32 p, %5, 0;\n@p ld.shared.v4.b32 {%0,%1,%2,%3}, [%4];\n}"
                 : "=r"(v.x), "=r"(v.y), "=r"(v.z), "=r"(v.w) : "r"(a), "r"((uint32_t)on) : "memory");
    return v;
}
__device__ __forceinline__ void stsf_if(uint32_t a, float v, bool on) {
    asm volatile("{\n.reg .pred p;\nsetp.ne.u32 p, %2, 0;\n@p st.shared.f32 [%0], %1;\n}" ::"r"(a), "f"(v), "r"((uint32_t)on) : "memory");
}
__device__ __forceinline__ void sts16(uint32_t a, uint16_t v) { asm volatile("st.shared.b16 [%0], %1;" ::"r"(a), "h"(v) : "memory"); }
__device__ __forceinline__ void sts32(uint32_t a, uint32_t v) { asm volatile("st.shared.b32 [%0], %1;" ::"r"(a), "r"(v) : "memory"); }
__device__ __forceinline__ void stsf(uint32_t a, float v) { asm volatile("st.shared.f32 [%0], %1;" ::"r"(a), "f"(v) : "memory"); }
__device__ __forceinline__ void sts64(uint32_t a, uint32_t x, uint32_t y) {
    asm volatile("st.shared.v2.b32 [%0], {%1,%2};" ::"r"(a), "r"(x), "r"(y) : "memory");
}
__device__ __forceinline__ void sts128(uint32_t a, uint4 v) {
    asm volatile("st.shared.v4.b32 [%0], {%1,%2,%3,%4};" ::"r"(a), "r"(v.x), "r"(v.y), "r"(v.z), "r"(v.w) : "memory");
}
__device__ __forceinline__ uint32_t pack_bf16(float lo, float hi) {
    uint32_t r; asm("cvt.rn.bf16x2.f32 %0, %1, %2;" : "=r"(r) : "f"(hi), "f"(lo)); return r;
}
__device__ __forceinline__ float bf_lo(uint32_t v) { return __uint_as_float(v << 16); }
__device__ __forceinline__ float bf_hi(uint32_t v) { return __uint_as_float(v & 0xffff0000u); }
__device__ __forceinline__ float ex2(float x) { float y; asm("ex2.approx.ftz.f32 %0, %1;" : "=f"(y) : "f"(x)); return y; }
__device__ __forceinline__ uint32_t timer_ns() { uint32_t t; asm volatile("mov.u32 %0, %%globaltimer_lo;" : "=r"(t)); return t; }
__device__ __forceinline__ void bar_consumers() { asm volatile("bar.sync 1, 256;" ::: "memory"); }

__device__ __forceinline__ uint32_t tagf(float v, uint32_t tag) { return (__float_as_uint(v) & 0xffffff00u) | tag; }
__device__ __forceinline__ uint2 ld_rlx2(const float* p) {
    uint2 v; asm volatile("ld.relaxed.gpu.global.v2.b32 {%0,%1}, [%2];" : "=r"(v.x), "=r"(v.y) : "l"(p) : "memory"); return v;
}
__device__ __forceinline__ float untag(uint32_t v) { return __uint_as_float(v & 0xffffff00u); }

__device__ __forceinline__ uint32_t slot_off(int item) { return (uint32_t)(item % NSLOT) * SLOT; }

template <bool TRANS, bool RELEASE = true>
__device__ __forceinline__ void tile_mma(uint32_t sb, int item, uint32_t in, int w, int lane, float (&acc)[2][2]) {
    const int g = lane >> 2, t = lane & 3;
    float c[4][4];
#pragma unroll
    for (int i = 0; i < 16; i++) (&c[0][0])[i] = 0.f;
    uint32_t a[16];
    const uint32_t ia = in + (g & 3) * 272 + t * 4;
#pragma unroll
    for (int i = 0; i < 16; i++) a[i] = lds32(ia + i * 16);
    const uint32_t s0 = sb + slot_off(item), s1 = sb + slot_off(item + 1);
    if (TRANS) {
        const int r = (lane & 7) + (lane & 8);
        const int ch = 2 * (w & 3) + (lane >> 4);
        const uint32_t off = (w >> 2) * 8192 + r * 128 + ((ch ^ (lane & 7)) << 4);
#pragma unroll
        for (int kk = 0; kk < 8; kk++) {
            if ((kk & 3) == 0) mbar_wait(sb + SM_FULL + (item + (kk >> 2)) * 8);
            uint32_t r0, r1, r2, r3;
            ldsm4t(((kk >> 2) ? s1 : s0) + off + (kk & 3) * 2048, r0, r1, r2, r3);
            mma16816(c[2 * (kk & 1)],     a[2 * kk], 0u, a[2 * kk + 1], 0u, r0, r1);
            mma16816(c[2 * (kk & 1) + 1], a[2 * kk], 0u, a[2 * kk + 1], 0u, r2, r3);
        }
    } else {
        mbar_wait(sb + SM_FULL + (item + (w >> 2)) * 8);
        const int r = 16 * (w & 3) + (lane & 7) + ((lane >> 4) << 3);
        const uint32_t base = ((w >> 2) ? s1 : s0) + r * 128 + ((((lane >> 3) & 1) ^ (lane & 7)) << 4);
#pragma unroll
        for (int kk = 0; kk < 8; kk++) {
            uint32_t r0, r1, r2, r3;
            ldsm4((base ^ ((kk & 3) << 5)) + (kk >> 2) * 8192, r0, r1, r2, r3);
            mma16816(c[2 * (kk & 1)],     a[2 * kk], 0u, a[2 * kk + 1], 0u, r0, r1);
            mma16816(c[2 * (kk & 1) + 1], a[2 * kk], 0u, a[2 * kk + 1], 0u, r2, r3);
        }
    }
    if (RELEASE) {
        __syncwarp();
        if (lane == 0) {
            mbar_arrive(sb + SM_EMPTY + item * 8);
            mbar_arrive(sb + SM_EMPTY + (item + 1) * 8);
        }
    }
    acc[0][0] = c[0][0] + c[2][0]; acc[0][1] = c[0][1] + c[2][1];
    acc[1][0] = c[1][0] + c[3][0]; acc[1][1] = c[1][1] + c[3][1];
}

__device__ __forceinline__ void publish(float* dst, int w, int lane, const float (&acc)[2][2], uint32_t tag) {
    if (lane < 16)
        asm volatile("st.relaxed.gpu.global.v4.b32 [%0], {%1,%2,%3,%4};" ::"l"(dst + w * 64 + lane * 4),
                     "r"(tagf(acc[0][0], tag)), "r"(tagf(acc[0][1], tag)), "r"(tagf(acc[1][0], tag)), "r"(tagf(acc[1][1], tag)) : "memory");
}

__device__ __forceinline__ void gather(const float* part, uint32_t in, int tid, uint32_t tag) {
    const float* p = part + tid * 2;
    uint2 v0, v1, v2, v3;
    int it = 0;
    while (true) {
        v0 = ld_rlx2(p); v1 = ld_rlx2(p + 512); v2 = ld_rlx2(p + 1024); v3 = ld_rlx2(p + 1536);
        uint32_t bad = ((v0.x ^ tag) | (v0.y ^ tag) | (v1.x ^ tag) | (v1.y ^ tag) |
                        (v2.x ^ tag) | (v2.y ^ tag) | (v3.x ^ tag) | (v3.y ^ tag)) & 0xffu;
        if (__all_sync(0xffffffffu, bad == 0)) break;
        if (++it > SPIN_LIMIT) __trap();
    }
    float x = (untag(v0.x) + untag(v1.x)) + (untag(v2.x) + untag(v3.x));
    float y = (untag(v0.y) + untag(v1.y)) + (untag(v2.y) + untag(v3.y));
    sts32(in + ((tid >> 3) & 3) * 272 + (tid >> 5) * 32 + (tid & 1) * 16 + (tid & 6) * 2, pack_bf16(x, y));
    bar_consumers();
}

constexpr uint32_t EMPTY = 0xffffffffu;
__device__ __forceinline__ void st_rlx(uint32_t* p, uint32_t v) {
    asm volatile("st.relaxed.gpu.global.b32 [%0], %1;" ::"l"(p), "r"(v) : "memory");
}
__device__ __forceinline__ void st_rlx2(uint32_t* p, uint32_t v0, uint32_t v1) {
    asm volatile("st.relaxed.gpu.global.v2.b32 [%0], {%1,%2};" ::"l"(p), "r"(v0), "r"(v1) : "memory");
}
__device__ __forceinline__ void ld_rlx4_if(uint4& v, const void* p, bool need) {
    asm volatile("{\n.reg .pred p;\nsetp.ne.u32 p, %5, 0;\n@p ld.relaxed.gpu.global.v4.b32 {%0,%1,%2,%3}, [%4];\n}"
                 : "+r"(v.x), "+r"(v.y), "+r"(v.z), "+r"(v.w) : "l"(p), "r"((uint32_t)need) : "memory");
}

template <int HALF, class F>
__device__ __forceinline__ bool refetch(uint4 (&x)[8], int lane, F addr) {
    uint32_t m[8], m0 = 0, m1 = 0;
#pragma unroll
    for (int i = 0; i < 8; i++) {
        m[i] = max(max(x[i].x, x[i].y), max(x[i].z, x[i].w));
        if (i < HALF) m0 = max(m0, m[i]); else m1 = max(m1, m[i]);
    }
    if (!__any_sync(0xffffffffu, (m0 == EMPTY && lane < 16) || m1 == EMPTY)) return false;
#pragma unroll
    for (int i = 0; i < 8; i++) ld_rlx4_if(x[i], addr(i), m[i] == EMPTY && (i >= HALF || lane < 16));
    return true;
}

__device__ __forceinline__ unsigned read_counter(const unsigned* cnt) {
    unsigned v;
    asm volatile("ld.relaxed.gpu.global.u32 %0, [%1];" : "=r"(v) : "l"(cnt) : "memory");
    return v;
}
__device__ __forceinline__ unsigned epoch_of(unsigned cnt) {
    asm volatile("" : "+r"(cnt) :: "memory");
    return cnt / NCTA + 1;
}
__device__ __forceinline__ uint32_t epoch_tag(unsigned epoch) { return (epoch & 0x7fu) | 0x80u; }

__device__ __forceinline__ void signal_and_wait(unsigned* cnt, unsigned target, int lane, uint32_t sb) {
    if (lane == 0) asm volatile("red.release.gpu.global.add.u32 [%0], 1;" ::"l"(cnt) : "memory");
    if (lane == 0) TL(30 + (((size_t)cnt >> 2) & 1));
    int it = 0;
    while (true) {
        unsigned v;
        asm volatile("ld.acquire.gpu.global.u32 %0, [%1];" : "=r"(v) : "l"(cnt) : "memory");
        if (__all_sync(0xffffffffu, (int)(v - target) >= 0)) break;
        if (++it > SPIN_LIMIT) __trap();
    }
    asm volatile("fence.proxy.async.global;" ::: "memory");
}

__global__ void __cluster_dims__(2, 1, 1) __launch_bounds__(NTHR, 1)
fused_decode_kernel(const __nv_bfloat16* __restrict__ xA, const __nv_bfloat16* __restrict__ xB,
                    const __nv_bfloat16* __restrict__ Kc, const __nv_bfloat16* __restrict__ Vc,
                    __nv_bfloat16* __restrict__ out, Scratch* gs, const __grid_constant__ Maps maps) {
    extern __shared__ __align__(1024) unsigned char smem_raw[];
    const uint32_t sb = smem_u32(smem_raw);
    const int tid = threadIdx.x, lane = tid & 31;
    const int cta = blockIdx.x, h = cta >> 2, j = cta & 3;
    const size_t kv_off = ((size_t)(j * 32 + h) * 4096 + 3072) * 128;
    uint64_t pol;
    asm volatile("createpolicy.fractional.L2::evict_first.b64 %0, 1.0;" : "=l"(pol));
    const unsigned cnt1 = read_counter(&gs->cnt[1]);
    uint4 xv;
    if (tid < 128) {
        const __nv_bfloat16* x = (tid < 64 ? xB : xA) + ((tid >> 4) & 3) * 512 + j * 128 + (tid & 15) * 8;
        xv = __ldg(reinterpret_cast<const uint4*>(x));
    }
    if (tid == STARTER) {
        TLX(0);
        asm volatile("cp.async.bulk.prefetch.L2.global [%0], %1;" ::"l"(Kc + kv_off), "r"(SLOT) : "memory");
#pragma unroll
        for (int i = 0; i < NFIRST; i++) mbar_init(sb + SM_FULL + i * 8, 1);
        asm volatile("fence.mbarrier_init.release.cluster;" ::: "memory");
#pragma unroll
        for (int i = 0; i < NFIRST; i++) {
            TLX(32 + i);
            mbar_expect_tx(sb + SM_FULL + i * 8, SLOT);
            tma3d(sb + i * SLOT, &maps.wqB, 0, j * 128 + i * 64, h * 2, sb + SM_FULL + i * 8, pol);
        }
    }
    uint32_t tnext = timer_ns() + (NFIRST + 1) * PACE - OFFS + STAG * cta * PACE / NCTA;
    if (tid == 0) TLX(21);
    const int w = __shfl_sync(0xffffffffu, tid >> 5, 0);
    const int pr = cta >> 1;
    const int slice = pr < 4 ? pr : pr < 36 ? 4 + ((pr - 4) & 7) * 4 + ((pr - 4) >> 3) : 36 + (pr - 36) % 7 * 4 + (pr - 36) / 7;

    if (w >= 8) {
        if (w == 8) {
            asm volatile(BAR2 ::: "memory");
            int slot = NFIRST, tail = NFIRST - INFLIGHT;
#pragma unroll 1
            for (int i = NFIRST; i < NITEM; i++) {
                const uint32_t dst = sb + slot * SLOT, bar = sb + SM_FULL + i * 8;
                if (++slot == NSLOT) slot = 0;
                if ((i & ~1) == IT_Q || (i & ~1) == IT_OP) continue;
                const bool ckv = i >= IT_C && i < IT_K1, wo = i >= IT_WO;
                const bool tiled = ckv || i < IT_K0 || i >= IT_WUV;
                const CUtensorMap* tm = &maps.wqB + (i < IT_K0 ? (i >> 1) : ckv ? 6 : wo ? 4 + (slice >> 5) : 3);
                const int c0 = wo ? (slice & 31) * 16 : i >= IT_WUV ? cta * 32 : 0;
                const int c1 = i < IT_K0 ? j * 128 + (i & 1) * 64 : ckv ? cta * 128 + (i - IT_C) * 16 : 0;
                const int c2 = i < IT_K0 ? h * 2 : ckv ? 0 : wo ? (i - IT_WO) * 4 + (j & 1) * 2 : i & 1;
                const int c = i < IT_Q ? i - IT_K0 : i < IT_V0 ? i - IT_K1 + 8 : i < IT_OP ? i - IT_V0 : i - IT_V1 + 8;
                const __nv_bfloat16* src = (i < IT_V0 ? Kc : Vc) + kv_off + (size_t)c * (SLOT / 2);
                if (i >= NSLOT) mbar_wait(sb + SM_EMPTY + (i - NSLOT) * 8);
                if (tail >= 0) mbar_wait(sb + SM_FULL + tail * 8);
                ++tail;
                if (tail == IT_Q || tail == IT_OP) tail += 2;
                if (i >= DRAIN_AT) mbar_wait(sb + SM_FULL + (i - DRAIN) * 8);
                if (i == NITEM - 1) {
                    mbar_wait(sb + SM_EMPTY + (IT_W2 - NSLOT) * 8);
                    mbar_wait(sb + SM_FULL + BAR_PEER * 8);
                }
                if (i == NITEM - 1 - (slice < 32 ? AEARLY : BEARLY)) {
                    while (__all_sync(0xffffffffu, (int)(timer_ns() - (tnext - GLEAD)) < 0)) {}
                    asm volatile("bar.arrive 4, 64;" ::: "memory");
                }
                if (i != IT_K0) {
                    while (__all_sync(0xffffffffu, (int)(timer_ns() - tnext) < 0)) {}
                    tnext += PACE;
                    if (i >= TAPER_AT && i < TAPER_AT + TAPER_N) tnext += TAPER;
                }
                if (lane == 0) {
                    TLX(32 + i);
                    if (i == NITEM - 1) tma3d_pair(dst + (j & 1) * (IT_W2 - i) * SLOT, tm, c0, c1, c2, bar + (j & 1) * (IT_W2 - i) * 8, pol);
                    else if (tiled) tma3d(dst, tm, c0, c1, c2, bar, pol);
                    else bulk_load(dst, src, SLOT, bar, pol);
                }
            }
        } else {
            if (lane == 0) {
                mbar_init(sb + SM_FULL + IT_W2 * 8, 1);
                mbar_init(sb + SM_FULL + BAR_X * 8, 1);
                mbar_init(sb + SM_FULL + BAR_PEER * 8, 1);
                mbar_expect_tx(sb + SM_FULL + IT_W2 * 8, SLOT);
                mbar_expect_tx(sb + SM_FULL + BAR_X * 8, SLOT + 4096);
                mbar_expect_tx(sb + SM_FULL + BAR_PEER * 8, 4);
                asm volatile("fence.mbarrier_init.release.cluster;" ::: "memory");
            }
            if (lane < 6) asm volatile("prefetch.tensormap [%0];" ::"l"(&maps.wqA + lane) : "memory");
            asm volatile(BAR2 ::: "memory");
            asm volatile("bar.sync 3, 288;" ::: "memory");
            const unsigned epoch = epoch_of(cnt1);
            if (lane == 0) TL(9);
            signal_and_wait(&gs->cnt[0], epoch * NCTA, lane, sb);
            if (lane == 0) {
                TL(2);
                const uint4* q = gs->q[cta >> 5];
                bulk_load_nohint(sb + slot_off(IT_Q), q, SLOT, sb + SM_FULL + IT_Q * 8);
                bulk_load_nohint(sb + slot_off(IT_Q + 1), q + 1024, SLOT, sb + SM_FULL + (IT_Q + 1) * 8);
            }
            asm volatile("bar.sync 3, 288;" ::: "memory");
            if (lane == 0) TL(13);
            signal_and_wait(&gs->cnt[1], epoch * NCTA, lane, sb);
            mbar_wait(sb + SM_EMPTY + (IT_OP - NSLOT) * 8);
            mbar_wait(sb + SM_EMPTY + (IT_OP + 1 - NSLOT) * 8);
            if (lane == 0) {
                TL(3);
                const uint4* op = gs->op[cta];
                bulk_load_nohint(sb + SM_MX, gs->stat[h], 1024, sb + SM_FULL + IT_OP * 8);
                bulk_load_nohint(sb + slot_off(IT_OP), op, SLOT, sb + SM_FULL + IT_OP * 8);
                bulk_load_nohint(sb + slot_off(IT_OP + 1), op + 1024, SLOT, sb + SM_FULL + (IT_OP + 1) * 8);
            }
            mbar_wait(sb + SM_FULL + LATAT * 8);
            if (lane == 0) bulk_load_nohint(sb + SM_LAT, gs->lat[h], 4096, sb + SM_FULL + BAR_LAT * 8);
            mbar_wait(sb + SM_EMPTY + (IT_X - NSLOT) * 8);
            mbar_wait(sb + SM_EMPTY + (IT_X + 1 - NSLOT) * 8);
            asm volatile("bar.sync 4, 64;" ::: "memory");
            if (lane == 0) {
                TL(27);
                bulk_load_nohint(sb + slot_off(IT_X), gs->x[slice >> 5][(j & 1) * 12], SLOT + 4096, sb + SM_FULL + BAR_X * 8);
            }
        }
        const uint32_t oo  = __shfl_sync(0xffffffffu, (lane >> 3) * 2048 + slice * 32 + (j & 1) * 16 + (lane & 7) * 2, lane);
        const uint32_t src = __shfl_sync(0xffffffffu, sb + SM_FIN + ((j ^ w ^ 1) & 1) * 1536 + lane * 48, lane);
        const uint32_t sr2 = __shfl_sync(0xffffffffu, sb + SM_FIN + 3072 + lane * 80, lane);
        const uint32_t to  = w == 8 ? map_cta(sb, (j & 1) ^ 1) : sb;
        const uint32_t rcv = __shfl_sync(0xffffffffu, to + SM_RCV + lane * 4, lane);
        const uint32_t fin = __shfl_sync(0xffffffffu, to + SM_FULL + BAR_FIN * 8, lane);
        mbar_wait(sb + SM_FULL + (NITEM - 3) * 8);
        asm volatile("bar.sync 5, 320;" ::: "memory");
        const float4 p0 = ldsf4(src), p1 = ldsf4(src + 16);
        float sum = ((p0.x + p0.y) + (p0.z + p0.w)) + ((p1.x + p1.y) + (p1.z + p1.w));
        if (w == 8) {
            st_async32(rcv, __float_as_uint(sum), fin);
        } else {
            __nv_bfloat16* dst = reinterpret_cast<__nv_bfloat16*>(reinterpret_cast<char*>(out) + oo);
            mbar_wait(sb + SM_FULL + BAR_FIN * 8);
            if (lane == 0) TLX(154);
            sum += ldsf(rcv);
            asm volatile("bar.sync 7, 288;" ::: "memory");
            const float4 q0 = ldsf4(sr2), q1 = ldsf4(sr2 + 16), q2 = ldsf4(sr2 + 32), q3 = ldsf4(sr2 + 48);
            *dst = __float2bfloat16((((q0.x + sum) + q0.y) + (q0.z + q0.w) + ((q1.x + q1.y) + (q1.z + q1.w))) +
                                    (((q2.x + q2.y) + (q2.z + q2.w)) + ((q3.x + q3.y) + (q3.z + q3.w))));
            if (lane == 0) TLX(4);
        }
        return;
    }

    const int g = lane >> 2, t = lane & 3;
    const uint32_t in0 = sb + SM_IN0, in1 = sb + SM_IN1;
    const int hx = (h & 4) * 4 + (((h >> 3) + (h >> 2 & 1)) & 3) * 4 + (h & 3);
    uint32_t* const ctx_dst = &gs->x[1][hx][(j * 4 + (w & 3)) * 16 + ((g ^ (w & 2)) & 3) * 4 + ((t - w) & 3)];
    uint32_t* const o_dst = &gs->x[0][hx][j * 64 + ((tid & 60) ^ ((j & 1) * 16)) + ((t - g) & 3)];
    uint32_t* const lat_dst = &gs->lat[h][g & 3][j * 64 + ((w >> 1) ^ (g & 1)) * 16 + t * 4 + ((w * 2 ^ t) & 2)];
    {
        if (lane == 0) {
            const uint32_t bars = sb + (w < 4 ? SM_EMPTY : SM_FULL + NFIRST * 8) + (w & 3) * 14 * 8;
            const uint32_t cnt = w < 4 ? 8 : 1;
#pragma unroll
            for (int i = 0; i < 14; i++) mbar_init(bars + i * 8, cnt);
            if (w >= 4) {
#pragma unroll
                for (int i = 0; i < 14; i++)
                    mbar_expect_tx(bars + i * 8, (i == (IT_OP - NFIRST) % 14 && w == 4 + (IT_OP - NFIRST) / 14) ? SLOT + 1024 :
                                                 (i >= 12 && w == 7) ? (i == 12 ? 4096 : 128) : SLOT);
            }
            asm volatile("fence.mbarrier_init.release.cluster;" ::: "memory");
        }
        if (tid == 0) TL(22);
        asm volatile(BAR2 ::: "memory");
        if (lane < 16) st_rlx2(lat_dst, EMPTY, EMPTY);
        if (lane < 16 && w < 4) st_rlx(ctx_dst, EMPTY);
        if (tid < 64) st_rlx(o_dst, EMPTY);
        if (tid < 128) sts128((tid < 64 ? in0 : in1) + ((tid >> 4) & 3) * 272 + (tid & 15) * 16, xv);
    }
    bar_consumers();
    const uint32_t tag = epoch_tag(epoch_of(cnt1));
    if (tid == 0) TL(23);

    float acc[2][2];
    tile_mma<true>(sb, IT_WQB, in0, w, lane, acc);
    if (tid == 0) TL(24);
    publish(gs->part[0][cta], w, lane, acc, tag);
    if (tid == 0) TL(6);
    tile_mma<true>(sb, IT_WQA, in1, w, lane, acc);
    publish(gs->part[1][cta], w, lane, acc, tag);
    if (tid == 0) TL(7);
    bar_consumers();

    const float SC = 0.08838834764831845f * 1.4426950408889634f;
    gather(gs->part[0][h * 4], in0, tid, tag);
    if (tid == 0) TL(8);
    tile_mma<false>(sb, IT_WUK, in0, w, lane, acc);
    if (tid == 0) TL(25);
    if (lane < 16) {
        uint32_t* q = reinterpret_cast<uint32_t*>(gs->q[g]) + (2 * j + (w >> 2)) * 1024 + h * 32 + t;
        const int ch = 2 * (w & 3);
        q[((ch) ^ (h & 7)) * 4]     = pack_bf16(acc[0][0] * SC, acc[0][1] * SC);
        q[((ch + 1) ^ (h & 7)) * 4] = pack_bf16(acc[1][0] * SC, acc[1][1] * SC);
    }
    __syncwarp();
    asm volatile("bar.arrive 3, 288;" ::: "memory");
    gather(gs->part[1][h * 4], in1, tid, tag);
    if (tid == 0) TL(28);

    uint32_t qf[16];
#pragma unroll
    for (int c = 0; c < 8; c++) {
        qf[2 * c]     = lds32(in1 + j * 272 + ((c ^ g) << 4) + t * 4);
        qf[2 * c + 1] = lds32(in1 + j * 272 + 128 + ((c ^ g) << 4) + t * 4);
    }
    const uint32_t sc_w = sb + SM_SC + w * 512;
    auto k_item = [&](int item, uint32_t sc) {
        mbar_wait(sb + SM_FULL + item * 8);
        const uint32_t base = sb + slot_off(item) + ((lane & 7) + (lane & 8)) * 256 + ((lane >> 4) << 7);
        float s[4][4];
#pragma unroll
        for (int T = 0; T < 4; T++) { s[T][0] = s[T][1] = s[T][2] = s[T][3] = 0.f; }
#pragma unroll
        for (int c = 0; c < 8; c++) {
            const uint32_t a = base + ((c ^ (lane & 7)) << 4);
#pragma unroll
            for (int T = 0; T < 4; T++) {
                uint32_t r0, r1, r2, r3;
                ldsm4(a + T * 4096, r0, r1, r2, r3);
                mma16816(s[T], r0, r1, r2, r3, qf[2 * c], qf[2 * c + 1]);
            }
        }
        __syncwarp();
        if (lane == 0) mbar_arrive8(sb + SM_EMPTY + item * 8);
        if (t == (g >> 1)) {
#pragma unroll
            for (int T = 0; T < 4; T++) {
                stsf(sc + (16 * T + g) * 4,     (g & 1) ? s[T][1] : s[T][0]);
                stsf(sc + (16 * T + g + 8) * 4, (g & 1) ? s[T][3] : s[T][2]);
            }
        }
    };
    k_item(IT_K0 + w, sc_w);
    if (tid == 224) TL(10);

    {
        float s[2][2][4];
#pragma unroll
        for (int i = 0; i < 16; i++) (&s[0][0][0])[i] = 0.f;
        mbar_wait(sb + SM_FULL + IT_Q * 8);
        mbar_wait(sb + SM_FULL + (IT_Q + 1) * 8);
        if (tid == 0) TLX(96 + IT_Q);
        mbar_wait(sb + SM_FULL + (IT_C + w) * 8);
        const uint32_t cb0 = sb + slot_off(IT_C + w) + ((lane & 7) + ((lane >> 4) << 3)) * 128;
        const uint32_t cx = (((lane >> 3) & 1) ^ (lane & 7)) << 4;
        const uint32_t qr = ((lane & 7) + (lane & 8)) * 128;
        const uint32_t qx = ((lane >> 4) ^ (lane & 7)) << 4;
#pragma unroll
        for (int cb = 0; cb < 8; cb++) {
            const uint32_t qb = sb + slot_off(IT_Q + (cb >> 2)) + (cb & 3) * 4096 + qr;
#pragma unroll
            for (int k4 = 0; k4 < 4; k4++) {
                uint32_t b0, b1, b2, b3, a0, a1, a2, a3;
                ldsm4(cb0 + cb * 2048 + (cx ^ (k4 << 5)), b0, b1, b2, b3);
                ldsm4(qb + (qx ^ (k4 << 5)), a0, a1, a2, a3);
                mma16816(s[0][0], a0, a1, a2, a3, b0, b1);
                mma16816(s[0][1], a0, a1, a2, a3, b2, b3);
                ldsm4(qb + 2048 + (qx ^ (k4 << 5)), a0, a1, a2, a3);
                mma16816(s[1][0], a0, a1, a2, a3, b0, b1);
                mma16816(s[1][1], a0, a1, a2, a3, b2, b3);
            }
        }
        __syncwarp();
        if (lane == 0) { mbar_arrive(sb + SM_EMPTY + IT_Q * 8); mbar_arrive(sb + SM_EMPTY + (IT_Q + 1) * 8); }
#pragma unroll
        for (int r = 0; r < 4; r++) {
            const int mt = r >> 1, hi = (r & 1) * 2;
            float m = fmaxf(fmaxf(s[mt][0][hi], s[mt][0][hi + 1]), fmaxf(s[mt][1][hi], s[mt][1][hi + 1]));
            m = fmaxf(m, __shfl_xor_sync(0xffffffffu, m, 1));
            m = fmaxf(m, __shfl_xor_sync(0xffffffffu, m, 2));
            if (t == 0) stsf(sb + SM_MX + (8 * r + g) * 32 + w * 4, m);
        }
        bar_consumers();
        if (tid == 0) TL(11);
        uint32_t pf[2][4];
#pragma unroll
        for (int r = 0; r < 4; r++) {
            const int mt = r >> 1, hi = r & 1;
            const float4 m0 = ldsf4(sb + SM_MX + (8 * r + g) * 32), m1 = ldsf4(sb + SM_MX + (8 * r + g) * 32 + 16);
            const float m = fmaxf(fmaxf(fmaxf(m0.x, m0.y), fmaxf(m0.z, m0.w)), fmaxf(fmaxf(m1.x, m1.y), fmaxf(m1.z, m1.w)));
            const uint32_t p0 = pack_bf16(ex2(s[mt][0][2 * hi] - m), ex2(s[mt][0][2 * hi + 1] - m));
            const uint32_t p1 = pack_bf16(ex2(s[mt][1][2 * hi] - m), ex2(s[mt][1][2 * hi + 1] - m));
            pf[mt][hi] = p0; pf[mt][2 + hi] = p1;
            float l = (bf_lo(p0) + bf_hi(p0)) + (bf_lo(p1) + bf_hi(p1));
            l += __shfl_xor_sync(0xffffffffu, l, 1);
            l += __shfl_xor_sync(0xffffffffu, l, 2);
            if (t == 0) stsf(sb + SM_SUM + (8 * r + g) * 32 + w * 4, l);
        }
        sts128(sb + SM_PF + (w * 2 + 0) * 512 + lane * 16, make_uint4(pf[0][0], pf[0][1], pf[0][2], pf[0][3]));
        sts128(sb + SM_PF + (w * 2 + 1) * 512 + lane * 16, make_uint4(pf[1][0], pf[1][1], pf[1][2], pf[1][3]));
        bar_consumers();
        if (w == 0) {
            const float4 m0 = ldsf4(sb + SM_MX + lane * 32), m1 = ldsf4(sb + SM_MX + lane * 32 + 16);
            const float4 l0 = ldsf4(sb + SM_SUM + lane * 32), l1 = ldsf4(sb + SM_SUM + lane * 32 + 16);
            const float m = fmaxf(fmaxf(fmaxf(m0.x, m0.y), fmaxf(m0.z, m0.w)), fmaxf(fmaxf(m1.x, m1.y), fmaxf(m1.z, m1.w)));
            const float l = ((l0.x + l0.y) + (l0.z + l0.w)) + ((l1.x + l1.y) + (l1.z + l1.w));
            gs->stat[lane][cta] = make_float2(m, l);
        }
        float o[2][8][4];
#pragma unroll
        for (int i = 0; i < 64; i++) (&o[0][0][0])[i] = 0.f;
        const uint32_t vr = w * 2048 + ((lane & 7) + (lane & 8)) * 128;
        const uint32_t vx = ((lane >> 4) ^ (lane & 7)) << 4;
#pragma unroll
        for (int ks = 0; ks < 8; ks++) {
            const uint4 p0 = lds128(sb + SM_PF + (ks * 2 + 0) * 512 + lane * 16);
            const uint4 p1 = lds128(sb + SM_PF + (ks * 2 + 1) * 512 + lane * 16);
            const uint32_t vb = sb + slot_off(IT_C + ks) + vr;
#pragma unroll
            for (int n2 = 0; n2 < 4; n2++) {
                uint32_t b0, b1, b2, b3;
                ldsm4t(vb + (vx ^ (n2 << 5)), b0, b1, b2, b3);
                mma16816(o[0][2 * n2],     p0.x, p0.y, p0.z, p0.w, b0, b1);
                mma16816(o[0][2 * n2 + 1], p0.x, p0.y, p0.z, p0.w, b2, b3);
                mma16816(o[1][2 * n2],     p1.x, p1.y, p1.z, p1.w, b0, b1);
                mma16816(o[1][2 * n2 + 1], p1.x, p1.y, p1.z, p1.w, b2, b3);
            }
            __syncwarp();
            if (lane == 0) mbar_arrive(sb + SM_EMPTY + (IT_C + ks) * 8);
        }
        if (tid == 0) TL(12);
        mbar_wait(sb + SM_FULL + (IT_K1 + STG_AT + (w >> STG_SH)) * 8);
#pragma unroll
        for (int r = 0; r < 4; r++) {
            const int mt = r >> 1, hi = (r & 1) * 2;
            uint4* dst = gs->op[(8 * r + g) * 4 + (w >> 1)] + (cta >> 6) * 1024 + (w & 1) * 512 + (cta & 63) * 8;
#pragma unroll
            for (int u = 0; u < 2; u++) {
                uint4 v;
                v.x = pack_bf16(o[mt][4 * u][hi],     o[mt][4 * u][hi + 1]);
                v.y = pack_bf16(o[mt][4 * u + 1][hi], o[mt][4 * u + 1][hi + 1]);
                v.z = pack_bf16(o[mt][4 * u + 2][hi], o[mt][4 * u + 2][hi + 1]);
                v.w = pack_bf16(o[mt][4 * u + 3][hi], o[mt][4 * u + 3][hi + 1]);
                dst[(t + 4 * u) ^ (cta & 7)] = v;
            }
        }
        if (tid == 0) TL(29);
        asm volatile("bar.arrive 3, 288;" ::: "memory");
    }

    k_item(IT_K1 + w, sc_w + 256);
    __syncwarp();
    {
        const float4 s = ldsf4(sc_w + lane * 16);
        float m = fmaxf(fmaxf(s.x, s.y), fmaxf(s.z, s.w));
#pragma unroll
        for (int d = 1; d < 32; d <<= 1) m = fmaxf(m, __shfl_xor_sync(0xffffffffu, m, d));
        if (lane == 0) stsf(sb + SM_ML + w * 4, m);
        bar_consumers();
        const float4 m0 = ldsf4(sb + SM_ML), m1 = ldsf4(sb + SM_ML + 16);
        m = fmaxf(fmaxf(fmaxf(m0.x, m0.y), fmaxf(m0.z, m0.w)), fmaxf(fmaxf(m1.x, m1.y), fmaxf(m1.z, m1.w))) * SC;
        const uint32_t p0 = pack_bf16(ex2(fmaf(s.x, SC, -m)), ex2(fmaf(s.y, SC, -m)));
        const uint32_t p1 = pack_bf16(ex2(fmaf(s.z, SC, -m)), ex2(fmaf(s.w, SC, -m)));
        float l = (bf_lo(p0) + bf_hi(p0)) + (bf_lo(p1) + bf_hi(p1));
#pragma unroll
        for (int d = 1; d < 32; d <<= 1) l += __shfl_xor_sync(0xffffffffu, l, d);
        if (lane == 0) stsf(sb + SM_ML + 32 + w * 4, l);
        sts64(sb + SM_PA + w * 256 + lane * 8, p0, p1);
        __syncwarp();
    }
    if (tid == 224) TL(14);

    float oa[4][4];
#pragma unroll
    for (int i = 0; i < 16; i++) (&oa[0][0])[i] = 0.f;
    auto v_item = [&](int item, uint32_t pa) {
        uint32_t p[8];
#pragma unroll
        for (int i = 0; i < 8; i++) p[i] = lds32(pa + i * 16 + t * 4);
        mbar_wait(sb + SM_FULL + item * 8);
        const uint32_t base = sb + slot_off(item) + ((lane & 7) + ((lane >> 4) << 3)) * 256 + ((lane & 8) << 4);
#pragma unroll
        for (int c = 0; c < 8; c++) {
            const uint32_t a = base + ((c ^ (lane & 7)) << 4);
            const uint32_t mask = ((c == (g ^ (2 * t))) ? 0x0000ffffu : 0u) | ((c == (g ^ (2 * t + 1))) ? 0xffff0000u : 0u);
#pragma unroll
            for (int T = 0; T < 4; T++) {
                uint32_t r0, r1, r2, r3;
                ldsm4t(a + T * 4096, r0, r1, r2, r3);
                mma16816(oa[T], r0, r1, r2, r3, p[2 * T] & mask, p[2 * T + 1] & mask);
            }
        }
        __syncwarp();
        if (lane == 0) mbar_arrive8(sb + SM_EMPTY + item * 8);
    };
    v_item(IT_V0 + w, sb + SM_PA + w * 256);
    if (tid == 224) TL(15);

    mbar_wait(sb + SM_FULL + IT_OP * 8);
    if (tid == 0) TLX(96 + IT_OP);
    if (w < 4) {
        const float2 st = ldsf2(sb + SM_MX + tid * 8);
        float m = st.x;
#pragma unroll
        for (int d = 1; d < 32; d <<= 1) m = fmaxf(m, __shfl_xor_sync(0xffffffffu, m, d));
        const uint32_t wb = pack_bf16(ex2(st.x - m), 0.f);
        float l = bf_lo(wb) * st.y;
#pragma unroll
        for (int d = 1; d < 32; d <<= 1) l += __shfl_xor_sync(0xffffffffu, l, d);
#pragma unroll
        for (int bb = 0; bb < 4; bb++) sts16(in0 + bb * 272 + tid * 2, bb == w ? (uint16_t)wb : (uint16_t)0);
        if (lane == 0) stsf(sb + SM_ML + 64 + w * 4, 1.f / l);
    }
    bar_consumers();
    tile_mma<true>(sb, IT_OP, in0, w, lane, acc);
    if (lane < 16) {
        const float inv = ldsf(sb + SM_ML + 64 + g * 4);
        const uint32_t v0 = pack_bf16(acc[0][0] * inv, acc[0][1] * inv), v1 = pack_bf16(acc[1][0] * inv, acc[1][1] * inv);
        st_rlx2(lat_dst, (t & 1) ? v1 : v0, (t & 1) ? v0 : v1);
    }
    if (tid == 0) TL(19);

    {
        const float4 l0 = ldsf4(sb + SM_ML + 32), l1 = ldsf4(sb + SM_ML + 48);
        const float inv = 1.f / (((l0.x + l0.y) + (l0.z + l0.w)) + ((l1.x + l1.y) + (l1.z + l1.w)));
        v_item(IT_V1 + w, sb + SM_PA + w * 256 + 128);
        const uint32_t so = sb + SM_PF + w * 512 + (16 * t + g) * 4;
        stsf(so,       (oa[0][0] + oa[1][0]) + (oa[2][0] + oa[3][0]));
        stsf(so + 32,  (oa[0][1] + oa[1][1]) + (oa[2][1] + oa[3][1]));
        stsf(so + 256, (oa[0][2] + oa[1][2]) + (oa[2][2] + oa[3][2]));
        stsf(so + 288, (oa[0][3] + oa[1][3]) + (oa[2][3] + oa[3][3]));
        bar_consumers();
        if (tid == 128) {
            const uint32_t peer = map_cta(sb, (j & 1) ^ 1);
            st_async32(peer + SM_RCV + 128, 0u, peer + SM_FULL + BAR_PEER * 8);
        }
        if (tid < 64) {
            float x = 0.f, y = 0.f;
#pragma unroll
            for (int i = 0; i < 8; i++) {
                const float2 v = ldsf2(sb + SM_PF + i * 512 + tid * 8);
                x += v.x; y += v.y;
            }
            st_rlx(o_dst, pack_bf16(x * inv, y * inv));
        }
    }
    if (tid == 0) TL(17);

    {
        const int item = IT_WUV + 1 - (w >> 2);
        const uint32_t lo = (g & 3) * 1024 + (item & 1) * 512 + (g & 1) * 64 + t * 16;
        const int wd = ((lane >> 2 & 2) + (lane >> 4)) ^ (lane >> 1 & 3);
        const uint32_t base = sb + (w < 4 ? slot_off(IT_WUV + 1) : slot_off(IT_WUV)) + ((lane & 6) * 4 + wd * 2 + (lane & 1)) * 64 + (((w ^ wd) & 3) << 4);
        mbar_wait(sb + SM_FULL + BAR_LAT * 8);
        uint4 a[8];
#pragma unroll
        for (int i = 0; i < 8; i++) a[i] = lds128_if(sb + SM_LAT + (lo ^ (i * 64)), lane < 16);
        int it = 0;
        while (refetch<8>(a, lane, [&](int i) { return (const char*)gs->lat[h] + (lo ^ (i * 64)); }))
            if (++it > SPIN_LIMIT) __trap();
        float c[4][4];
#pragma unroll
        for (int i = 0; i < 16; i++) (&c[0][0])[i] = 0.f;
        mbar_wait(sb + SM_FULL + item * 8);
#pragma unroll
        for (int kk = 0; kk < 8; kk++) {
            uint32_t r0, r1, r2, r3;
            ldsm4t(base + kk * 2048, r0, r1, r2, r3);
            mma16816(c[2 * (kk & 1)],     a[kk].x, a[kk].y, a[kk].z, a[kk].w, r0, r1);
            mma16816(c[2 * (kk & 1) + 1], a[kk].x, a[kk].y, a[kk].z, a[kk].w, r2, r3);
        }
        const float v0 = (c[0][0] + c[1][2]) + (c[2][0] + c[3][2]), v1 = (c[0][1] + c[1][3]) + (c[2][1] + c[3][3]);
        const uint32_t px = in1 + (w & 3) * 256 + lane * 8;
        if (w >= 4) {
            sts64(px, __float_as_uint(v0), __float_as_uint(v1));
            asm volatile("bar.arrive 6, 256;" ::: "memory");
        } else {
            asm volatile("bar.sync 6, 256;" ::: "memory");
            const float2 p = ldsf2(px);
            if (lane < 16) st_rlx(ctx_dst, pack_bf16(v0 + p.x, v1 + p.y));
        }
    }
    if (tid == 0) TL(16);

    {
        const bool isB = slice >= 32;
        const int r = j & 1;
        const uint32_t xl = isB ? t * 64 + (((g ^ (t & 2)) & 3) << 4) : (g & 3) * 256 + ((g & 1) * 4 + t) * 16;
        const uint32_t cs = isB ? 256 : 64;
        const uint32_t xo = r * 8192 + (w >> 1) * 1024 + (w & 1) * 2 * cs + xl, xz = (1 - r) * 12288 + w * 1024 + (g >> 2) * 2 * cs + xl;
        auto xoff = [&](int i) { return i < 6 ? (i >> 1) * 4096 + (xo ^ ((i & 1) * cs)) : xz ^ ((i & 1) * cs); };
        const char* src = (const char*)gs->x[slice >> 5][r * 12];
        uint32_t off[2], ofz[2];
#pragma unroll
        for (int u = 0; u < 2; u++) {
            const int tt = (lane & 7) >> 1;
            const int row = 8 * tt + 2 * ((2 * u + (lane >> 4) + tt) & 3) + (lane & 1);
            off[u] = sb + w * 2048 + row * 32 + ((((lane >> 3) ^ (row >> 2)) & 1) << 4);
            ofz[u] = __shfl_sync(0xffffffffu, sb + (w < 4 ? slot_off(IT_WO + 3) : slot_off(IT_W2)) + (w & 3) * 4096 + (lane & 8) * 256 +
                                              row * 32 + (((r ^ (row >> 2)) & 1) << 4), lane);
        }
        const uint32_t fin = __shfl_sync(0xffffffffu, sb + SM_FIN + (t & 1) * 768 + g * 48 + ((w ^ (t & 1)) << 2), lane);
        const uint32_t fi2 = __shfl_sync(0xffffffffu, sb + SM_FIN + 3072 + (t & 1) * 1280 + g * 80 + (((w * 2 + (t >> 1)) ^ (t * 2 & 2)) << 2), lane);
        uint32_t a[2][4][4];
        uint4 x[8];
        float c[4][4];
        auto load_w = [&](int i) {
            mbar_wait(sb + SM_FULL + (i < 3 ? IT_WO + i : w < 4 ? IT_WO + 3 : IT_W2) * 8);
#pragma unroll
            for (int q = 0; q < 4; q++)
                ldsm4t((i < 3 ? slot_off(IT_WO + i) + off[q & 1] : ofz[q & 1]) + (q >> 1) * 1024,
                       a[i & 1][q][0], a[i & 1][q][1], a[i & 1][q][2], a[i & 1][q][3]);
        };
        auto mma_w = [&](int i) {
#pragma unroll
            for (int q = 0; q < 4; q++) {
                if (i == 0 || i == 3) c[q][0] = c[q][1] = c[q][2] = c[q][3] = 0.f;
                mma16816(c[q], a[i & 1][q][0], a[i & 1][q][1], a[i & 1][q][2], a[i & 1][q][3],
                         (q & 1) ? x[2 * i + (q >> 1)].z : x[2 * i + (q >> 1)].x, (q & 1) ? x[2 * i + (q >> 1)].w : x[2 * i + (q >> 1)].y);
            }
        };
        load_w(0); load_w(1);
        mbar_wait(sb + SM_FULL + BAR_X * 8);
        if (tid == 224) TLX(20);
#pragma unroll
        for (int i = 0; i < 8; i++) x[i] = lds128_if(sb + slot_off(IT_X) + xoff(i), i >= 6 || lane < 16);
        int it = 0;
        while (true) {
            mma_w(0); mma_w(1);
            if (!refetch<6>(x, lane, [&](int i) { return src + xoff(i); })) break;
            if (++it > SPIN_LIMIT) __trap();
        }
        load_w(2);
        mma_w(2);
#pragma unroll
        for (int e = 0; e < 4; e++) stsf_if(fin + (e >> 1) * 1536 + (e & 1) * 384, (c[0][e] + c[1][e]) + (c[2][e] + c[3][e]), t < 2);
        asm volatile("bar.arrive 5, 320;" ::: "memory");
        if (tid == 0) TLX(18);
        load_w(3);
        mma_w(3);
#pragma unroll
        for (int e = 0; e < 2; e++) {
            const float lo = (c[0][e] + c[1][e]) + (c[2][e] + c[3][e]), hi = (c[0][e + 2] + c[1][e + 2]) + (c[2][e + 2] + c[3][e + 2]);
            stsf(fi2 + e * 640, t < 2 ? lo : hi);
        }
        asm volatile("bar.arrive 7, 288;" ::: "memory");
        if (tid == 224) TLX(26);
    }
}

typedef CUresult (*EncodeTiledFn)(CUtensorMap*, CUtensorMapDataType, cuuint32_t, void*, const cuuint64_t*,
                                  const cuuint64_t*, const cuuint32_t*, const cuuint32_t*, CUtensorMapInterleave,
                                  CUtensorMapSwizzle, CUtensorMapL2promotion, CUtensorMapFloatOOBfill);

void encode_map(EncodeTiledFn enc, CUtensorMap* tm, const void* p, cuuint64_t cols, cuuint64_t rows,
                cuuint32_t brows, cuuint32_t bblk) {
    cuuint64_t dims[3] = {64, rows, cols / 64};
    cuuint64_t strides[2] = {cols * 2, 128};
    cuuint32_t box[3] = {64, brows, bblk};
    cuuint32_t es[3] = {1, 1, 1};
    enc(tm, CU_TENSOR_MAP_DATA_TYPE_BFLOAT16, 3, const_cast<void*>(p), dims, strides, box, es,
        CU_TENSOR_MAP_INTERLEAVE_NONE, CU_TENSOR_MAP_SWIZZLE_128B, CU_TENSOR_MAP_L2_PROMOTION_L2_256B,
        CU_TENSOR_MAP_FLOAT_OOB_FILL_NONE);
}

void encode_slice_map(EncodeTiledFn enc, CUtensorMap* tm, const void* p, cuuint64_t cols, cuuint64_t rows, cuuint32_t bcols) {
    cuuint64_t dims[3] = {cols, 256, rows / 256};
    cuuint64_t strides[2] = {cols * 2, cols * 512};
    cuuint32_t box[3] = {bcols, 256, 32 / bcols};
    cuuint32_t es[3] = {1, 1, 1};
    enc(tm, CU_TENSOR_MAP_DATA_TYPE_BFLOAT16, 3, const_cast<void*>(p), dims, strides, box, es, CU_TENSOR_MAP_INTERLEAVE_NONE,
        bcols == 16 ? CU_TENSOR_MAP_SWIZZLE_32B : CU_TENSOR_MAP_SWIZZLE_64B, CU_TENSOR_MAP_L2_PROMOTION_L2_128B,
        CU_TENSOR_MAP_FLOAT_OOB_FILL_NONE);
}

}

extern "C" void kernel_launch(void* const* d_in, const int* in_sizes, int n_in, void* d_out, int out_size) {
    (void)in_sizes; (void)n_in; (void)out_size;
    static EncodeTiledFn enc = nullptr;
    static Scratch* gs = nullptr;
    if (!enc) {
        cudaGetSymbolAddress((void**)&gs, g_scratch);
        void* fn = nullptr;
        cudaDriverEntryPointQueryResult qr;
        cudaGetDriverEntryPoint("cuTensorMapEncodeTiled", &fn, cudaEnableDefault, &qr);
        enc = (EncodeTiledFn)fn;
        cudaFuncSetAttribute(fused_decode_kernel, cudaFuncAttributeMaxDynamicSharedMemorySize, SM_END);
    }
    Maps maps;
    encode_map(enc, &maps.wqB, d_in[7], 4096, 512, 64, 2);
    encode_map(enc, &maps.wqA, d_in[3], 4096, 512, 64, 2);
    encode_map(enc, &maps.wuk, d_in[8], 4096, 512, 64, 2);
    encode_slice_map(enc, &maps.wuv, d_in[9], 4096, 512, 32);
    encode_slice_map(enc, &maps.woB, d_in[10], 512, 4096, 16);
    encode_slice_map(enc, &maps.woA, d_in[4], 512, 4096, 16);
    encode_map(enc, &maps.ckv, d_in[6], 512, 16384, 16, 8);
    fused_decode_kernel<<<NCTA, NTHR, SM_END>>>((const __nv_bfloat16*)d_in[0], (const __nv_bfloat16*)d_in[5],
                                                (const __nv_bfloat16*)d_in[1], (const __nv_bfloat16*)d_in[2],
                                                (__nv_bfloat16*)d_out, gs, maps);
}
```

```cpp
#include <cuda_runtime.h>
#include <cuda_bf16.h>
#include <cuda.h>
#include <stdint.h>

namespace {

constexpr int NCTA   = 128;
constexpr int NSLOT  = 13;
constexpr int SLOT   = 16384;
constexpr int NITEM  = 56;
#define INFLIGHT 4
#define PACE 650
#define OFFS 500
#define STAG 0
#define OWAIT 0
#define FINMODE 1
#define FINDELAY 0
#define NFIRST 2
#define STARTER 256
#define CTXWAIT 0
#define LATAT 46
#define TAPER 250
#define TAPER_AT 49
#define TAPER_N 1
#define STG_AT 2
#define STG_SH 1
#define OPN 8
#define OPGAP 200
#define QN 2
#define QGAP 0
#define PFSTARTER 288
#define GLEAD 150
#define AEARLY 0
#define BEARLY 0
#define DRAIN_AT 99
#define DRAIN 2
#define AWAIT 0
#define NPOLL 4
#define FGAP 170
#define FDEL 0
constexpr int NTHR   = 320;
#define BAR2 "bar.sync 2, 320;"

constexpr int IT_WQB = 0, IT_WQA = 2, IT_WUK = 4, IT_K0 = 6, IT_Q = 14, IT_C = 16, IT_K1 = 24, IT_V0 = 32,
              IT_OP = 40, IT_V1 = 42, IT_WUV = 50, IT_WO = 52;
constexpr int IT_X = 56;
constexpr int IT_W2 = 58;
constexpr int BAR_LAT = 56, BAR_FIN = 57, BAR_X = 59, BAR_PEER = 60;

constexpr int SM_FULL  = NSLOT * SLOT;
constexpr int SM_EMPTY = SM_FULL + 512;
constexpr int SM_IN0   = SM_EMPTY + 512;
constexpr int SM_IN1   = SM_IN0 + 1088;
constexpr int SM_SC    = SM_IN1 + 1088;
constexpr int SM_PA    = SM_SC + 4096;
constexpr int SM_PF    = SM_PA + 2048;
constexpr int SM_MX    = SM_PF + 8192;
constexpr int SM_ML    = SM_MX + 1024;
constexpr int SM_RCV   = SM_ML + 128;
constexpr int SM_END   = SM_RCV + 144;
constexpr int SM_LAT   = SM_PF + 4096;
constexpr int SM_FIN   = SM_SC;
constexpr int SM_SUM   = SM_IN0;
static_assert(SM_END <= 232448, "smem");

struct Maps { CUtensorMap wqB, wqA, wuk, wuv, woA, woB, ckv; };

struct Scratch {
    unsigned cnt[32];
    float    part[2][NCTA][512];
    uint32_t x[2][32][256];
    uint32_t lat[32][4][256];
    uint4    q[4][2048];
    uint4    op[NCTA][2048];
    float2   stat[32][128];
};
__device__ __align__(128) Scratch g_scratch;
#define TLX(i) do {} while (0)
#define TL(i) do {} while (0)

constexpr int SPIN_LIMIT = 1 << 22;

__device__ __forceinline__ uint32_t smem_u32(const void* p) { return (uint32_t)__cvta_generic_to_shared(p); }
__device__ __forceinline__ void mbar_init(uint32_t bar, uint32_t cnt) {
    asm volatile("mbarrier.init.shared::cta.b64 [%0], %1;" ::"r"(bar), "r"(cnt) : "memory");
}
__device__ __forceinline__ void mbar_expect_tx(uint32_t bar, uint32_t bytes) {
    asm volatile("mbarrier.arrive.expect_tx.shared::cta.b64 _, [%0], %1;" ::"r"(bar), "r"(bytes) : "memory");
}
__device__ __forceinline__ void mbar_arrive(uint32_t bar) {
    asm volatile("mbarrier.arrive.shared::cta.b64 _, [%0];" ::"r"(bar) : "memory");
}
__device__ __forceinline__ void mbar_arrive8(uint32_t bar) {
    asm volatile("mbarrier.arrive.shared::cta.b64 _, [%0], 8;" ::"r"(bar) : "memory");
}
__device__ __forceinline__ void mbar_wait(uint32_t bar) {
    uint32_t done;
    int it = 0;
    do {
        asm volatile("{\n.reg .pred p;\nmbarrier.try_wait.parity.shared::cta.b64 p, [%1], 0;\nselp.u32 %0, 1, 0, p;\n}"
                     : "=r"(done) : "r"(bar) : "memory");
        if (++it > SPIN_LIMIT) __trap();
    } while (!done);
}
__device__ __forceinline__ uint32_t map_cta(uint32_t a, uint32_t rank) {
    uint32_t r; asm("mapa.shared::cluster.u32 %0, %1, %2;" : "=r"(r) : "r"(a), "r"(rank)); return r;
}
__device__ __forceinline__ void st_async32(uint32_t a, uint32_t v, uint32_t bar) {
    asm volatile("st.async.shared::cluster.mbarrier::complete_tx::bytes.b32 [%0], %1, [%2];" ::"r"(a), "r"(v), "r"(bar) : "memory");
}
__device__ __forceinline__ void bulk_load(uint32_t dst, const void* src, uint32_t bytes, uint32_t bar, uint64_t pol) {
    asm volatile("cp.async.bulk.shared::cluster.global.mbarrier::complete_tx::bytes.L2::cache_hint [%0], [%1], %2, [%3], %4;"
                 ::"r"(dst), "l"(src), "r"(bytes), "r"(bar), "l"(pol) : "memory");
}
__device__ __forceinline__ void bulk_load_nohint(uint32_t dst, const void* src, uint32_t bytes, uint32_t bar) {
    asm volatile("cp.async.bulk.shared::cluster.global.mbarrier::complete_tx::bytes [%0], [%1], %2, [%3];"
                 ::"r"(dst), "l"(src), "r"(bytes), "r"(bar) : "memory");
}
__device__ __forceinline__ void bulk_load_pair(uint32_t dst, const void* src, uint32_t bytes, uint32_t bar) {
    asm volatile("cp.async.bulk.shared::cluster.global.mbarrier::complete_tx::bytes.multicast::cluster [%0], [%1], %2, [%3], %4;"
                 ::"r"(dst), "l"(src), "r"(bytes), "r"(bar), "h"((uint16_t)3) : "memory");
}
__device__ __forceinline__ void tma3d(uint32_t dst, const CUtensorMap* tm, int c0, int c1, int c2, uint32_t bar, uint64_t pol) {
    asm volatile("cp.async.bulk.tensor.3d.shared::cluster.global.mbarrier::complete_tx::bytes.L2::cache_hint [%0], [%1, {%3, %4, %5}], [%2], %6;"
                 ::"r"(dst), "l"(tm), "r"(bar), "r"(c0), "r"(c1), "r"(c2), "l"(pol) : "memory");
}
__device__ __forceinline__ void tma3d_pair(uint32_t dst, const CUtensorMap* tm, int c0, int c1, int c2, uint32_t bar, uint64_t pol) {
    asm volatile("cp.async.bulk.tensor.3d.shared::cluster.global.mbarrier::complete_tx::bytes.multicast::cluster.L2::cache_hint [%0], [%1, {%3, %4, %5}], [%2], %7, %6;"
                 ::"r"(dst), "l"(tm), "r"(bar), "r"(c0), "r"(c1), "r"(c2), "l"(pol), "h"((uint16_t)3) : "memory");
}
__device__ __forceinline__ void ldsm4(uint32_t a, uint32_t& r0, uint32_t& r1, uint32_t& r2, uint32_t& r3) {
    asm volatile("ldmatrix.sync.aligned.m8n8.x4.shared.b16 {%0,%1,%2,%3}, [%4];"
                 : "=r"(r0), "=r"(r1), "=r"(r2), "=r"(r3) : "r"(a) : "memory");
}
__device__ __forceinline__ void ldsm4t(uint32_t a, uint32_t& r0, uint32_t& r1, uint32_t& r2, uint32_t& r3) {
    asm volatile("ldmatrix.sync.aligned.m8n8.x4.trans.shared.b16 {%0,%1,%2,%3}, [%4];"
                 : "=r"(r0), "=r"(r1), "=r"(r2), "=r"(r3) : "r"(a) : "memory");
}
__device__ __forceinline__ void mma16816(float (&c)[4], uint32_t a0, uint32_t a1, uint32_t a2, uint32_t a3,
                                         uint32_t b0, uint32_t b1) {
    asm volatile("mma.sync.aligned.m16n8k16.row.col.f32.bf16.bf16.f32 {%0,%1,%2,%3}, {%4,%5,%6,%7}, {%8,%9}, {%0,%1,%2,%3};"
                 : "+f"(c[0]), "+f"(c[1]), "+f"(c[2]), "+f"(c[3])
                 : "r"(a0), "r"(a1), "r"(a2), "r"(a3), "r"(b0), "r"(b1));
}
__device__ __forceinline__ uint32_t lds32(uint32_t a) {
    uint32_t v; asm volatile("ld.shared.b32 %0, [%1];" : "=r"(v) : "r"(a) : "memory"); return v;
}
__device__ __forceinline__ float ldsf(uint32_t a) {
    float v; asm volatile("ld.shared.f32 %0, [%1];" : "=f"(v) : "r"(a) : "memory"); return v;
}
__device__ __forceinline__ float2 ldsf2(uint32_t a) {
    float2 v; asm volatile("ld.shared.v2.f32 {%0,%1}, [%2];" : "=f"(v.x), "=f"(v.y) : "r"(a) : "memory"); return v;
}
__device__ __forceinline__ float4 ldsf4(uint32_t a) {
    float4 v; asm volatile("ld.shared.v4.f32 {%0,%1,%2,%3}, [%4];" : "=f"(v.x), "=f"(v.y), "=f"(v.z), "=f"(v.w) : "r"(a) : "memory"); return v;
}
__device__ __forceinline__ uint4 lds128(uint32_t a) {
    uint4 v; asm volatile("ld.shared.v4.b32 {%0,%1,%2,%3}, [%4];" : "=r"(v.x), "=r"(v.y), "=r"(v.z), "=r"(v.w) : "r"(a) : "memory"); return v;
}
__device__ __forceinline__ uint4 lds128_if(uint32_t a, bool on) {
    uint4 v;
    asm volatile("{\n.reg .pred p;\nsetp.ne.u32 p, %5, 0;\n@p ld.shared.v4.b32 {%0,%1,%2,%3}, [%4];\n}"
                 : "=r"(v.x), "=r"(v.y), "=r"(v.z), "=r"(v.w) : "r"(a), "r"((uint32_t)on) : "memory");
    return v;
}
__device__ __forceinline__ void stsf_if(uint32_t a, float v, bool on) {
    asm volatile("{\n.reg .pred p;\nsetp.ne.u32 p, %2, 0;\n@p st.shared.f32 [%0], %1;\n}" ::"r"(a), "f"(v), "r"((uint32_t)on) : "memory");
}
__device__ __forceinline__ void sts16(uint32_t a, uint16_t v) { asm volatile("st.shared.b16 [%0], %1;" ::"r"(a), "h"(v) : "memory"); }
__device__ __forceinline__ void sts32(uint32_t a, uint32_t v) { asm volatile("st.shared.b32 [%0], %1;" ::"r"(a), "r"(v) : "memory"); }
__device__ __forceinline__ void stsf(uint32_t a, float v) { asm volatile("st.shared.f32 [%0], %1;" ::"r"(a), "f"(v) : "memory"); }
__device__ __forceinline__ void sts64(uint32_t a, uint32_t x, uint32_t y) {
    asm volatile("st.shared.v2.b32 [%0], {%1,%2};" ::"r"(a), "r"(x), "r"(y) : "memory");
}
__device__ __forceinline__ void sts128(uint32_t a, uint4 v) {
    asm volatile("st.shared.v4.b32 [%0], {%1,%2,%3,%4};" ::"r"(a), "r"(v.x), "r"(v.y), "r"(v.z), "r"(v.w) : "memory");
}
__device__ __forceinline__ uint32_t pack_bf16(float lo, float hi) {
    uint32_t r; asm("cvt.rn.bf16x2.f32 %0, %1, %2;" : "=r"(r) : "f"(hi), "f"(lo)); return r;
}
__device__ __forceinline__ float bf_lo(uint32_t v) { return __uint_as_float(v << 16); }
__device__ __forceinline__ float bf_hi(uint32_t v) { return __uint_as_float(v & 0xffff0000u); }
__device__ __forceinline__ float ex2(float x) { float y; asm("ex2.approx.ftz.f32 %0, %1;" : "=f"(y) : "f"(x)); return y; }
__device__ __forceinline__ uint32_t timer_ns() { uint32_t t; asm volatile("mov.u32 %0, %%globaltimer_lo;" : "=r"(t)); return t; }
__device__ __forceinline__ void bar_consumers() { asm volatile("bar.sync 1, 256;" ::: "memory"); }

__device__ __forceinline__ uint32_t tagf(float v, uint32_t tag) { return (__float_as_uint(v) & 0xffffff00u) | tag; }
__device__ __forceinline__ uint2 ld_rlx2(const float* p) {
    uint2 v; asm volatile("ld.relaxed.gpu.global.v2.b32 {%0,%1}, [%2];" : "=r"(v.x), "=r"(v.y) : "l"(p) : "memory"); return v;
}
__device__ __forceinline__ float untag(uint32_t v) { return __uint_as_float(v & 0xffffff00u); }

__device__ __forceinline__ uint32_t slot_off(int item) { return (uint32_t)(item % NSLOT) * SLOT; }

template <bool TRANS, bool RELEASE = true>
__device__ __forceinline__ void tile_mma(uint32_t sb, int item, uint32_t in, int w, int lane, float (&acc)[2][2]) {
    const int g = lane >> 2, t = lane & 3;
    float c[4][4];
#pragma unroll
    for (int i = 0; i < 16; i++) (&c[0][0])[i] = 0.f;
    uint32_t a[16];
    const uint32_t ia = in + (g & 3) * 272 + t * 4;
#pragma unroll
    for (int i = 0; i < 16; i++) a[i] = lds32(ia + i * 16);
    const uint32_t s0 = sb + slot_off(item), s1 = sb + slot_off(item + 1);
    if (TRANS) {
        const int r = (lane & 7) + (lane & 8);
        const int ch = 2 * (w & 3) + (lane >> 4);
        const uint32_t off = (w >> 2) * 8192 + r * 128 + ((ch ^ (lane & 7)) << 4);
#pragma unroll
        for (int kk = 0; kk < 8; kk++) {
            if ((kk & 3) == 0) mbar_wait(sb + SM_FULL + (item + (kk >> 2)) * 8);
            uint32_t r0, r1, r2, r3;
            ldsm4t(((kk >> 2) ? s1 : s0) + off + (kk & 3) * 2048, r0, r1, r2, r3);
            mma16816(c[2 * (kk & 1)],     a[2 * kk], 0u, a[2 * kk + 1], 0u, r0, r1);
            mma16816(c[2 * (kk & 1) + 1], a[2 * kk], 0u, a[2 * kk + 1], 0u, r2, r3);
        }
    } else {
        mbar_wait(sb + SM_FULL + (item + (w >> 2)) * 8);
        const int r = 16 * (w & 3) + (lane & 7) + ((lane >> 4) << 3);
        const uint32_t base = ((w >> 2) ? s1 : s0) + r * 128 + ((((lane >> 3) & 1) ^ (lane & 7)) << 4);
#pragma unroll
        for (int kk = 0; kk < 8; kk++) {
            uint32_t r0, r1, r2, r3;
            ldsm4((base ^ ((kk & 3) << 5)) + (kk >> 2) * 8192, r0, r1, r2, r3);
            mma16816(c[2 * (kk & 1)],     a[2 * kk], 0u, a[2 * kk + 1], 0u, r0, r1);
            mma16816(c[2 * (kk & 1) + 1], a[2 * kk], 0u, a[2 * kk + 1], 0u, r2, r3);
        }
    }
    if (RELEASE) {
        __syncwarp();
        if (lane == 0) {
            mbar_arrive(sb + SM_EMPTY + item * 8);
            mbar_arrive(sb + SM_EMPTY + (item + 1) * 8);
        }
    }
    acc[0][0] = c[0][0] + c[2][0]; acc[0][1] = c[0][1] + c[2][1];
    acc[1][0] = c[1][0] + c[3][0]; acc[1][1] = c[1][1] + c[3][1];
}

__device__ __forceinline__ void publish(float* dst, int w, int lane, const float (&acc)[2][2], uint32_t tag) {
    if (lane < 16)
        asm volatile("st.relaxed.gpu.global.v4.b32 [%0], {%1,%2,%3,%4};" ::"l"(dst + w * 64 + lane * 4),
                     "r"(tagf(acc[0][0], tag)), "r"(tagf(acc[0][1], tag)), "r"(tagf(acc[1][0], tag)), "r"(tagf(acc[1][1], tag)) : "memory");
}

__device__ __forceinline__ void gather(const float* part, uint32_t in, int tid, uint32_t tag) {
    const float* p = part + tid * 2;
    uint2 v0, v1, v2, v3;
    int it = 0;
    while (true) {
        v0 = ld_rlx2(p); v1 = ld_rlx2(p + 512); v2 = ld_rlx2(p + 1024); v3 = ld_rlx2(p + 1536);
        uint32_t bad = ((v0.x ^ tag) | (v0.y ^ tag) | (v1.x ^ tag) | (v1.y ^ tag) |
                        (v2.x ^ tag) | (v2.y ^ tag) | (v3.x ^ tag) | (v3.y ^ tag)) & 0xffu;
        if (__all_sync(0xffffffffu, bad == 0)) break;
        if (++it > SPIN_LIMIT) __trap();
    }
    float x = (untag(v0.x) + untag(v1.x)) + (untag(v2.x) + untag(v3.x));
    float y = (untag(v0.y) + untag(v1.y)) + (untag(v2.y) + untag(v3.y));
    sts32(in + ((tid >> 3) & 3) * 272 + (tid >> 5) * 32 + (tid & 1) * 16 + (tid & 6) * 2, pack_bf16(x, y));
    bar_consumers();
}

constexpr uint32_t EMPTY = 0xffffffffu;
__device__ __forceinline__ void st_rlx(uint32_t* p, uint32_t v) {
    asm volatile("st.relaxed.gpu.global.b32 [%0], %1;" ::"l"(p), "r"(v) : "memory");
}
__device__ __forceinline__ void st_rlx2(uint32_t* p, uint32_t v0, uint32_t v1) {
    asm volatile("st.relaxed.gpu.global.v2.b32 [%0], {%1,%2};" ::"l"(p), "r"(v0), "r"(v1) : "memory");
}
__device__ __forceinline__ void ld_rlx4_if(uint4& v, const void* p, bool need) {
    asm volatile("{\n.reg .pred p;\nsetp.ne.u32 p, %5, 0;\n@p ld.relaxed.gpu.global.v4.b32 {%0,%1,%2,%3}, [%4];\n}"
                 : "+r"(v.x), "+r"(v.y), "+r"(v.z), "+r"(v.w) : "l"(p), "r"((uint32_t)need) : "memory");
}

template <int HALF, class F>
__device__ __forceinline__ bool refetch(uint4 (&x)[8], int lane, F addr) {
    uint32_t m[8], m0 = 0, m1 = 0;
#pragma unroll
    for (int i = 0; i < 8; i++) {
        m[i] = max(max(x[i].x, x[i].y), max(x[i].z, x[i].w));
        if (i < HALF) m0 = max(m0, m[i]); else m1 = max(m1, m[i]);
    }
    if (!__any_sync(0xffffffffu, (m0 == EMPTY && lane < 16) || m1 == EMPTY)) return false;
#pragma unroll
    for (int i = 0; i < 8; i++) ld_rlx4_if(x[i], addr(i), m[i] == EMPTY && (i >= HALF || lane < 16));
    return true;
}

__device__ __forceinline__ unsigned read_counter(const unsigned* cnt) {
    unsigned v;
    asm volatile("ld.relaxed.gpu.global.u32 %0, [%1];" : "=r"(v) : "l"(cnt) : "memory");
    return v;
}
__device__ __forceinline__ unsigned epoch_of(unsigned cnt) {
    asm volatile("" : "+r"(cnt) :: "memory");
    return cnt / NCTA + 1;
}
__device__ __forceinline__ uint32_t epoch_tag(unsigned epoch) { return (epoch & 0x7fu) | 0x80u; }

__device__ __forceinline__ void signal_and_wait(unsigned* cnt, unsigned target, int lane, uint32_t sb) {
    if (lane == 0) asm volatile("red.release.gpu.global.add.u32 [%0], 1;" ::"l"(cnt) : "memory");
    if (lane == 0) TL(30 + (((size_t)cnt >> 2) & 1));
    int it = 0;
    while (true) {
        unsigned v;
        asm volatile("ld.acquire.gpu.global.u32 %0, [%1];" : "=r"(v) : "l"(cnt) : "memory");
        if (__all_sync(0xffffffffu, (int)(v - target) >= 0)) break;
        if (++it > SPIN_LIMIT) __trap();
    }
    asm volatile("fence.proxy.async.global;" ::: "memory");
}

__global__ void __cluster_dims__(2, 1, 1) __launch_bounds__(NTHR, 1)
fused_decode_kernel(const __nv_bfloat16* __restrict__ xA, const __nv_bfloat16* __restrict__ xB,
                    const __nv_bfloat16* __restrict__ Kc, const __nv_bfloat16* __restrict__ Vc,
                    __nv_bfloat16* __restrict__ out, Scratch* gs, const __grid_constant__ Maps maps) {
    extern __shared__ __align__(1024) unsigned char smem_raw[];
    const uint32_t sb = smem_u32(smem_raw);
    const int tid = threadIdx.x, lane = tid & 31;
    const int cta = blockIdx.x, h = cta >> 2, j = cta & 3;
    const size_t kv_off = ((size_t)(j * 32 + h) * 4096 + 3072) * 128;
    if (tid == PFSTARTER) {
        asm volatile("cp.async.bulk.prefetch.L2.global [%0], %1;" ::"l"(Kc + kv_off), "r"(SLOT) : "memory");
        TLX(0);
    }
    uint64_t pol;
    asm volatile("createpolicy.fractional.L2::evict_first.b64 %0, 1.0;" : "=l"(pol));
    if (tid == STARTER) {
#pragma unroll
        for (int i = 0; i < NFIRST; i++) mbar_init(sb + SM_FULL + i * 8, 1);
        asm volatile("fence.mbarrier_init.release.cluster;" ::: "memory");
#pragma unroll
        for (int i = 0; i < NFIRST; i++) {
            TLX(32 + i);
            mbar_expect_tx(sb + SM_FULL + i * 8, SLOT);
            tma3d(sb + i * SLOT, &maps.wqB, 0, j * 128 + i * 64, h * 2, sb + SM_FULL + i * 8, pol);
        }
    }
    uint32_t tnext = timer_ns() + (NFIRST + 1) * PACE - OFFS + STAG * cta * PACE / NCTA;
    const unsigned cnt1 = read_counter(&gs->cnt[1]);
    uint4 xv;
    if (tid < 128) {
        const __nv_bfloat16* x = (tid < 64 ? xB : xA) + ((tid >> 4) & 3) * 512 + j * 128 + (tid & 15) * 8;
        xv = __ldg(reinterpret_cast<const uint4*>(x));
    }
    if (tid == 0) TLX(21);
    const int w = __shfl_sync(0xffffffffu, tid >> 5, 0);
    const int pr = cta >> 1;
    const int slice = pr < 4 ? pr : pr < 36 ? 4 + ((pr - 4) & 7) * 4 + ((pr - 4) >> 3) : 36 + (pr - 36) % 7 * 4 + (pr - 36) / 7;

    if (w >= 8) {
        if (w == 8) {
            asm volatile(BAR2 ::: "memory");
            int slot = NFIRST, tail = NFIRST - INFLIGHT;
#pragma unroll 1
            for (int i = NFIRST; i < NITEM; i++) {
                const uint32_t dst = sb + slot * SLOT, bar = sb + SM_FULL + i * 8;
                if (++slot == NSLOT) slot = 0;
                if ((i & ~1) == IT_Q || (i & ~1) == IT_OP) continue;
                const bool ckv = i >= IT_C && i < IT_K1, wo = i >= IT_WO;
                const bool tiled = ckv || i < IT_K0 || i >= IT_WUV;
                const CUtensorMap* tm = &maps.wqB + (i < IT_K0 ? (i >> 1) : ckv ? 6 : wo ? 4 + (slice >> 5) : 3);
                const int c0 = wo ? (slice & 31) * 16 : i >= IT_WUV ? cta * 32 : 0;
                const int c1 = i < IT_K0 ? j * 128 + (i & 1) * 64 : ckv ? cta * 128 + (i - IT_C) * 16 : 0;
                const int c2 = i < IT_K0 ? h * 2 : ckv ? 0 : wo ? (i - IT_WO) * 4 + (j & 1) * 2 : i & 1;
                const int c = i < IT_Q ? i - IT_K0 : i < IT_V0 ? i - IT_K1 + 8 : i < IT_OP ? i - IT_V0 : i - IT_V1 + 8;
                const __nv_bfloat16* src = (i < IT_V0 ? Kc : Vc) + kv_off + (size_t)c * (SLOT / 2);
                if (i >= NSLOT) mbar_wait(sb + SM_EMPTY + (i - NSLOT) * 8);
                if (tail >= 0) mbar_wait(sb + SM_FULL + tail * 8);
                ++tail;
                if (tail == IT_Q || tail == IT_OP) tail += 2;
                if (i >= DRAIN_AT) mbar_wait(sb + SM_FULL + (i - DRAIN) * 8);
                if (i == NITEM - 1) {
                    mbar_wait(sb + SM_EMPTY + (IT_W2 - NSLOT) * 8);
                    mbar_wait(sb + SM_FULL + BAR_PEER * 8);
                }
                if (i == NITEM - 1 - (slice < 32 ? AEARLY : BEARLY)) {
                    while (__all_sync(0xffffffffu, (int)(timer_ns() - (tnext - GLEAD)) < 0)) {}
                    asm volatile("bar.arrive 4, 64;" ::: "memory");
                }
                if (i != IT_K0) {
                    while (__all_sync(0xffffffffu, (int)(timer_ns() - tnext) < 0)) {}
                    tnext += PACE;
                    if (i >= TAPER_AT && i < TAPER_AT + TAPER_N) tnext += TAPER;
                }
                if (lane == 0) {
                    TLX(32 + i);
                    if (i == NITEM - 1) tma3d_pair(dst + (j & 1) * (IT_W2 - i) * SLOT, tm, c0, c1, c2, bar + (j & 1) * (IT_W2 - i) * 8, pol);
                    else if (tiled) tma3d(dst, tm, c0, c1, c2, bar, pol);
                    else bulk_load(dst, src, SLOT, bar, pol);
                }
            }
        } else {
            if (lane == 0) {
                mbar_init(sb + SM_FULL + IT_W2 * 8, 1);
                mbar_init(sb + SM_FULL + BAR_X * 8, 1);
                mbar_init(sb + SM_FULL + BAR_PEER * 8, 1);
                mbar_expect_tx(sb + SM_FULL + IT_W2 * 8, SLOT);
                mbar_expect_tx(sb + SM_FULL + BAR_X * 8, SLOT + 4096);
                mbar_expect_tx(sb + SM_FULL + BAR_PEER * 8, 4);
                asm volatile("fence.mbarrier_init.release.cluster;" ::: "memory");
            }
            if (lane < 6) asm volatile("prefetch.tensormap [%0];" ::"l"(&maps.wqA + lane) : "memory");
            asm volatile(BAR2 ::: "memory");
            asm volatile("bar.sync 3, 288;" ::: "memory");
            const unsigned epoch = epoch_of(cnt1);
            if (lane == 0) TL(9);
            signal_and_wait(&gs->cnt[0], epoch * NCTA, lane, sb);
            if (lane == 0) {
                TL(2);
                const uint4* q = gs->q[cta >> 5];
                uint32_t t1 = timer_ns();
#pragma unroll 1
                for (int i = 0; i < QN; i++) {
                    while ((int)(timer_ns() - t1) < 0) {}
                    t1 += QGAP;
                    bulk_load_nohint(sb + slot_off(IT_Q) + i * (2 * SLOT / QN), q + i * (2048 / QN), 2 * SLOT / QN,
                                     sb + SM_FULL + (IT_Q + i / (QN / 2)) * 8);
                }
            }
            asm volatile("bar.sync 3, 288;" ::: "memory");
            if (lane == 0) TL(13);
            signal_and_wait(&gs->cnt[1], epoch * NCTA, lane, sb);
            mbar_wait(sb + SM_EMPTY + (IT_OP - NSLOT) * 8);
            mbar_wait(sb + SM_EMPTY + (IT_OP + 1 - NSLOT) * 8);
            if (lane == 0) {
                TL(3);
                const uint4* op = gs->op[cta];
                bulk_load_nohint(sb + SM_MX, gs->stat[h], 1024, sb + SM_FULL + IT_OP * 8);
                uint32_t t1 = timer_ns();
#pragma unroll 1
                for (int i = 0; i < OPN; i++) {
                    while ((int)(timer_ns() - t1) < 0) {}
                    t1 += OPGAP;
                    bulk_load_nohint(sb + slot_off(IT_OP) + i * (2 * SLOT / OPN), op + i * (2048 / OPN), 2 * SLOT / OPN,
                                     sb + SM_FULL + (IT_OP + i / (OPN / 2)) * 8);
                }
            }
            mbar_wait(sb + SM_FULL + LATAT * 8);
            if (lane == 0) bulk_load_nohint(sb + SM_LAT, gs->lat[h], 4096, sb + SM_FULL + BAR_LAT * 8);
            mbar_wait(sb + SM_EMPTY + (IT_X - NSLOT) * 8);
            mbar_wait(sb + SM_EMPTY + (IT_X + 1 - NSLOT) * 8);
            asm volatile("bar.sync 4, 64;" ::: "memory");
            if (lane == 0) {
                TL(27);
                bulk_load_nohint(sb + slot_off(IT_X), gs->x[slice >> 5][(j & 1) * 12], SLOT + 4096, sb + SM_FULL + BAR_X * 8);
            }
        }
        const uint32_t oo  = __shfl_sync(0xffffffffu, (lane >> 3) * 2048 + slice * 32 + (j & 1) * 16 + (lane & 7) * 2, lane);
        const uint32_t src = __shfl_sync(0xffffffffu, sb + SM_FIN + ((j ^ w ^ 1) & 1) * 1536 + lane * 48, lane);
        const uint32_t sr2 = __shfl_sync(0xffffffffu, sb + SM_FIN + 3072 + lane * 80, lane);
        const uint32_t to  = w == 8 ? map_cta(sb, (j & 1) ^ 1) : sb;
        const uint32_t rcv = __shfl_sync(0xffffffffu, to + SM_RCV + lane * 4, lane);
        const uint32_t fin = __shfl_sync(0xffffffffu, to + SM_FULL + BAR_FIN * 8, lane);
        mbar_wait(sb + SM_FULL + (NITEM - 3) * 8);
        asm volatile("bar.sync 5, 320;" ::: "memory");
        const float4 p0 = ldsf4(src), p1 = ldsf4(src + 16);
        float sum = ((p0.x + p0.y) + (p0.z + p0.w)) + ((p1.x + p1.y) + (p1.z + p1.w));
        if (w == 8) {
            st_async32(rcv, __float_as_uint(sum), fin);
        } else {
            __nv_bfloat16* dst = reinterpret_cast<__nv_bfloat16*>(reinterpret_cast<char*>(out) + oo);
            mbar_wait(sb + SM_FULL + BAR_FIN * 8);
            if (lane == 0) TLX(154);
            sum += ldsf(rcv);
            asm volatile("bar.sync 7, 288;" ::: "memory");
            const float4 q0 = ldsf4(sr2), q1 = ldsf4(sr2 + 16), q2 = ldsf4(sr2 + 32), q3 = ldsf4(sr2 + 48);
            *dst = __float2bfloat16((((q0.x + sum) + q0.y) + (q0.z + q0.w) + ((q1.x + q1.y) + (q1.z + q1.w))) +
                                    (((q2.x + q2.y) + (q2.z + q2.w)) + ((q3.x + q3.y) + (q3.z + q3.w))));
            if (lane == 0) TLX(4);
        }
        return;
    }

    const int g = lane >> 2, t = lane & 3;
    const uint32_t in0 = sb + SM_IN0, in1 = sb + SM_IN1;
    const int hx = (h & 4) * 4 + (((h >> 3) + (h >> 2 & 1)) & 3) * 4 + (h & 3);
    uint32_t* const ctx_dst = &gs->x[1][hx][(j * 4 + (w & 3)) * 16 + ((g ^ (w & 2)) & 3) * 4 + ((t - w) & 3)];
    uint32_t* const o_dst = &gs->x[0][hx][j * 64 + ((tid & 60) ^ ((j & 1) * 16)) + ((t - g) & 3)];
    uint32_t* const lat_dst = &gs->lat[h][g & 3][j * 64 + ((w >> 1) ^ (g & 1)) * 16 + t * 4 + ((w * 2 ^ t) & 2)];
    {
        if (lane == 0) {
            const uint32_t bars = sb + (w < 4 ? SM_EMPTY : SM_FULL + NFIRST * 8) + (w & 3) * 14 * 8;
            const uint32_t cnt = w < 4 ? 8 : 1;
#pragma unroll
            for (int i = 0; i < 14; i++) mbar_init(bars + i * 8, cnt);
            if (w >= 4) {
#pragma unroll
                for (int i = 0; i < 14; i++)
                    mbar_expect_tx(bars + i * 8, (i == (IT_OP - NFIRST) % 14 && w == 4 + (IT_OP - NFIRST) / 14) ? SLOT + 1024 :
                                                 (i >= 12 && w == 7) ? (i == 12 ? 4096 : 128) : SLOT);
            }
            asm volatile("fence.mbarrier_init.release.cluster;" ::: "memory");
        }
        if (tid == 0) TL(22);
        asm volatile(BAR2 ::: "memory");
        if (lane < 16) st_rlx2(lat_dst, EMPTY, EMPTY);
        if (lane < 16 && w < 4) st_rlx(ctx_dst, EMPTY);
        if (tid < 64) st_rlx(o_dst, EMPTY);
        if (tid < 128) sts128((tid < 64 ? in0 : in1) + ((tid >> 4) & 3) * 272 + (tid & 15) * 16, xv);
    }
    bar_consumers();
    const uint32_t tag = epoch_tag(epoch_of(cnt1));
    if (tid == 0) TL(23);

    float acc[2][2];
    tile_mma<true>(sb, IT_WQB, in0, w, lane, acc);
    if (tid == 0) TL(24);
    publish(gs->part[0][cta], w, lane, acc, tag);
    if (tid == 0) TL(6);
    tile_mma<true>(sb, IT_WQA, in1, w, lane, acc);
    publish(gs->part[1][cta], w, lane, acc, tag);
    if (tid == 0) TL(7);
    bar_consumers();

    const float SC = 0.08838834764831845f * 1.4426950408889634f;
    gather(gs->part[0][h * 4], in0, tid, tag);
    if (tid == 0) TL(8);
    tile_mma<false>(sb, IT_WUK, in0, w, lane, acc);
    if (tid == 0) TL(25);
    if (lane < 16) {
        uint32_t* q = reinterpret_cast<uint32_t*>(gs->q[g]) + (2 * j + (w >> 2)) * 1024 + h * 32 + t;
        const int ch = 2 * (w & 3);
        q[((ch) ^ (h & 7)) * 4]     = pack_bf16(acc[0][0] * SC, acc[0][1] * SC);
        q[((ch + 1) ^ (h & 7)) * 4] = pack_bf16(acc[1][0] * SC, acc[1][1] * SC);
    }
    __syncwarp();
    asm volatile("bar.arrive 3, 288;" ::: "memory");
    gather(gs->part[1][h * 4], in1, tid, tag);
    if (tid == 0) TL(28);

    uint32_t qf[16];
#pragma unroll
    for (int c = 0; c < 8; c++) {
        qf[2 * c]     = lds32(in1 + j * 272 + ((c ^ g) << 4) + t * 4);
        qf[2 * c + 1] = lds32(in1 + j * 272 + 128 + ((c ^ g) << 4) + t * 4);
    }
    const uint32_t sc_w = sb + SM_SC + w * 512;
    auto k_item = [&](int item, uint32_t sc) {
        mbar_wait(sb + SM_FULL + item * 8);
        const uint32_t base = sb + slot_off(item) + ((lane & 7) + (lane & 8)) * 256 + ((lane >> 4) << 7);
        float s[4][4];
#pragma unroll
        for (int T = 0; T < 4; T++) { s[T][0] = s[T][1] = s[T][2] = s[T][3] = 0.f; }
#pragma unroll
        for (int c = 0; c < 8; c++) {
            const uint32_t a = base + ((c ^ (lane & 7)) << 4);
#pragma unroll
            for (int T = 0; T < 4; T++) {
                uint32_t r0, r1, r2, r3;
                ldsm4(a + T * 4096, r0, r1, r2, r3);
                mma16816(s[T], r0, r1, r2, r3, qf[2 * c], qf[2 * c + 1]);
            }
        }
        __syncwarp();
        if (lane == 0) mbar_arrive8(sb + SM_EMPTY + item * 8);
        if (t == (g >> 1)) {
#pragma unroll
            for (int T = 0; T < 4; T++) {
                stsf(sc + (16 * T + g) * 4,     (g & 1) ? s[T][1] : s[T][0]);
                stsf(sc + (16 * T + g + 8) * 4, (g & 1) ? s[T][3] : s[T][2]);
            }
        }
    };
    k_item(IT_K0 + w, sc_w);
    if (tid == 224) TL(10);

    {
        float s[2][2][4];
#pragma unroll
        for (int i = 0; i < 16; i++) (&s[0][0][0])[i] = 0.f;
        mbar_wait(sb + SM_FULL + IT_Q * 8);
        mbar_wait(sb + SM_FULL + (IT_Q + 1) * 8);
        if (tid == 0) TLX(96 + IT_Q);
        mbar_wait(sb + SM_FULL + (IT_C + w) * 8);
        const uint32_t cb0 = sb + slot_off(IT_C + w) + ((lane & 7) + ((lane >> 4) << 3)) * 128;
        const uint32_t cx = (((lane >> 3) & 1) ^ (lane & 7)) << 4;
        const uint32_t qr = ((lane & 7) + (lane & 8)) * 128;
        const uint32_t qx = ((lane >> 4) ^ (lane & 7)) << 4;
#pragma unroll
        for (int cb = 0; cb < 8; cb++) {
            const uint32_t qb = sb + slot_off(IT_Q + (cb >> 2)) + (cb & 3) * 4096 + qr;
#pragma unroll
            for (int k4 = 0; k4 < 4; k4++) {
                uint32_t b0, b1, b2, b3, a0, a1, a2, a3;
                ldsm4(cb0 + cb * 2048 + (cx ^ (k4 << 5)), b0, b1, b2, b3);
                ldsm4(qb + (qx ^ (k4 << 5)), a0, a1, a2, a3);
                mma16816(s[0][0], a0, a1, a2, a3, b0, b1);
                mma16816(s[0][1], a0, a1, a2, a3, b2, b3);
                ldsm4(qb + 2048 + (qx ^ (k4 << 5)), a0, a1, a2, a3);
                mma16816(s[1][0], a0, a1, a2, a3, b0, b1);
                mma16816(s[1][1], a0, a1, a2, a3, b2, b3);
            }
        }
        __syncwarp();
        if (lane == 0) { mbar_arrive(sb + SM_EMPTY + IT_Q * 8); mbar_arrive(sb + SM_EMPTY + (IT_Q + 1) * 8); }
#pragma unroll
        for (int r = 0; r < 4; r++) {
            const int mt = r >> 1, hi = (r & 1) * 2;
            float m = fmaxf(fmaxf(s[mt][0][hi], s[mt][0][hi + 1]), fmaxf(s[mt][1][hi], s[mt][1][hi + 1]));
            m = fmaxf(m, __shfl_xor_sync(0xffffffffu, m, 1));
            m = fmaxf(m, __shfl_xor_sync(0xffffffffu, m, 2));
            if (t == 0) stsf(sb + SM_MX + (8 * r + g) * 32 + w * 4, m);
        }
        bar_consumers();
        if (tid == 0) TL(11);
        uint32_t pf[2][4];
#pragma unroll
        for (int r = 0; r < 4; r++) {
            const int mt = r >> 1, hi = r & 1;
            const float4 m0 = ldsf4(sb + SM_MX + (8 * r + g) * 32), m1 = ldsf4(sb + SM_MX + (8 * r + g) * 32 + 16);
            const float m = fmaxf(fmaxf(fmaxf(m0.x, m0.y), fmaxf(m0.z, m0.w)), fmaxf(fmaxf(m1.x, m1.y), fmaxf(m1.z, m1.w)));
            const uint32_t p0 = pack_bf16(ex2(s[mt][0][2 * hi] - m), ex2(s[mt][0][2 * hi + 1] - m));
            const uint32_t p1 = pack_bf16(ex2(s[mt][1][2 * hi] - m), ex2(s[mt][1][2 * hi + 1] - m));
            pf[mt][hi] = p0; pf[mt][2 + hi] = p1;
            float l = (bf_lo(p0) + bf_hi(p0)) + (bf_lo(p1) + bf_hi(p1));
            l += __shfl_xor_sync(0xffffffffu, l, 1);
            l += __shfl_xor_sync(0xffffffffu, l, 2);
            if (t == 0) stsf(sb + SM_SUM + (8 * r + g) * 32 + w * 4, l);
        }
        sts128(sb + SM_PF + (w * 2 + 0) * 512 + lane * 16, make_uint4(pf[0][0], pf[0][1], pf[0][2], pf[0][3]));
        sts128(sb + SM_PF + (w * 2 + 1) * 512 + lane * 16, make_uint4(pf[1][0], pf[1][1], pf[1][2], pf[1][3]));
        bar_consumers();
        if (w == 0) {
            const float4 m0 = ldsf4(sb + SM_MX + lane * 32), m1 = ldsf4(sb + SM_MX + lane * 32 + 16);
            const float4 l0 = ldsf4(sb + SM_SUM + lane * 32), l1 = ldsf4(sb + SM_SUM + lane * 32 + 16);
            const float m = fmaxf(fmaxf(fmaxf(m0.x, m0.y), fmaxf(m0.z, m0.w)), fmaxf(fmaxf(m1.x, m1.y), fmaxf(m1.z, m1.w)));
            const float l = ((l0.x + l0.y) + (l0.z + l0.w)) + ((l1.x + l1.y) + (l1.z + l1.w));
            gs->stat[lane][cta] = make_float2(m, l);
        }
        float o[2][8][4];
#pragma unroll
        for (int i = 0; i < 64; i++) (&o[0][0][0])[i] = 0.f;
        const uint32_t vr = w * 2048 + ((lane & 7) + (lane & 8)) * 128;
        const uint32_t vx = ((lane >> 4) ^ (lane & 7)) << 4;
#pragma unroll
        for (int ks = 0; ks < 8; ks++) {
            const uint4 p0 = lds128(sb + SM_PF + (ks * 2 + 0) * 512 + lane * 16);
            const uint4 p1 = lds128(sb + SM_PF + (ks * 2 + 1) * 512 + lane * 16);
            const uint32_t vb = sb + slot_off(IT_C + ks) + vr;
#pragma unroll
            for (int n2 = 0; n2 < 4; n2++) {
                uint32_t b0, b1, b2, b3;
                ldsm4t(vb + (vx ^ (n2 << 5)), b0, b1, b2, b3);
                mma16816(o[0][2 * n2],     p0.x, p0.y, p0.z, p0.w, b0, b1);
                mma16816(o[0][2 * n2 + 1], p0.x, p0.y, p0.z, p0.w, b2, b3);
                mma16816(o[1][2 * n2],     p1.x, p1.y, p1.z, p1.w, b0, b1);
                mma16816(o[1][2 * n2 + 1], p1.x, p1.y, p1.z, p1.w, b2, b3);
            }
            __syncwarp();
            if (lane == 0) mbar_arrive(sb + SM_EMPTY + (IT_C + ks) * 8);
        }
        if (tid == 0) TL(12);
        mbar_wait(sb + SM_FULL + (IT_K1 + STG_AT + (w >> STG_SH)) * 8);
#pragma unroll
        for (int r = 0; r < 4; r++) {
            const int mt = r >> 1, hi = (r & 1) * 2;
            uint4* dst = gs->op[(8 * r + g) * 4 + (w >> 1)] + (cta >> 6) * 1024 + (w & 1) * 512 + (cta & 63) * 8;
#pragma unroll
            for (int u = 0; u < 2; u++) {
                uint4 v;
                v.x = pack_bf16(o[mt][4 * u][hi],     o[mt][4 * u][hi + 1]);
                v.y = pack_bf16(o[mt][4 * u + 1][hi], o[mt][4 * u + 1][hi + 1]);
                v.z = pack_bf16(o[mt][4 * u + 2][hi], o[mt][4 * u + 2][hi + 1]);
                v.w = pack_bf16(o[mt][4 * u + 3][hi], o[mt][4 * u + 3][hi + 1]);
                dst[(t + 4 * u) ^ (cta & 7)] = v;
            }
        }
        if (tid == 0) TL(29);
        asm volatile("bar.arrive 3, 288;" ::: "memory");
    }

    k_item(IT_K1 + w, sc_w + 256);
    __syncwarp();
    {
        const float4 s = ldsf4(sc_w + lane * 16);
        float m = fmaxf(fmaxf(s.x, s.y), fmaxf(s.z, s.w));
#pragma unroll
        for (int d = 1; d < 32; d <<= 1) m = fmaxf(m, __shfl_xor_sync(0xffffffffu, m, d));
        if (lane == 0) stsf(sb + SM_ML + w * 4, m);
        bar_consumers();
        const float4 m0 = ldsf4(sb + SM_ML), m1 = ldsf4(sb + SM_ML + 16);
        m = fmaxf(fmaxf(fmaxf(m0.x, m0.y), fmaxf(m0.z, m0.w)), fmaxf(fmaxf(m1.x, m1.y), fmaxf(m1.z, m1.w))) * SC;
        const uint32_t p0 = pack_bf16(ex2(fmaf(s.x, SC, -m)), ex2(fmaf(s.y, SC, -m)));
        const uint32_t p1 = pack_bf16(ex2(fmaf(s.z, SC, -m)), ex2(fmaf(s.w, SC, -m)));
        float l = (bf_lo(p0) + bf_hi(p0)) + (bf_lo(p1) + bf_hi(p1));
#pragma unroll
        for (int d = 1; d < 32; d <<= 1) l += __shfl_xor_sync(0xffffffffu, l, d);
        if (lane == 0) stsf(sb + SM_ML + 32 + w * 4, l);
        sts64(sb + SM_PA + w * 256 + lane * 8, p0, p1);
        __syncwarp();
    }
    if (tid == 224) TL(14);

    float oa[4][4];
#pragma unroll
    for (int i = 0; i < 16; i++) (&oa[0][0])[i] = 0.f;
    auto v_item = [&](int item, uint32_t pa) {
        uint32_t p[8];
#pragma unroll
        for (int i = 0; i < 8; i++) p[i] = lds32(pa + i * 16 + t * 4);
        mbar_wait(sb + SM_FULL + item * 8);
        const uint32_t base = sb + slot_off(item) + ((lane & 7) + ((lane >> 4) << 3)) * 256 + ((lane & 8) << 4);
#pragma unroll
        for (int c = 0; c < 8; c++) {
            const uint32_t a = base + ((c ^ (lane & 7)) << 4);
            const uint32_t mask = ((c == (g ^ (2 * t))) ? 0x0000ffffu : 0u) | ((c == (g ^ (2 * t + 1))) ? 0xffff0000u : 0u);
#pragma unroll
            for (int T = 0; T < 4; T++) {
                uint32_t r0, r1, r2, r3;
                ldsm4t(a + T * 4096, r0, r1, r2, r3);
                mma16816(oa[T], r0, r1, r2, r3, p[2 * T] & mask, p[2 * T + 1] & mask);
            }
        }
        __syncwarp();
        if (lane == 0) mbar_arrive8(sb + SM_EMPTY + item * 8);
    };
    v_item(IT_V0 + w, sb + SM_PA + w * 256);
    if (tid == 224) TL(15);

    mbar_wait(sb + SM_FULL + IT_OP * 8);
    if (tid == 0) TLX(96 + IT_OP);
    if (w < 4) {
        const float2 st = ldsf2(sb + SM_MX + tid * 8);
        float m = st.x;
#pragma unroll
        for (int d = 1; d < 32; d <<= 1) m = fmaxf(m, __shfl_xor_sync(0xffffffffu, m, d));
        const uint32_t wb = pack_bf16(ex2(st.x - m), 0.f);
        float l = bf_lo(wb) * st.y;
#pragma unroll
        for (int d = 1; d < 32; d <<= 1) l += __shfl_xor_sync(0xffffffffu, l, d);
#pragma unroll
        for (int bb = 0; bb < 4; bb++) sts16(in0 + bb * 272 + tid * 2, bb == w ? (uint16_t)wb : (uint16_t)0);
        if (lane == 0) stsf(sb + SM_ML + 64 + w * 4, 1.f / l);
    }
    bar_consumers();
    tile_mma<true>(sb, IT_OP, in0, w, lane, acc);
    if (lane < 16) {
        const float inv = ldsf(sb + SM_ML + 64 + g * 4);
        const uint32_t v0 = pack_bf16(acc[0][0] * inv, acc[0][1] * inv), v1 = pack_bf16(acc[1][0] * inv, acc[1][1] * inv);
        st_rlx2(lat_dst, (t & 1) ? v1 : v0, (t & 1) ? v0 : v1);
    }
    if (tid == 0) TL(19);

    {
        const float4 l0 = ldsf4(sb + SM_ML + 32), l1 = ldsf4(sb + SM_ML + 48);
        const float inv = 1.f / (((l0.x + l0.y) + (l0.z + l0.w)) + ((l1.x + l1.y) + (l1.z + l1.w)));
        v_item(IT_V1 + w, sb + SM_PA + w * 256 + 128);
        const uint32_t so = sb + SM_PF + w * 512 + (16 * t + g) * 4;
        stsf(so,       (oa[0][0] + oa[1][0]) + (oa[2][0] + oa[3][0]));
        stsf(so + 32,  (oa[0][1] + oa[1][1]) + (oa[2][1] + oa[3][1]));
        stsf(so + 256, (oa[0][2] + oa[1][2]) + (oa[2][2] + oa[3][2]));
        stsf(so + 288, (oa[0][3] + oa[1][3]) + (oa[2][3] + oa[3][3]));
        bar_consumers();
        if (tid == 128) {
            const uint32_t peer = map_cta(sb, (j & 1) ^ 1);
            st_async32(peer + SM_RCV + 128, 0u, peer + SM_FULL + BAR_PEER * 8);
        }
        if (tid < 64) {
            float x = 0.f, y = 0.f;
#pragma unroll
            for (int i = 0; i < 8; i++) {
                const float2 v = ldsf2(sb + SM_PF + i * 512 + tid * 8);
                x += v.x; y += v.y;
            }
            st_rlx(o_dst, pack_bf16(x * inv, y * inv));
        }
    }
    if (tid == 0) TL(17);

    {
        const int item = IT_WUV + 1 - (w >> 2);
        const uint32_t lo = (g & 3) * 1024 + (item & 1) * 512 + (g & 1) * 64 + t * 16;
        const int wd = ((lane >> 2 & 2) + (lane >> 4)) ^ (lane >> 1 & 3);
        const uint32_t base = sb + (w < 4 ? slot_off(IT_WUV + 1) : slot_off(IT_WUV)) + ((lane & 6) * 4 + wd * 2 + (lane & 1)) * 64 + (((w ^ wd) & 3) << 4);
        mbar_wait(sb + SM_FULL + BAR_LAT * 8);
        uint4 a[8];
#pragma unroll
        for (int i = 0; i < 8; i++) a[i] = lds128_if(sb + SM_LAT + (lo ^ (i * 64)), lane < 16);
        int it = 0;
        while (refetch<8>(a, lane, [&](int i) { return (const char*)gs->lat[h] + (lo ^ (i * 64)); }))
            if (++it > SPIN_LIMIT) __trap();
        float c[4][4];
#pragma unroll
        for (int i = 0; i < 16; i++) (&c[0][0])[i] = 0.f;
        mbar_wait(sb + SM_FULL + item * 8);
#pragma unroll
        for (int kk = 0; kk < 8; kk++) {
            uint32_t r0, r1, r2, r3;
            ldsm4t(base + kk * 2048, r0, r1, r2, r3);
            mma16816(c[2 * (kk & 1)],     a[kk].x, a[kk].y, a[kk].z, a[kk].w, r0, r1);
            mma16816(c[2 * (kk & 1) + 1], a[kk].x, a[kk].y, a[kk].z, a[kk].w, r2, r3);
        }
        const float v0 = (c[0][0] + c[1][2]) + (c[2][0] + c[3][2]), v1 = (c[0][1] + c[1][3]) + (c[2][1] + c[3][3]);
        const uint32_t px = in1 + (w & 3) * 256 + lane * 8;
        if (w >= 4) {
            sts64(px, __float_as_uint(v0), __float_as_uint(v1));
            asm volatile("bar.arrive 6, 256;" ::: "memory");
        } else {
            asm volatile("bar.sync 6, 256;" ::: "memory");
            const float2 p = ldsf2(px);
            if (lane < 16) st_rlx(ctx_dst, pack_bf16(v0 + p.x, v1 + p.y));
        }
    }
    if (tid == 0) TL(16);

    {
        const bool isB = slice >= 32;
        const int r = j & 1;
        const uint32_t xl = isB ? t * 64 + (((g ^ (t & 2)) & 3) << 4) : (g & 3) * 256 + ((g & 1) * 4 + t) * 16;
        const uint32_t cs = isB ? 256 : 64;
        const uint32_t xo = r * 8192 + (w >> 1) * 1024 + (w & 1) * 2 * cs + xl, xz = (1 - r) * 12288 + w * 1024 + (g >> 2) * 2 * cs + xl;
        auto xoff = [&](int i) { return i < 6 ? (i >> 1) * 4096 + (xo ^ ((i & 1) * cs)) : xz ^ ((i & 1) * cs); };
        const char* src = (const char*)gs->x[slice >> 5][r * 12];
        uint32_t off[2], ofz[2];
#pragma unroll
        for (int u = 0; u < 2; u++) {
            const int tt = (lane & 7) >> 1;
            const int row = 8 * tt + 2 * ((2 * u + (lane >> 4) + tt) & 3) + (lane & 1);
            off[u] = sb + w * 2048 + row * 32 + ((((lane >> 3) ^ (row >> 2)) & 1) << 4);
            ofz[u] = __shfl_sync(0xffffffffu, sb + (w < 4 ? slot_off(IT_WO + 3) : slot_off(IT_W2)) + (w & 3) * 4096 + (lane & 8) * 256 +
                                              row * 32 + (((r ^ (row >> 2)) & 1) << 4), lane);
        }
        const uint32_t fin = __shfl_sync(0xffffffffu, sb + SM_FIN + (t & 1) * 768 + g * 48 + ((w ^ (t & 1)) << 2), lane);
        const uint32_t fi2 = __shfl_sync(0xffffffffu, sb + SM_FIN + 3072 + (t & 1) * 1280 + g * 80 + (((w * 2 + (t >> 1)) ^ (t * 2 & 2)) << 2), lane);
        uint32_t a[2][4][4];
        uint4 x[8];
        float c[4][4];
        auto load_w = [&](int i) {
            mbar_wait(sb + SM_FULL + (i < 3 ? IT_WO + i : w < 4 ? IT_WO + 3 : IT_W2) * 8);
#pragma unroll
            for (int q = 0; q < 4; q++)
                ldsm4t((i < 3 ? slot_off(IT_WO + i) + off[q & 1] : ofz[q & 1]) + (q >> 1) * 1024,
                       a[i & 1][q][0], a[i & 1][q][1], a[i & 1][q][2], a[i & 1][q][3]);
        };
        auto mma_w = [&](int i) {
#pragma unroll
            for (int q = 0; q < 4; q++) {
                if (i == 0 || i == 3) c[q][0] = c[q][1] = c[q][2] = c[q][3] = 0.f;
                mma16816(c[q], a[i & 1][q][0], a[i & 1][q][1], a[i & 1][q][2], a[i & 1][q][3],
                         (q & 1) ? x[2 * i + (q >> 1)].z : x[2 * i + (q >> 1)].x, (q & 1) ? x[2 * i + (q >> 1)].w : x[2 * i + (q >> 1)].y);
            }
        };
        load_w(0); load_w(1);
        mbar_wait(sb + SM_FULL + BAR_X * 8);
        if (tid == 224) TLX(20);
#pragma unroll
        for (int i = 0; i < 8; i++) x[i] = lds128_if(sb + slot_off(IT_X) + xoff(i), i >= 6 || lane < 16);
        int it = 0;
        while (true) {
            mma_w(0); mma_w(1);
            if (!refetch<6>(x, lane, [&](int i) { return src + xoff(i); })) break;
            if (++it > SPIN_LIMIT) __trap();
        }
        load_w(2);
        mma_w(2);
#pragma unroll
        for (int e = 0; e < 4; e++) stsf_if(fin + (e >> 1) * 1536 + (e & 1) * 384, (c[0][e] + c[1][e]) + (c[2][e] + c[3][e]), t < 2);
        asm volatile("bar.arrive 5, 320;" ::: "memory");
        if (tid == 0) TLX(18);
        load_w(3);
        mma_w(3);
#pragma unroll
        for (int e = 0; e < 2; e++) {
            const float lo = (c[0][e] + c[1][e]) + (c[2][e] + c[3][e]), hi = (c[0][e + 2] + c[1][e + 2]) + (c[2][e + 2] + c[3][e + 2]);
            stsf(fi2 + e * 640, t < 2 ? lo : hi);
        }
        asm volatile("bar.arrive 7, 288;" ::: "memory");
        if (tid == 224) TLX(26);
    }
}

typedef CUresult (*EncodeTiledFn)(CUtensorMap*, CUtensorMapDataType, cuuint32_t, void*, const cuuint64_t*,
                                  const cuuint64_t*, const cuuint32_t*, const cuuint32_t*, CUtensorMapInterleave,
                                  CUtensorMapSwizzle, CUtensorMapL2promotion, CUtensorMapFloatOOBfill);

void encode_map(EncodeTiledFn enc, CUtensorMap* tm, const void* p, cuuint64_t cols, cuuint64_t rows,
                cuuint32_t brows, cuuint32_t bblk) {
    cuuint64_t dims[3] = {64, rows, cols / 64};
    cuuint64_t strides[2] = {cols * 2, 128};
    cuuint32_t box[3] = {64, brows, bblk};
    cuuint32_t es[3] = {1, 1, 1};
    enc(tm, CU_TENSOR_MAP_DATA_TYPE_BFLOAT16, 3, const_cast<void*>(p), dims, strides, box, es,
        CU_TENSOR_MAP_INTERLEAVE_NONE, CU_TENSOR_MAP_SWIZZLE_128B, CU_TENSOR_MAP_L2_PROMOTION_L2_256B,
        CU_TENSOR_MAP_FLOAT_OOB_FILL_NONE);
}

void encode_slice_map(EncodeTiledFn enc, CUtensorMap* tm, const void* p, cuuint64_t cols, cuuint64_t rows, cuuint32_t bcols) {
    cuuint64_t dims[3] = {cols, 256, rows / 256};
    cuuint64_t strides[2] = {cols * 2, cols * 512};
    cuuint32_t box[3] = {bcols, 256, 32 / bcols};
    cuuint32_t es[3] = {1, 1, 1};
    enc(tm, CU_TENSOR_MAP_DATA_TYPE_BFLOAT16, 3, const_cast<void*>(p), dims, strides, box, es, CU_TENSOR_MAP_INTERLEAVE_NONE,
        bcols == 16 ? CU_TENSOR_MAP_SWIZZLE_32B : CU_TENSOR_MAP_SWIZZLE_64B, CU_TENSOR_MAP_L2_PROMOTION_L2_128B,
        CU_TENSOR_MAP_FLOAT_OOB_FILL_NONE);
}

}

extern "C" void kernel_launch(void* const* d_in, const int* in_sizes, int n_in, void* d_out, int out_size) {
    (void)in_sizes; (void)n_in; (void)out_size;
    static EncodeTiledFn enc = nullptr;
    static Scratch* gs = nullptr;
    if (!enc) {
        cudaGetSymbolAddress((void**)&gs, g_scratch);
        void* fn = nullptr;
        cudaDriverEntryPointQueryResult qr;
        cudaGetDriverEntryPoint("cuTensorMapEncodeTiled", &fn, cudaEnableDefault, &qr);
        enc = (EncodeTiledFn)fn;
        cudaFuncSetAttribute(fused_decode_kernel, cudaFuncAttributeMaxDynamicSharedMemorySize, SM_END);
    }
    Maps maps;
    encode_map(enc, &maps.wqB, d_in[7], 4096, 512, 64, 2);
    encode_map(enc, &maps.wqA, d_in[3], 4096, 512, 64, 2);
    encode_map(enc, &maps.wuk, d_in[8], 4096, 512, 64, 2);
    encode_slice_map(enc, &maps.wuv, d_in[9], 4096, 512, 32);
    encode_slice_map(enc, &maps.woB, d_in[10], 512, 4096, 16);
    encode_slice_map(enc, &maps.woA, d_in[4], 512, 4096, 16);
    encode_map(enc, &maps.ckv, d_in[6], 512, 16384, 16, 8);
    fused_decode_kernel<<<NCTA, NTHR, SM_END>>>((const __nv_bfloat16*)d_in[0], (const __nv_bfloat16*)d_in[5],
                                                (const __nv_bfloat16*)d_in[1], (const __nv_bfloat16*)d_in[2],
                                                (__nv_bfloat16*)d_out, gs, maps);
}
```

```cpp
#include <cuda_runtime.h>
#include <cuda_bf16.h>
#include <cuda.h>
#include <stdint.h>

namespace {

constexpr int NCTA   = 128;
constexpr int NSLOT  = 13;
constexpr int SLOT   = 16384;
constexpr int NITEM  = 56;
#define INFLIGHT 4
#define PACE 650
#define OFFS 600
#define STAG 0
#define OWAIT 0
#define FINMODE 1
#define FINDELAY 0
#define NFIRST 2
#define STARTER 256
#define CTXWAIT 0
#define LATAT 46
#define TAPER 250
#define TAPER_AT 49
#define TAPER_N 1
#define STG_AT 2
#define STG_SH 1
#define OPN 8
#define OPGAP 200
#define QN 2
#define QGAP 0
#define PFSTARTER 288
#define PFMODE 0
#define GLEAD 150
#define AEARLY 0
#define BEARLY 0
#define DRAIN_AT 99
#define DRAIN 2
#define AWAIT 0
#define NPOLL 4
#define FGAP 170
#define FDEL 0
constexpr int NTHR   = 320;
#define BAR2 "bar.sync 2, 320;"

constexpr int IT_WQB = 0, IT_WQA = 2, IT_WUK = 4, IT_K0 = 6, IT_Q = 14, IT_C = 16, IT_K1 = 24, IT_V0 = 32,
              IT_OP = 40, IT_V1 = 42, IT_WUV = 50, IT_WO = 52;
constexpr int IT_X = 56;
constexpr int IT_W2 = 58;
constexpr int BAR_LAT = 56, BAR_FIN = 57, BAR_X = 59, BAR_PEER = 60;

constexpr int SM_FULL  = NSLOT * SLOT;
constexpr int SM_EMPTY = SM_FULL + 512;
constexpr int SM_IN0   = SM_EMPTY + 512;
constexpr int SM_IN1   = SM_IN0 + 1088;
constexpr int SM_SC    = SM_IN1 + 1088;
constexpr int SM_PA    = SM_SC + 4096;
constexpr int SM_PF    = SM_PA + 2048;
constexpr int SM_MX    = SM_PF + 8192;
constexpr int SM_ML    = SM_MX + 1024;
constexpr int SM_RCV   = SM_ML + 128;
constexpr int SM_END   = SM_RCV + 144;
constexpr int SM_LAT   = SM_PF + 4096;
constexpr int SM_FIN   = SM_SC;
constexpr int SM_SUM   = SM_IN0;
static_assert(SM_END <= 232448, "smem");

struct Maps { CUtensorMap wqB, wqA, wuk, wuv, woA, woB, ckv; };

struct Scratch {
    unsigned cnt[32];
    float    part[2][NCTA][512];
    uint32_t x[2][32][256];
    uint32_t lat[32][4][256];
    uint4    q[4][2048];
    uint4    op[NCTA][2048];
    float2   stat[32][128];
};
__device__ __align__(128) Scratch g_scratch;
#define TLX(i) do {} while (0)
#define TL(i) do {} while (0)

constexpr int SPIN_LIMIT = 1 << 22;

__device__ __forceinline__ uint32_t smem_u32(const void* p) { return (uint32_t)__cvta_generic_to_shared(p); }
__device__ __forceinline__ void mbar_init(uint32_t bar, uint32_t cnt) {
    asm volatile("mbarrier.init.shared::cta.b64 [%0], %1;" ::"r"(bar), "r"(cnt) : "memory");
}
__device__ __forceinline__ void mbar_expect_tx(uint32_t bar, uint32_t bytes) {
    asm volatile("mbarrier.arrive.expect_tx.shared::cta.b64 _, [%0], %1;" ::"r"(bar), "r"(bytes) : "memory");
}
__device__ __forceinline__ void mbar_arrive(uint32_t bar) {
    asm volatile("mbarrier.arrive.shared::cta.b64 _, [%0];" ::"r"(bar) : "memory");
}
__device__ __forceinline__ void mbar_arrive8(uint32_t bar) {
    asm volatile("mbarrier.arrive.shared::cta.b64 _, [%0], 8;" ::"r"(bar) : "memory");
}
__device__ __forceinline__ void mbar_wait(uint32_t bar) {
    uint32_t done;
    int it = 0;
    do {
        asm volatile("{\n.reg .pred p;\nmbarrier.try_wait.parity.shared::cta.b64 p, [%1], 0;\nselp.u32 %0, 1, 0, p;\n}"
                     : "=r"(done) : "r"(bar) : "memory");
        if (++it > SPIN_LIMIT) __trap();
    } while (!done);
}
__device__ __forceinline__ uint32_t map_cta(uint32_t a, uint32_t rank) {
    uint32_t r; asm("mapa.shared::cluster.u32 %0, %1, %2;" : "=r"(r) : "r"(a), "r"(rank)); return r;
}
__device__ __forceinline__ void st_async32(uint32_t a, uint32_t v, uint32_t bar) {
    asm volatile("st.async.shared::cluster.mbarrier::complete_tx::bytes.b32 [%0], %1, [%2];" ::"r"(a), "r"(v), "r"(bar) : "memory");
}
__device__ __forceinline__ uint64_t evict_first() {
    uint64_t pol; asm volatile("createpolicy.fractional.L2::evict_first.b64 %0, 1.0;" : "=l"(pol)); return pol;
}
__device__ __forceinline__ void bulk_load(uint32_t dst, const void* src, uint32_t bytes, uint32_t bar, uint64_t pol) {
    asm volatile("cp.async.bulk.shared::cluster.global.mbarrier::complete_tx::bytes.L2::cache_hint [%0], [%1], %2, [%3], %4;"
                 ::"r"(dst), "l"(src), "r"(bytes), "r"(bar), "l"(pol) : "memory");
}
__device__ __forceinline__ void bulk_load_nohint(uint32_t dst, const void* src, uint32_t bytes, uint32_t bar) {
    asm volatile("cp.async.bulk.shared::cluster.global.mbarrier::complete_tx::bytes [%0], [%1], %2, [%3];"
                 ::"r"(dst), "l"(src), "r"(bytes), "r"(bar) : "memory");
}
__device__ __forceinline__ void bulk_load_pair(uint32_t dst, const void* src, uint32_t bytes, uint32_t bar) {
    asm volatile("cp.async.bulk.shared::cluster.global.mbarrier::complete_tx::bytes.multicast::cluster [%0], [%1], %2, [%3], %4;"
                 ::"r"(dst), "l"(src), "r"(bytes), "r"(bar), "h"((uint16_t)3) : "memory");
}
__device__ __forceinline__ void tma3d(uint32_t dst, const CUtensorMap* tm, int c0, int c1, int c2, uint32_t bar, uint64_t pol) {
    asm volatile("cp.async.bulk.tensor.3d.shared::cluster.global.mbarrier::complete_tx::bytes.L2::cache_hint [%0], [%1, {%3, %4, %5}], [%2], %6;"
                 ::"r"(dst), "l"(tm), "r"(bar), "r"(c0), "r"(c1), "r"(c2), "l"(pol) : "memory");
}
__device__ __forceinline__ void tma3d_pair(uint32_t dst, const CUtensorMap* tm, int c0, int c1, int c2, uint32_t bar, uint64_t pol) {
    asm volatile("cp.async.bulk.tensor.3d.shared::cluster.global.mbarrier::complete_tx::bytes.multicast::cluster.L2::cache_hint [%0], [%1, {%3, %4, %5}], [%2], %7, %6;"
                 ::"r"(dst), "l"(tm), "r"(bar), "r"(c0), "r"(c1), "r"(c2), "l"(pol), "h"((uint16_t)3) : "memory");
}
__device__ __forceinline__ void ldsm4(uint32_t a, uint32_t& r0, uint32_t& r1, uint32_t& r2, uint32_t& r3) {
    asm volatile("ldmatrix.sync.aligned.m8n8.x4.shared.b16 {%0,%1,%2,%3}, [%4];"
                 : "=r"(r0), "=r"(r1), "=r"(r2), "=r"(r3) : "r"(a) : "memory");
}
__device__ __forceinline__ void ldsm4t(uint32_t a, uint32_t& r0, uint32_t& r1, uint32_t& r2, uint32_t& r3) {
    asm volatile("ldmatrix.sync.aligned.m8n8.x4.trans.shared.b16 {%0,%1,%2,%3}, [%4];"
                 : "=r"(r0), "=r"(r1), "=r"(r2), "=r"(r3) : "r"(a) : "memory");
}
__device__ __forceinline__ void mma16816(float (&c)[4], uint32_t a0, uint32_t a1, uint32_t a2, uint32_t a3,
                                         uint32_t b0, uint32_t b1) {
    asm volatile("mma.sync.aligned.m16n8k16.row.col.f32.bf16.bf16.f32 {%0,%1,%2,%3}, {%4,%5,%6,%7}, {%8,%9}, {%0,%1,%2,%3};"
                 : "+f"(c[0]), "+f"(c[1]), "+f"(c[2]), "+f"(c[3])
                 : "r"(a0), "r"(a1), "r"(a2), "r"(a3), "r"(b0), "r"(b1));
}
__device__ __forceinline__ uint32_t lds32(uint32_t a) {
    uint32_t v; asm volatile("ld.shared.b32 %0, [%1];" : "=r"(v) : "r"(a) : "memory"); return v;
}
__device__ __forceinline__ float ldsf(uint32_t a) {
    float v; asm volatile("ld.shared.f32 %0, [%1];" : "=f"(v) : "r"(a) : "memory"); return v;
}
__device__ __forceinline__ float2 ldsf2(uint32_t a) {
    float2 v; asm volatile("ld.shared.v2.f32 {%0,%1}, [%2];" : "=f"(v.x), "=f"(v.y) : "r"(a) : "memory"); return v;
}
__device__ __forceinline__ float4 ldsf4(uint32_t a) {
    float4 v; asm volatile("ld.shared.v4.f32 {%0,%1,%2,%3}, [%4];" : "=f"(v.x), "=f"(v.y), "=f"(v.z), "=f"(v.w) : "r"(a) : "memory"); return v;
}
__device__ __forceinline__ uint4 lds128(uint32_t a) {
    uint4 v; asm volatile("ld.shared.v4.b32 {%0,%1,%2,%3}, [%4];" : "=r"(v.x), "=r"(v.y), "=r"(v.z), "=r"(v.w) : "r"(a) : "memory"); return v;
}
__device__ __forceinline__ uint4 lds128_if(uint32_t a, bool on) {
    uint4 v;
    asm volatile("{\n.reg .pred p;\nsetp.ne.u32 p, %5, 0;\n@p ld.shared.v4.b32 {%0,%1,%2,%3}, [%4];\n}"
                 : "=r"(v.x), "=r"(v.y), "=r"(v.z), "=r"(v.w) : "r"(a), "r"((uint32_t)on) : "memory");
    return v;
}
__device__ __forceinline__ void stsf_if(uint32_t a, float v, bool on) {
    asm volatile("{\n.reg .pred p;\nsetp.ne.u32 p, %2, 0;\n@p st.shared.f32 [%0], %1;\n}" ::"r"(a), "f"(v), "r"((uint32_t)on) : "memory");
}
__device__ __forceinline__ void sts16(uint32_t a, uint16_t v) { asm volatile("st.shared.b16 [%0], %1;" ::"r"(a), "h"(v) : "memory"); }
__device__ __forceinline__ void sts32(uint32_t a, uint32_t v) { asm volatile("st.shared.b32 [%0], %1;" ::"r"(a), "r"(v) : "memory"); }
__device__ __forceinline__ void stsf(uint32_t a, float v) { asm volatile("st.shared.f32 [%0], %1;" ::"r"(a), "f"(v) : "memory"); }
__device__ __forceinline__ void sts64(uint32_t a, uint32_t x, uint32_t y) {
    asm volatile("st.shared.v2.b32 [%0], {%1,%2};" ::"r"(a), "r"(x), "r"(y) : "memory");
}
__device__ __forceinline__ void sts128(uint32_t a, uint4 v) {
    asm volatile("st.shared.v4.b32 [%0], {%1,%2,%3,%4};" ::"r"(a), "r"(v.x), "r"(v.y), "r"(v.z), "r"(v.w) : "memory");
}
__device__ __forceinline__ uint32_t pack_bf16(float lo, float hi) {
    uint32_t r; asm("cvt.rn.bf16x2.f32 %0, %1, %2;" : "=r"(r) : "f"(hi), "f"(lo)); return r;
}
__device__ __forceinline__ float bf_lo(uint32_t v) { return __uint_as_float(v << 16); }
__device__ __forceinline__ float bf_hi(uint32_t v) { return __uint_as_float(v & 0xffff0000u); }
__device__ __forceinline__ float ex2(float x) { float y; asm("ex2.approx.ftz.f32 %0, %1;" : "=f"(y) : "f"(x)); return y; }
__device__ __forceinline__ uint32_t timer_ns() { uint32_t t; asm volatile("mov.u32 %0, %%globaltimer_lo;" : "=r"(t)); return t; }
__device__ __forceinline__ void bar_consumers() { asm volatile("bar.sync 1, 256;" ::: "memory"); }

__device__ __forceinline__ uint32_t tagf(float v, uint32_t tag) { return (__float_as_uint(v) & 0xffffff00u) | tag; }
__device__ __forceinline__ uint2 ld_rlx2(const float* p) {
    uint2 v; asm volatile("ld.relaxed.gpu.global.v2.b32 {%0,%1}, [%2];" : "=r"(v.x), "=r"(v.y) : "l"(p) : "memory"); return v;
}
__device__ __forceinline__ float untag(uint32_t v) { return __uint_as_float(v & 0xffffff00u); }

__device__ __forceinline__ uint32_t slot_off(int item) { return (uint32_t)(item % NSLOT) * SLOT; }

template <bool TRANS, bool RELEASE = true>
__device__ __forceinline__ void tile_mma(uint32_t sb, int item, uint32_t in, int w, int lane, float (&acc)[2][2]) {
    const int g = lane >> 2, t = lane & 3;
    float c[4][4];
#pragma unroll
    for (int i = 0; i < 16; i++) (&c[0][0])[i] = 0.f;
    uint32_t a[16];
    const uint32_t ia = in + (g & 3) * 272 + t * 4;
#pragma unroll
    for (int i = 0; i < 16; i++) a[i] = lds32(ia + i * 16);
    const uint32_t s0 = sb + slot_off(item), s1 = sb + slot_off(item + 1);
    if (TRANS) {
        const int r = (lane & 7) + (lane & 8);
        const int ch = 2 * (w & 3) + (lane >> 4);
        const uint32_t off = (w >> 2) * 8192 + r * 128 + ((ch ^ (lane & 7)) << 4);
#pragma unroll
        for (int kk = 0; kk < 8; kk++) {
            if ((kk & 3) == 0) mbar_wait(sb + SM_FULL + (item + (kk >> 2)) * 8);
            uint32_t r0, r1, r2, r3;
            ldsm4t(((kk >> 2) ? s1 : s0) + off + (kk & 3) * 2048, r0, r1, r2, r3);
            mma16816(c[2 * (kk & 1)],     a[2 * kk], 0u, a[2 * kk + 1], 0u, r0, r1);
            mma16816(c[2 * (kk & 1) + 1], a[2 * kk], 0u, a[2 * kk + 1], 0u, r2, r3);
        }
    } else {
        mbar_wait(sb + SM_FULL + (item + (w >> 2)) * 8);
        const int r = 16 * (w & 3) + (lane & 7) + ((lane >> 4) << 3);
        const uint32_t base = ((w >> 2) ? s1 : s0) + r * 128 + ((((lane >> 3) & 1) ^ (lane & 7)) << 4);
#pragma unroll
        for (int kk = 0; kk < 8; kk++) {
            uint32_t r0, r1, r2, r3;
            ldsm4((base ^ ((kk & 3) << 5)) + (kk >> 2) * 8192, r0, r1, r2, r3);
            mma16816(c[2 * (kk & 1)],     a[2 * kk], 0u, a[2 * kk + 1], 0u, r0, r1);
            mma16816(c[2 * (kk & 1) + 1], a[2 * kk], 0u, a[2 * kk + 1], 0u, r2, r3);
        }
    }
    if (RELEASE) {
        __syncwarp();
        if (lane == 0) {
            mbar_arrive(sb + SM_EMPTY + item * 8);
            mbar_arrive(sb + SM_EMPTY + (item + 1) * 8);
        }
    }
    acc[0][0] = c[0][0] + c[2][0]; acc[0][1] = c[0][1] + c[2][1];
    acc[1][0] = c[1][0] + c[3][0]; acc[1][1] = c[1][1] + c[3][1];
}

__device__ __forceinline__ void publish(float* dst, int w, int lane, const float (&acc)[2][2], uint32_t tag) {
    if (lane < 16)
        asm volatile("st.relaxed.gpu.global.v4.b32 [%0], {%1,%2,%3,%4};" ::"l"(dst + w * 64 + lane * 4),
                     "r"(tagf(acc[0][0], tag)), "r"(tagf(acc[0][1], tag)), "r"(tagf(acc[1][0], tag)), "r"(tagf(acc[1][1], tag)) : "memory");
}

__device__ __forceinline__ void gather(const float* part, uint32_t in, int tid, uint32_t tag) {
    const float* p = part + tid * 2;
    uint2 v0, v1, v2, v3;
    int it = 0;
    while (true) {
        v0 = ld_rlx2(p); v1 = ld_rlx2(p + 512); v2 = ld_rlx2(p + 1024); v3 = ld_rlx2(p + 1536);
        uint32_t bad = ((v0.x ^ tag) | (v0.y ^ tag) | (v1.x ^ tag) | (v1.y ^ tag) |
                        (v2.x ^ tag) | (v2.y ^ tag) | (v3.x ^ tag) | (v3.y ^ tag)) & 0xffu;
        if (__all_sync(0xffffffffu, bad == 0)) break;
        if (++it > SPIN_LIMIT) __trap();
    }
    float x = (untag(v0.x) + untag(v1.x)) + (untag(v2.x) + untag(v3.x));
    float y = (untag(v0.y) + untag(v1.y)) + (untag(v2.y) + untag(v3.y));
    sts32(in + ((tid >> 3) & 3) * 272 + (tid >> 5) * 32 + (tid & 1) * 16 + (tid & 6) * 2, pack_bf16(x, y));
    bar_consumers();
}

constexpr uint32_t EMPTY = 0xffffffffu;
__device__ __forceinline__ void st_rlx(uint32_t* p, uint32_t v) {
    asm volatile("st.relaxed.gpu.global.b32 [%0], %1;" ::"l"(p), "r"(v) : "memory");
}
__device__ __forceinline__ void st_rlx_if(uint64_t p, uint32_t v, bool on) {
    asm volatile("{\n.reg .pred p;\nsetp.ne.u32 p, %2, 0;\n@p st.relaxed.gpu.global.b32 [%0], %1;\n}" ::"l"(p), "r"(v), "r"((uint32_t)on) : "memory");
}
__device__ __forceinline__ void st_rlx2(uint32_t* p, uint32_t v0, uint32_t v1) {
    asm volatile("st.relaxed.gpu.global.v2.b32 [%0], {%1,%2};" ::"l"(p), "r"(v0), "r"(v1) : "memory");
}
__device__ __forceinline__ void ld_rlx4_if(uint4& v, const void* p, bool need) {
    asm volatile("{\n.reg .pred p;\nsetp.ne.u32 p, %5, 0;\n@p ld.relaxed.gpu.global.v4.b32 {%0,%1,%2,%3}, [%4];\n}"
                 : "+r"(v.x), "+r"(v.y), "+r"(v.z), "+r"(v.w) : "l"(p), "r"((uint32_t)need) : "memory");
}

template <int HALF, class F>
__device__ __forceinline__ bool refetch(uint4 (&x)[8], int lane, F addr) {
    uint32_t m[8], m0 = 0, m1 = 0;
#pragma unroll
    for (int i = 0; i < 8; i++) {
        m[i] = max(max(x[i].x, x[i].y), max(x[i].z, x[i].w));
        if (i < HALF) m0 = max(m0, m[i]); else m1 = max(m1, m[i]);
    }
    if (!__any_sync(0xffffffffu, (m0 == EMPTY && lane < 16) || m1 == EMPTY)) return false;
#pragma unroll
    for (int i = 0; i < 8; i++) ld_rlx4_if(x[i], addr(i), m[i] == EMPTY && (i >= HALF || lane < 16));
    return true;
}

__device__ __forceinline__ unsigned read_counter(const unsigned* cnt) {
    unsigned v;
    asm volatile("ld.relaxed.gpu.global.u32 %0, [%1];" : "=r"(v) : "l"(cnt) : "memory");
    return v;
}
__device__ __forceinline__ unsigned epoch_of(unsigned cnt) {
    asm volatile("" : "+r"(cnt) :: "memory");
    return cnt / NCTA + 1;
}
__device__ __forceinline__ uint32_t epoch_tag(unsigned epoch) { return (epoch & 0x7fu) | 0x80u; }

__device__ __forceinline__ void signal_and_wait(unsigned* cnt, unsigned target, int lane, uint32_t sb) {
    if (lane == 0) asm volatile("red.release.gpu.global.add.u32 [%0], 1;" ::"l"(cnt) : "memory");
    if (lane == 0) TL(30 + (((size_t)cnt >> 2) & 1));
    int it = 0;
    while (true) {
        unsigned v;
        asm volatile("ld.acquire.gpu.global.u32 %0, [%1];" : "=r"(v) : "l"(cnt) : "memory");
        if (__all_sync(0xffffffffu, (int)(v - target) >= 0)) break;
        if (++it > SPIN_LIMIT) __trap();
    }
    asm volatile("fence.proxy.async.global;" ::: "memory");
}

__global__ void __cluster_dims__(2, 1, 1) __launch_bounds__(NTHR, 1)
fused_decode_kernel(const __nv_bfloat16* __restrict__ xA, const __nv_bfloat16* __restrict__ xB,

                    const __nv_bfloat16* __restrict__ Kc, const __nv_bfloat16* __restrict__ Vc,
                    __nv_bfloat16* __restrict__ out, Scratch* gs, const __grid_constant__ Maps maps) {
    extern __shared__ __align__(1024) unsigned char smem_raw[];
    const uint32_t sb = smem_u32(smem_raw);
    const int tid = threadIdx.x, lane = tid & 31;
    const int cta = blockIdx.x, h = cta >> 2, j = cta & 3;
    const size_t kv_off = (size_t)blockIdx.x * 4096 * 128;
    if (tid == PFSTARTER) {
        asm volatile("cp.async.bulk.prefetch.L2.global [%0], %1;" ::"l"(Kc + kv_off), "r"(PFMODE == 2 ? 2 * SLOT : SLOT) : "memory");
        TLX(0);
    }
    if (tid == STARTER) {
        const uint64_t pol = evict_first();
#pragma unroll
        for (int i = 0; i < NFIRST; i++) mbar_init(sb + SM_FULL + i * 8, 1);
        asm volatile("fence.mbarrier_init.release.cluster;" ::: "memory");
#pragma unroll
        for (int i = 0; i < NFIRST; i++) {
            TLX(32 + i);
            mbar_expect_tx(sb + SM_FULL + i * 8, SLOT);
            tma3d(sb + i * SLOT, &maps.wqB, 0, j * 128 + i * 64, h * 2, sb + SM_FULL + i * 8, pol);
        }
    }
    uint32_t tnext = timer_ns() + (NFIRST + (PFMODE == 1 ? 0 : PFMODE == 2 ? 2 : 1)) * PACE - OFFS;
    const unsigned cnt1 = read_counter(&gs->cnt[1]);
    uint4 xv;
    if (tid < 128) {
        const __nv_bfloat16* x = (tid < 64 ? xB : xA) + ((tid >> 4) & 3) * 512 + j * 128 + (tid & 15) * 8;
        xv = __ldg(reinterpret_cast<const uint4*>(x));
    }
    if (tid == 0) TLX(21);
    const int w = __shfl_sync(0xffffffffu, tid >> 5, 0);
    const int pr = cta >> 1;
    const int slice = pr < 4 ? pr : pr < 36 ? 4 + ((pr - 4) & 7) * 4 + ((pr - 4) >> 3) : 36 + (pr - 36) % 7 * 4 + (pr - 36) / 7;

    if (w >= 8) {
        if (w == 8) {
            asm volatile(BAR2 ::: "memory");
            const uint64_t pol = evict_first();
            int slot = NFIRST, tail = NFIRST - INFLIGHT;
#pragma unroll 1
            for (int i = NFIRST; i < NITEM; i++) {
                const uint32_t dst = sb + slot * SLOT, bar = sb + SM_FULL + i * 8;
                if (++slot == NSLOT) slot = 0;
                if ((i & ~1) == IT_Q || (i & ~1) == IT_OP) continue;
                const bool ckv = i >= IT_C && i < IT_K1, wo = i >= IT_WO;
                const bool tiled = ckv || i < IT_K0 || i >= IT_WUV;
                const CUtensorMap* tm = &maps.wqB + (i < IT_K0 ? (i >> 1) : ckv ? 6 : wo ? 4 + (slice >> 5) : 3);
                const int c0 = wo ? (slice & 31) * 16 : i >= IT_WUV ? cta * 32 : 0;
                const int c1 = i < IT_K0 ? j * 128 + (i & 1) * 64 : ckv ? cta * 128 + (i - IT_C) * 16 : 0;
                const int c2 = i < IT_K0 ? h * 2 : ckv ? 0 : wo ? (i - IT_WO) * 4 + (j & 1) * 2 : i & 1;
                const int c = i < IT_Q ? i - IT_K0 : i < IT_V0 ? i - IT_K1 + 8 : i < IT_OP ? i - IT_V0 : i - IT_V1 + 8;
                const __nv_bfloat16* src = (i < IT_V0 ? Kc : Vc) + kv_off + (size_t)c * (SLOT / 2);
                if (i >= NSLOT) mbar_wait(sb + SM_EMPTY + (i - NSLOT) * 8);
                if (tail >= 0) mbar_wait(sb + SM_FULL + tail * 8);
                ++tail;
                if (tail == IT_Q || tail == IT_OP) tail += 2;
                if (i >= DRAIN_AT) mbar_wait(sb + SM_FULL + (i - DRAIN) * 8);
                if (i == NITEM - 1) mbar_wait(sb + SM_FULL + BAR_PEER * 8);
                if (i == NITEM - 1 - (slice < 32 ? AEARLY : BEARLY)) {
                    while (__all_sync(0xffffffffu, (int)(timer_ns() - (tnext - GLEAD)) < 0)) {}
                    asm volatile("bar.arrive 4, 64;" ::: "memory");
                }
                if (PFMODE == 1 || (PFMODE == 0 ? i != IT_K0 : (i & ~1) != IT_K0)) {
                    while (__all_sync(0xffffffffu, (int)(timer_ns() - tnext) < 0)) {}
                    tnext += PACE;
                    if (i >= TAPER_AT && i < TAPER_AT + TAPER_N) tnext += TAPER;
                }
                if (lane == 0) {
                    TLX(32 + i);
                    if (i == NITEM - 1) tma3d_pair(dst + (j & 1) * (IT_W2 - i) * SLOT, tm, c0, c1, c2, bar + (j & 1) * (IT_W2 - i) * 8, pol);
                    else if (tiled) tma3d(dst, tm, c0, c1, c2, bar, pol);
                    else bulk_load(dst, src, SLOT, bar, pol);
                }
            }
        } else {
            if (lane == 0) {
                mbar_init(sb + SM_FULL + IT_W2 * 8, 1);
                mbar_init(sb + SM_FULL + BAR_X * 8, 1);
                mbar_init(sb + SM_FULL + BAR_PEER * 8, 1);
                mbar_expect_tx(sb + SM_FULL + IT_W2 * 8, SLOT);
                mbar_expect_tx(sb + SM_FULL + BAR_X * 8, SLOT + 4096);
                mbar_expect_tx(sb + SM_FULL + BAR_PEER * 8, 8);
                asm volatile("fence.mbarrier_init.release.cluster;" ::: "memory");
            }
            if (lane < 6) asm volatile("prefetch.tensormap [%0];" ::"l"(&maps.wqA + lane) : "memory");
            asm volatile(BAR2 ::: "memory");
            asm volatile("bar.sync 3, 288;" ::: "memory");
            const unsigned epoch = epoch_of(cnt1);
            if (lane == 0) TL(9);
            signal_and_wait(&gs->cnt[0], epoch * NCTA, lane, sb);
            if (lane == 0) {
                TL(2);
                const uint4* q = gs->q[cta >> 5];
                uint32_t t1 = timer_ns();
#pragma unroll 1
                for (int i = 0; i < QN; i++) {
                    while ((int)(timer_ns() - t1) < 0) {}
                    t1 += QGAP;
                    bulk_load_nohint(sb + slot_off(IT_Q) + i * (2 * SLOT / QN), q + i * (2048 / QN), 2 * SLOT / QN,
                                     sb + SM_FULL + (IT_Q + i / (QN / 2)) * 8);
                }
            }
            asm volatile("bar.sync 3, 288;" ::: "memory");
            if (lane == 0) TL(13);
            signal_and_wait(&gs->cnt[1], epoch * NCTA, lane, sb);
            mbar_wait(sb + SM_EMPTY + (IT_OP - NSLOT) * 8);
            mbar_wait(sb + SM_EMPTY + (IT_OP + 1 - NSLOT) * 8);
            if (lane == 0) {
                TL(3);
                const uint4* op = gs->op[cta];
                bulk_load_nohint(sb + SM_MX, gs->stat[h], 1024, sb + SM_FULL + IT_OP * 8);
                uint32_t t1 = timer_ns();
#pragma unroll 1
                for (int i = 0; i < OPN; i++) {
                    while ((int)(timer_ns() - t1) < 0) {}
                    t1 += OPGAP;
                    bulk_load_nohint(sb + slot_off(IT_OP) + i * (2 * SLOT / OPN), op + i * (2048 / OPN), 2 * SLOT / OPN,
                                     sb + SM_FULL + (IT_OP + i / (OPN / 2)) * 8);
                }
            }
            mbar_wait(sb + SM_FULL + LATAT * 8);
            if (lane == 0) bulk_load_nohint(sb + SM_LAT, gs->lat[h], 4096, sb + SM_FULL + BAR_LAT * 8);
            mbar_wait(sb + SM_EMPTY + (IT_X - NSLOT) * 8);
            mbar_wait(sb + SM_EMPTY + (IT_X + 1 - NSLOT) * 8);
            asm volatile("bar.sync 4, 64;" ::: "memory");
            if (lane == 0) {
                TL(27);
                bulk_load_nohint(sb + slot_off(IT_X), gs->x[slice >> 5][(j & 1) * 12], SLOT + 4096, sb + SM_FULL + BAR_X * 8);
            }
        }
        const uint32_t oo  = __shfl_sync(0xffffffffu, (lane >> 3) * 2048 + slice * 32 + (j & 1) * 16 + (lane & 7) * 2, lane);
        const uint32_t src = __shfl_sync(0xffffffffu, sb + SM_FIN + ((j ^ w ^ 1) & 1) * 1536 + lane * 48, lane);
        const uint32_t sr2 = __shfl_sync(0xffffffffu, sb + SM_FIN + 3072 + lane * 80, lane);
        const uint32_t to  = w == 8 ? map_cta(sb, (j & 1) ^ 1) : sb;
        const uint32_t rcv = __shfl_sync(0xffffffffu, to + SM_RCV + lane * 4, lane);
        const uint32_t fin = __shfl_sync(0xffffffffu, to + SM_FULL + BAR_FIN * 8, lane);
        mbar_wait(sb + SM_FULL + (NITEM - 3) * 8);
        asm volatile("bar.sync 5, 320;" ::: "memory");
        const float4 p0 = ldsf4(src), p1 = ldsf4(src + 16);
        float sum = ((p0.x + p0.y) + (p0.z + p0.w)) + ((p1.x + p1.y) + (p1.z + p1.w));
        if (w == 8) {
            st_async32(rcv, __float_as_uint(sum), fin);
        } else {
            __nv_bfloat16* dst = reinterpret_cast<__nv_bfloat16*>(reinterpret_cast<char*>(out) + oo);
            mbar_wait(sb + SM_FULL + BAR_FIN * 8);
            if (lane == 0) TLX(154);
            sum += ldsf(rcv);
            asm volatile("bar.sync 7, 288;" ::: "memory");
            const float4 q0 = ldsf4(sr2), q1 = ldsf4(sr2 + 16), q2 = ldsf4(sr2 + 32), q3 = ldsf4(sr2 + 48);
            *dst = __float2bfloat16((((q0.x + sum) + q0.y) + (q0.z + q0.w) + ((q1.x + q1.y) + (q1.z + q1.w))) +
                                    (((q2.x + q2.y) + (q2.z + q2.w)) + ((q3.x + q3.y) + (q3.z + q3.w))));
            if (lane == 0) TLX(4);
        }
        return;
    }

    const int g = lane >> 2, t = lane & 3;
    const uint32_t in0 = sb + SM_IN0, in1 = sb + SM_IN1;
    auto xpos = [](int hh) { return (hh & 4) * 4 + (((hh >> 3) + (hh >> 2 & 1)) & 3) * 4 + (hh & 3); };
    const int ba = cta >> 5, ha = cta & 31;
    uint32_t* const ctx_dst = &gs->x[1][xpos(h)][(j * 4 + (w & 3)) * 16 + ((g ^ (w & 2)) & 3) * 4 + ((t - w) & 3)];
    uint32_t* const o_dst = &gs->x[0][xpos(ha)][ba * 64 + ((tid & 60) ^ ((ba & 1) * 16)) + ((t - g) & 3)];
    uint32_t* const lat_dst = &gs->lat[h][g & 3][j * 64 + ((w >> 1) ^ (g & 1)) * 16 + t * 4 + ((w * 2 ^ t) & 2)];
    {
        if (lane == 0) {
            const uint32_t bars = sb + (w < 4 ? SM_EMPTY : SM_FULL + NFIRST * 8) + (w & 3) * 14 * 8;
            const uint32_t cnt = w < 4 ? 8 : 1;
#pragma unroll
            for (int i = 0; i < 14; i++) mbar_init(bars + i * 8, cnt);
            if (w >= 4) {
#pragma unroll
                for (int i = 0; i < 14; i++)
                    mbar_expect_tx(bars + i * 8, (i == (IT_OP - NFIRST) % 14 && w == 4 + (IT_OP - NFIRST) / 14) ? SLOT + 1024 :
                                                 (i >= 12 && w == 7) ? (i == 12 ? 4096 : 128) : SLOT);
            }
            asm volatile("fence.mbarrier_init.release.cluster;" ::: "memory");
        }
        if (tid == 0) TL(22);
        asm volatile(BAR2 ::: "memory");
        if (lane < 16) st_rlx2(lat_dst, EMPTY, EMPTY);
        if (lane >= 16 && w < 4) st_rlx(ctx_dst, EMPTY);
        if (w >= 6) st_rlx(o_dst, EMPTY);
        if (tid < 128) sts128((tid < 64 ? in0 : in1) + ((tid >> 4) & 3) * 272 + (tid & 15) * 16, xv);
    }
    bar_consumers();
    const uint32_t tag = epoch_tag(epoch_of(cnt1));
    if (tid == 0) TL(23);

    float acc[2][2];
    tile_mma<true>(sb, IT_WQB, in0, w, lane, acc);
    if (tid == 0) TL(24);
    publish(gs->part[0][cta], w, lane, acc, tag);
    if (tid == 0) TL(6);
    tile_mma<true>(sb, IT_WQA, in1, w, lane, acc);
    publish(gs->part[1][cta], w, lane, acc, tag);
    if (tid == 0) TL(7);
    bar_consumers();

    const float SC = 0.08838834764831845f * 1.4426950408889634f;
    gather(gs->part[0][h * 4], in0, tid, tag);
    if (tid == 0) TL(8);
    tile_mma<false>(sb, IT_WUK, in0, w, lane, acc);
    if (tid == 0) TL(25);
    if (lane < 16) {
        uint32_t* q = reinterpret_cast<uint32_t*>(gs->q[g]) + (2 * j + (w >> 2)) * 1024 + h * 32 + t;
        const int ch = 2 * (w & 3);
        q[((ch) ^ (h & 7)) * 4]     = pack_bf16(acc[0][0] * SC, acc[0][1] * SC);
        q[((ch + 1) ^ (h & 7)) * 4] = pack_bf16(acc[1][0] * SC, acc[1][1] * SC);
    }
    __syncwarp();
    asm volatile("bar.arrive 3, 288;" ::: "memory");
    gather(gs->part[1][ha * 4], in1, tid, tag);
    if (tid == 0) TL(28);

    uint32_t qf[16];
#pragma unroll
    for (int c = 0; c < 8; c++) {
        qf[2 * c]     = lds32(in1 + ba * 272 + ((c ^ g) << 4) + t * 4);
        qf[2 * c + 1] = lds32(in1 + ba * 272 + 128 + ((c ^ g) << 4) + t * 4);
    }
    const uint32_t sc_w = sb + SM_SC + w * 512;
    auto k_item = [&](int item, uint32_t sc) {
        mbar_wait(sb + SM_FULL + item * 8);
        const uint32_t base = sb + slot_off(item) + ((lane & 7) + (lane & 8)) * 256 + ((lane >> 4) << 7);
        float s[4][4];
#pragma unroll
        for (int T = 0; T < 4; T++) { s[T][0] = s[T][1] = s[T][2] = s[T][3] = 0.f; }
#pragma unroll
        for (int c = 0; c < 8; c++) {
            const uint32_t a = base + ((c ^ (lane & 7)) << 4);
#pragma unroll
            for (int T = 0; T < 4; T++) {
                uint32_t r0, r1, r2, r3;
                ldsm4(a + T * 4096, r0, r1, r2, r3);
                mma16816(s[T], r0, r1, r2, r3, qf[2 * c], qf[2 * c + 1]);
            }
        }
        __syncwarp();
        if (lane == 0) mbar_arrive8(sb + SM_EMPTY + item * 8);
        if (t == (g >> 1)) {
#pragma unroll
            for (int T = 0; T < 4; T++) {
                stsf(sc + (16 * T + g) * 4,     (g & 1) ? s[T][1] : s[T][0]);
                stsf(sc + (16 * T + g + 8) * 4, (g & 1) ? s[T][3] : s[T][2]);
            }
        }
    };
    k_item(IT_K0 + w, sc_w);
    if (tid == 224) TL(10);

    {
        float s[2][2][4];
#pragma unroll
        for (int i = 0; i < 16; i++) (&s[0][0][0])[i] = 0.f;
        mbar_wait(sb + SM_FULL + IT_Q * 8);
        mbar_wait(sb + SM_FULL + (IT_Q + 1) * 8);
        if (tid == 0) TLX(96 + IT_Q);
        mbar_wait(sb + SM_FULL + (IT_C + w) * 8);
        const uint32_t cb0 = sb + slot_off(IT_C + w) + ((lane & 7) + ((lane >> 4) << 3)) * 128;
        const uint32_t cx = (((lane >> 3) & 1) ^ (lane & 7)) << 4;
        const uint32_t qr = ((lane & 7) + (lane & 8)) * 128;
        const uint32_t qx = ((lane >> 4) ^ (lane & 7)) << 4;
#pragma unroll
        for (int cb = 0; cb < 8; cb++) {
            const uint32_t qb = sb + slot_off(IT_Q + (cb >> 2)) + (cb & 3) * 4096 + qr;
#pragma unroll
            for (int k4 = 0; k4 < 4; k4++) {
                uint32_t b0, b1, b2, b3, a0, a1, a2, a3;
                ldsm4(cb0 + cb * 2048 + (cx ^ (k4 << 5)), b0, b1, b2, b3);
                ldsm4(qb + (qx ^ (k4 << 5)), a0, a1, a2, a3);
                mma16816(s[0][0], a0, a1, a2, a3, b0, b1);
                mma16816(s[0][1], a0, a1, a2, a3, b2, b3);
                ldsm4(qb + 2048 + (qx ^ (k4 << 5)), a0, a1, a2, a3);
                mma16816(s[1][0], a0, a1, a2, a3, b0, b1);
                mma16816(s[1][1], a0, a1, a2, a3, b2, b3);
            }
        }
        __syncwarp();
        if (lane == 0) { mbar_arrive(sb + SM_EMPTY + IT_Q * 8); mbar_arrive(sb + SM_EMPTY + (IT_Q + 1) * 8); }
#pragma unroll
        for (int r = 0; r < 4; r++) {
            const int mt = r >> 1, hi = (r & 1) * 2;
            float m = fmaxf(fmaxf(s[mt][0][hi], s[mt][0][hi + 1]), fmaxf(s[mt][1][hi], s[mt][1][hi + 1]));
            m = fmaxf(m, __shfl_xor_sync(0xffffffffu, m, 1));
            m = fmaxf(m, __shfl_xor_sync(0xffffffffu, m, 2));
            if (t == 0) stsf(sb + SM_MX + (8 * r + g) * 32 + w * 4, m);
        }
        bar_consumers();
        if (tid == 0) TL(11);
        uint32_t pf[2][4];
#pragma unroll
        for (int r = 0; r < 4; r++) {
            const int mt = r >> 1, hi = r & 1;
            const float4 m0 = ldsf4(sb + SM_MX + (8 * r + g) * 32), m1 = ldsf4(sb + SM_MX + (8 * r + g) * 32 + 16);
            const float m = fmaxf(fmaxf(fmaxf(m0.x, m0.y), fmaxf(m0.z, m0.w)), fmaxf(fmaxf(m1.x, m1.y), fmaxf(m1.z, m1.w)));
            const uint32_t p0 = pack_bf16(ex2(s[mt][0][2 * hi] - m), ex2(s[mt][0][2 * hi + 1] - m));
            const uint32_t p1 = pack_bf16(ex2(s[mt][1][2 * hi] - m), ex2(s[mt][1][2 * hi + 1] - m));
            pf[mt][hi] = p0; pf[mt][2 + hi] = p1;
            float l = (bf_lo(p0) + bf_hi(p0)) + (bf_lo(p1) + bf_hi(p1));
            l += __shfl_xor_sync(0xffffffffu, l, 1);
            l += __shfl_xor_sync(0xffffffffu, l, 2);
            if (t == 0) stsf(sb + SM_SUM + (8 * r + g) * 32 + w * 4, l);
        }
        sts128(sb + SM_PF + (w * 2 + 0) * 512 + lane * 16, make_uint4(pf[0][0], pf[0][1], pf[0][2], pf[0][3]));
        sts128(sb + SM_PF + (w * 2 + 1) * 512 + lane * 16, make_uint4(pf[1][0], pf[1][1], pf[1][2], pf[1][3]));
        bar_consumers();
        if (w == 0) {
            const float4 m0 = ldsf4(sb + SM_MX + lane * 32), m1 = ldsf4(sb + SM_MX + lane * 32 + 16);
            const float4 l0 = ldsf4(sb + SM_SUM + lane * 32), l1 = ldsf4(sb + SM_SUM + lane * 32 + 16);
            const float m = fmaxf(fmaxf(fmaxf(m0.x, m0.y), fmaxf(m0.z, m0.w)), fmaxf(fmaxf(m1.x, m1.y), fmaxf(m1.z, m1.w)));
            const float l = ((l0.x + l0.y) + (l0.z + l0.w)) + ((l1.x + l1.y) + (l1.z + l1.w));
            gs->stat[lane][cta] = make_float2(m, l);
        }
        float o[2][8][4];
#pragma unroll
        for (int i = 0; i < 64; i++) (&o[0][0][0])[i] = 0.f;
        const uint32_t vr = w * 2048 + ((lane & 7) + (lane & 8)) * 128;
        const uint32_t vx = ((lane >> 4) ^ (lane & 7)) << 4;
#pragma unroll
        for (int ks = 0; ks < 8; ks++) {
            const uint4 p0 = lds128(sb + SM_PF + (ks * 2 + 0) * 512 + lane * 16);
            const uint4 p1 = lds128(sb + SM_PF + (ks * 2 + 1) * 512 + lane * 16);
            const uint32_t vb = sb + slot_off(IT_C + ks) + vr;
#pragma unroll
            for (int n2 = 0; n2 < 4; n2++) {
                uint32_t b0, b1, b2, b3;
                ldsm4t(vb + (vx ^ (n2 << 5)), b0, b1, b2, b3);
                mma16816(o[0][2 * n2],     p0.x, p0.y, p0.z, p0.w, b0, b1);
                mma16816(o[0][2 * n2 + 1], p0.x, p0.y, p0.z, p0.w, b2, b3);
                mma16816(o[1][2 * n2],     p1.x, p1.y, p1.z, p1.w, b0, b1);
                mma16816(o[1][2 * n2 + 1], p1.x, p1.y, p1.z, p1.w, b2, b3);
            }
            __syncwarp();
            if (lane == 0) mbar_arrive(sb + SM_EMPTY + (IT_C + ks) * 8);
        }
        if (tid == 0) TL(12);
        mbar_wait(sb + SM_FULL + (IT_K1 + STG_AT + (w >> STG_SH)) * 8);
#pragma unroll
        for (int r = 0; r < 4; r++) {
            const int mt = r >> 1, hi = (r & 1) * 2;
            uint4* dst = gs->op[(8 * r + g) * 4 + (w >> 1)] + (cta >> 6) * 1024 + (w & 1) * 512 + (cta & 63) * 8;
#pragma unroll
            for (int u = 0; u < 2; u++) {
                uint4 v;
                v.x = pack_bf16(o[mt][4 * u][hi],     o[mt][4 * u][hi + 1]);
                v.y = pack_bf16(o[mt][4 * u + 1][hi], o[mt][4 * u + 1][hi + 1]);
                v.z = pack_bf16(o[mt][4 * u + 2][hi], o[mt][4 * u + 2][hi + 1]);
                v.w = pack_bf16(o[mt][4 * u + 3][hi], o[mt][4 * u + 3][hi + 1]);
                dst[(t + 4 * u) ^ (cta & 7)] = v;
            }
        }
        if (tid == 0) TL(29);
        asm volatile("bar.arrive 3, 288;" ::: "memory");
    }

    k_item(IT_K1 + w, sc_w + 256);
    __syncwarp();
    {
        const float4 s = ldsf4(sc_w + lane * 16);
        float m = fmaxf(fmaxf(s.x, s.y), fmaxf(s.z, s.w));
#pragma unroll
        for (int d = 1; d < 32; d <<= 1) m = fmaxf(m, __shfl_xor_sync(0xffffffffu, m, d));
        if (lane == 0) stsf(sb + SM_ML + w * 4, m);
        bar_consumers();
        const float4 m0 = ldsf4(sb + SM_ML), m1 = ldsf4(sb + SM_ML + 16);
        m = fmaxf(fmaxf(fmaxf(m0.x, m0.y), fmaxf(m0.z, m0.w)), fmaxf(fmaxf(m1.x, m1.y), fmaxf(m1.z, m1.w))) * SC;
        const uint32_t p0 = pack_bf16(ex2(fmaf(s.x, SC, -m)), ex2(fmaf(s.y, SC, -m)));
        const uint32_t p1 = pack_bf16(ex2(fmaf(s.z, SC, -m)), ex2(fmaf(s.w, SC, -m)));
        float l = (bf_lo(p0) + bf_hi(p0)) + (bf_lo(p1) + bf_hi(p1));
#pragma unroll
        for (int d = 1; d < 32; d <<= 1) l += __shfl_xor_sync(0xffffffffu, l, d);
        if (lane == 0) stsf(sb + SM_ML + 32 + w * 4, l);
        sts64(sb + SM_PA + w * 256 + lane * 8, p0, p1);
        __syncwarp();
    }
    if (tid == 224) TL(14);

    float oa[4][4];
#pragma unroll
    for (int i = 0; i < 16; i++) (&oa[0][0])[i] = 0.f;
    auto v_item = [&](int item, uint32_t pa) {
        uint32_t p[8];
#pragma unroll
        for (int i = 0; i < 8; i++) p[i] = lds32(pa + i * 16 + t * 4);
        mbar_wait(sb + SM_FULL + item * 8);
        const uint32_t base = sb + slot_off(item) + ((lane & 7) + ((lane >> 4) << 3)) * 256 + ((lane & 8) << 4);
#pragma unroll
        for (int c = 0; c < 8; c++) {
            const uint32_t a = base + ((c ^ (lane & 7)) << 4);
            const uint32_t mask = ((c == (g ^ (2 * t))) ? 0x0000ffffu : 0u) | ((c == (g ^ (2 * t + 1))) ? 0xffff0000u : 0u);
#pragma unroll
            for (int T = 0; T < 4; T++) {
                uint32_t r0, r1, r2, r3;
                ldsm4t(a + T * 4096, r0, r1, r2, r3);
                mma16816(oa[T], r0, r1, r2, r3, p[2 * T] & mask, p[2 * T + 1] & mask);
            }
        }
        __syncwarp();
        if (lane == 0) mbar_arrive8(sb + SM_EMPTY + item * 8);
    };
    v_item(IT_V0 + w, sb + SM_PA + w * 256);
    if (tid == 224) TL(15);

    mbar_wait(sb + SM_FULL + IT_OP * 8);
    if (tid == 0) TLX(96 + IT_OP);
    if (w < 4) {
        const float2 st = ldsf2(sb + SM_MX + tid * 8);
        float m = st.x;
#pragma unroll
        for (int d = 1; d < 32; d <<= 1) m = fmaxf(m, __shfl_xor_sync(0xffffffffu, m, d));
        const uint32_t wb = pack_bf16(ex2(st.x - m), 0.f);
        float l = bf_lo(wb) * st.y;
#pragma unroll
        for (int d = 1; d < 32; d <<= 1) l += __shfl_xor_sync(0xffffffffu, l, d);
#pragma unroll
        for (int bb = 0; bb < 4; bb++) sts16(in0 + bb * 272 + tid * 2, bb == w ? (uint16_t)wb : (uint16_t)0);
        if (lane == 0) stsf(sb + SM_ML + 64 + w * 4, 1.f / l);
    }
    bar_consumers();
    tile_mma<true>(sb, IT_OP, in0, w, lane, acc);
    if (lane < 16) {
        const float inv = ldsf(sb + SM_ML + 64 + g * 4);
        const uint32_t v0 = pack_bf16(acc[0][0] * inv, acc[0][1] * inv), v1 = pack_bf16(acc[1][0] * inv, acc[1][1] * inv);
        st_rlx2(lat_dst, (t & 1) ? v1 : v0, (t & 1) ? v0 : v1);
    }
    if (tid == 0) TL(19);

    {
        const float4 l0 = ldsf4(sb + SM_ML + 32), l1 = ldsf4(sb + SM_ML + 48);
        const float inv = 1.f / (((l0.x + l0.y) + (l0.z + l0.w)) + ((l1.x + l1.y) + (l1.z + l1.w)));
        v_item(IT_V1 + w, sb + SM_PA + w * 256 + 128);
        const uint32_t so = sb + SM_PF + w * 512 + (16 * t + g) * 4;
        stsf(so,       (oa[0][0] + oa[1][0]) + (oa[2][0] + oa[3][0]));
        stsf(so + 32,  (oa[0][1] + oa[1][1]) + (oa[2][1] + oa[3][1]));
        stsf(so + 256, (oa[0][2] + oa[1][2]) + (oa[2][2] + oa[3][2]));
        stsf(so + 288, (oa[0][3] + oa[1][3]) + (oa[2][3] + oa[3][3]));
        if (w < 6) {
            asm volatile("bar.arrive 1, 256;" ::: "memory");
        } else {
            bar_consumers();
            float x = 0.f, y = 0.f;
#pragma unroll
            for (int i = 0; i < 8; i++) {
                const float2 v = ldsf2(sb + SM_PF + i * 512 + (tid & 63) * 8);
                x += v.x; y += v.y;
            }
            st_rlx(o_dst, pack_bf16(x * inv, y * inv));
            if (lane == 0) {
                const uint32_t to = map_cta(sb, w & 1);
                st_async32(to + SM_RCV + 128 + (j & 1) * 4, 0u, to + SM_FULL + BAR_PEER * 8);
            }
            if (tid == 224) TL(17);
        }
    }

    if (w < 4) {
        const uint32_t lo = (g & 3) * 1024 + (g >> 2) * 512 + (g & 1) * 64 + t * 16;
        const int wd = ((lane >> 2 & 2) + (lane >> 4)) ^ (lane >> 1 & 3);
        const uint32_t base = sb + ((lane & 6) * 4 + wd * 2 + (lane & 1)) * 64 + (((w ^ wd) & 3) << 4);
        const uint64_t dst = __shfl_sync(0xffffffffu, (unsigned long long)ctx_dst, lane);
        mbar_wait(sb + SM_FULL + BAR_LAT * 8);
        uint4 a[8];
#pragma unroll
        for (int i = 0; i < 8; i++) a[i] = lds128(sb + SM_LAT + (lo ^ (i * 64)));
        int it = 0;
        while (refetch<0>(a, lane, [&](int i) { return (const char*)gs->lat[h] + (lo ^ (i * 64)); }))
            if (++it > SPIN_LIMIT) __trap();
        float v0 = 0.f, v1 = 0.f;
#pragma unroll
        for (int i = 0; i < 2; i++) {
            float c[4][4];
#pragma unroll
            for (int k = 0; k < 16; k++) (&c[0][0])[k] = 0.f;
            c[0][0] = v0; c[0][1] = v1;
            mbar_wait(sb + SM_FULL + (IT_WUV + i) * 8);
#pragma unroll
            for (int kk = 0; kk < 8; kk++) {
                uint32_t r0, r1, r2, r3;
                ldsm4t(base + slot_off(IT_WUV + i) + kk * 2048, r0, r1, r2, r3);
                mma16816(c[2 * (kk & 1)],     a[kk].x, a[kk].y, a[kk].z, a[kk].w, r0, r1);
                mma16816(c[2 * (kk & 1) + 1], a[kk].x, a[kk].y, a[kk].z, a[kk].w, r2, r3);
            }
            v0 = (c[0][0] + c[1][2]) + (c[2][0] + c[3][2]);
            v1 = (c[0][1] + c[1][3]) + (c[2][1] + c[3][3]);
            if (i == 0) { v0 = __shfl_xor_sync(0xffffffffu, v0, 16); v1 = __shfl_xor_sync(0xffffffffu, v1, 16); }
        }
        st_rlx_if(dst, pack_bf16(v0, v1), lane >= 16);
        if (tid == 0) TL(16);
    }

    {
        const bool isB = slice >= 32;
        const int r = j & 1;
        const uint32_t xl = isB ? t * 64 + (((g ^ (t & 2)) & 3) << 4) : (g & 3) * 256 + ((g & 1) * 4 + t) * 16;
        const uint32_t cs = isB ? 256 : 64;
        const uint32_t xo = r * 8192 + (w >> 1) * 1024 + (w & 1) * 2 * cs + xl, xz = (1 - r) * 12288 + w * 1024 + (g >> 2) * 2 * cs + xl;
        auto xoff = [&](int i) { return i < 6 ? (i >> 1) * 4096 + (xo ^ ((i & 1) * cs)) : xz ^ ((i & 1) * cs); };
        const char* src = (const char*)gs->x[slice >> 5][r * 12];
        uint32_t off[2], ofz[2];
#pragma unroll
        for (int u = 0; u < 2; u++) {
            const int tt = (lane & 7) >> 1;
            const int row = 8 * tt + 2 * ((2 * u + (lane >> 4) + tt) & 3) + (lane & 1);
            off[u] = sb + w * 2048 + row * 32 + ((((lane >> 3) ^ (row >> 2)) & 1) << 4);
            ofz[u] = __shfl_sync(0xffffffffu, sb + (w < 4 ? slot_off(IT_WO + 3) : slot_off(IT_W2)) + (w & 3) * 4096 + (lane & 8) * 256 +
                                              row * 32 + (((r ^ (row >> 2)) & 1) << 4), lane);
        }
        const uint32_t fin = __shfl_sync(0xffffffffu, sb + SM_FIN + (t & 1) * 768 + g * 48 + ((w ^ (t & 1)) << 2), lane);
        const uint32_t fi2 = __shfl_sync(0xffffffffu, sb + SM_FIN + 3072 + (t & 1) * 1280 + g * 80 + (((w * 2 + (t >> 1)) ^ (t * 2 & 2)) << 2), lane);
        uint32_t a[2][4][4];
        uint4 x[8];
        float c[4][4];
        auto load_w = [&](int i) {
            mbar_wait(sb + SM_FULL + (i < 3 ? IT_WO + i : w < 4 ? IT_WO + 3 : IT_W2) * 8);
#pragma unroll
            for (int q = 0; q < 4; q++)
                ldsm4t((i < 3 ? slot_off(IT_WO + i) + off[q & 1] : ofz[q & 1]) + (q >> 1) * 1024,
                       a[i & 1][q][0], a[i & 1][q][1], a[i & 1][q][2], a[i & 1][q][3]);
        };
        auto mma_w = [&](int i) {
#pragma unroll
            for (int q = 0; q < 4; q++) {
                if (i == 0 || i == 3) c[q][0] = c[q][1] = c[q][2] = c[q][3] = 0.f;
                mma16816(c[q], a[i & 1][q][0], a[i & 1][q][1], a[i & 1][q][2], a[i & 1][q][3],
                         (q & 1) ? x[2 * i + (q >> 1)].z : x[2 * i + (q >> 1)].x, (q & 1) ? x[2 * i + (q >> 1)].w : x[2 * i + (q >> 1)].y);
            }
        };
        load_w(0); load_w(1);
        mbar_wait(sb + SM_FULL + BAR_X * 8);
        if (tid == 224) TLX(20);
#pragma unroll
        for (int i = 0; i < 8; i++) x[i] = lds128_if(sb + slot_off(IT_X) + xoff(i), i >= 6 || lane < 16);
        int it = 0;
        while (true) {
            mma_w(0); mma_w(1);
            if (!refetch<6>(x, lane, [&](int i) { return src + xoff(i); })) break;
            if (++it > SPIN_LIMIT) __trap();
        }
        load_w(2);
        mma_w(2);
#pragma unroll
        for (int e = 0; e < 4; e++) stsf_if(fin + (e >> 1) * 1536 + (e & 1) * 384, (c[0][e] + c[1][e]) + (c[2][e] + c[3][e]), t < 2);
        asm volatile("bar.arrive 5, 320;" ::: "memory");
        if (tid == 0) TLX(18);
        load_w(3);
        mma_w(3);
#pragma unroll
        for (int e = 0; e < 2; e++) {
            const float lo = (c[0][e] + c[1][e]) + (c[2][e] + c[3][e]), hi = (c[0][e + 2] + c[1][e + 2]) + (c[2][e + 2] + c[3][e + 2]);
            stsf(fi2 + e * 640, t < 2 ? lo : hi);
        }
        asm volatile("bar.arrive 7, 288;" ::: "memory");
        if (tid == 224) TLX(26);
    }
}

typedef CUresult (*EncodeTiledFn)(CUtensorMap*, CUtensorMapDataType, cuuint32_t, void*, const cuuint64_t*,
                                  const cuuint64_t*, const cuuint32_t*, const cuuint32_t*, CUtensorMapInterleave,
                                  CUtensorMapSwizzle, CUtensorMapL2promotion, CUtensorMapFloatOOBfill);

void encode_map(EncodeTiledFn enc, CUtensorMap* tm, const void* p, cuuint64_t cols, cuuint64_t rows,
                cuuint32_t brows, cuuint32_t bblk) {
    cuuint64_t dims[3] = {64, rows, cols / 64};
    cuuint64_t strides[2] = {cols * 2, 128};
    cuuint32_t box[3] = {64, brows, bblk};
    cuuint32_t es[3] = {1, 1, 1};
    enc(tm, CU_TENSOR_MAP_DATA_TYPE_BFLOAT16, 3, const_cast<void*>(p), dims, strides, box, es,
        CU_TENSOR_MAP_INTERLEAVE_NONE, CU_TENSOR_MAP_SWIZZLE_128B, CU_TENSOR_MAP_L2_PROMOTION_L2_256B,
        CU_TENSOR_MAP_FLOAT_OOB_FILL_NONE);
}

void encode_slice_map(EncodeTiledFn enc, CUtensorMap* tm, const void* p, cuuint64_t cols, cuuint64_t rows, cuuint32_t bcols) {
    cuuint64_t dims[3] = {cols, 256, rows / 256};
    cuuint64_t strides[2] = {cols * 2, cols * 512};
    cuuint32_t box[3] = {bcols, 256, 32 / bcols};
    cuuint32_t es[3] = {1, 1, 1};
    enc(tm, CU_TENSOR_MAP_DATA_TYPE_BFLOAT16, 3, const_cast<void*>(p), dims, strides, box, es, CU_TENSOR_MAP_INTERLEAVE_NONE,
        bcols == 16 ? CU_TENSOR_MAP_SWIZZLE_32B : CU_TENSOR_MAP_SWIZZLE_64B, CU_TENSOR_MAP_L2_PROMOTION_L2_128B,
        CU_TENSOR_MAP_FLOAT_OOB_FILL_NONE);
}

}

extern "C" void kernel_launch(void* const* d_in, const int* in_sizes, int n_in, void* d_out, int out_size) {
    (void)in_sizes; (void)n_in; (void)out_size;
    static EncodeTiledFn enc = nullptr;
    static Scratch* gs = nullptr;
    if (!enc) {
        cudaGetSymbolAddress((void**)&gs, g_scratch);
        void* fn = nullptr;
        cudaDriverEntryPointQueryResult qr;
        cudaGetDriverEntryPoint("cuTensorMapEncodeTiled", &fn, cudaEnableDefault, &qr);
        enc = (EncodeTiledFn)fn;
        cudaFuncSetAttribute(fused_decode_kernel, cudaFuncAttributeMaxDynamicSharedMemorySize, SM_END);
    }
    Maps maps;
    encode_map(enc, &maps.wqB, d_in[7], 4096, 512, 64, 2);
    encode_map(enc, &maps.wqA, d_in[3], 4096, 512, 64, 2);
    encode_map(enc, &maps.wuk, d_in[8], 4096, 512, 64, 2);
    encode_slice_map(enc, &maps.wuv, d_in[9], 4096, 512, 32);
    encode_slice_map(enc, &maps.woB, d_in[10], 512, 4096, 16);
    encode_slice_map(enc, &maps.woA, d_in[4], 512, 4096, 16);
    encode_map(enc, &maps.ckv, d_in[6], 512, 16384, 16, 8);
    fused_decode_kernel<<<NCTA, NTHR, SM_END>>>((const __nv_bfloat16*)d_in[0], (const __nv_bfloat16*)d_in[5],
                                                (const __nv_bfloat16*)d_in[1] + 3072 * 128, (const __nv_bfloat16*)d_in[2] + 3072 * 128,
                                                (__nv_bfloat16*)d_out, gs, maps);
}
```

```cpp
#include <cuda_runtime.h>
#include <cuda_bf16.h>
#include <cuda.h>
#include <stdint.h>

namespace {

constexpr int NCTA   = 128;
constexpr int NSLOT  = 13;
constexpr int SLOT   = 16384;
constexpr int NITEM  = 56;
#define INFLIGHT 4
#define ADAPT
#define PACE 646
#define OFFS 450
#define STAG 0
#define OWAIT 0
#define FINMODE 1
#define FINDELAY 0
#define NFIRST 2
#define STARTER 256
#define CTXWAIT 0
#define LATAT 46
#define TAPER 250
#define TAPER_AT 49
#define TAPER_N 1
#define STG_AT 2
#define STG_SH 1
#define OPN 8
#define OPGAP 200
#define QN 2
#define QGAP 0
#define PFSTARTER 288
#define PFMODE 0
#define GLEAD 150
#define AEARLY 0
#define BEARLY 0
#define DRAIN_AT 99
#define DRAIN 2
#define AWAIT 0
#define NPOLL 4
#define FGAP 170
#define FDEL 0
#define LSTAR 178172182000ll
#define WINS 10243800
#define GAIN 11
#define ANCH 0
constexpr int NTHR   = 352;
#define BAR2 "bar.sync 2, 352;"

constexpr int IT_WQB = 0, IT_WQA = 2, IT_WUK = 4, IT_K0 = 6, IT_Q = 14, IT_C = 16, IT_K1 = 24, IT_V0 = 32,
              IT_OP = 40, IT_V1 = 42, IT_WUV = 50, IT_WO = 52;
constexpr int IT_X = 56;
constexpr int IT_W2 = 58;
constexpr int BAR_LAT = 56, BAR_FIN = 57, BAR_X = 59, BAR_PEER = 60;

constexpr int SM_FULL  = NSLOT * SLOT;
constexpr int SM_EMPTY = SM_FULL + 512;
constexpr int SM_IN0   = SM_EMPTY + 512;
constexpr int SM_IN1   = SM_IN0 + 1088;
constexpr int SM_SC    = SM_IN1 + 1088;
constexpr int SM_PA    = SM_SC + 4096;
constexpr int SM_PF    = SM_PA + 2048;
constexpr int SM_MX    = SM_PF + 8192;
constexpr int SM_ML    = SM_MX + 1024;
constexpr int SM_RCV   = SM_ML + 128;
constexpr int SM_PACE  = SM_RCV + 144;
constexpr int SM_END   = SM_PACE + 32;
constexpr int SM_LAT   = SM_PF + 4096;
constexpr int SM_FIN   = SM_SC;
constexpr int SM_SUM   = SM_IN0;
static_assert(SM_END <= 232448, "smem");

struct Maps { CUtensorMap wqB, wqA, wuk, wuv, woA, woB, ckv; };

struct Scratch {
    unsigned cnt[32];
    unsigned late[32];
    float    part[2][NCTA][512];
    uint32_t x[2][32][256];
    uint32_t lat[32][4][256];
    uint4    q[4][2048];
    uint4    op[NCTA][2048];
    float2   stat[32][128];
};
__device__ __align__(128) Scratch g_scratch;
#define TLX(i) do {} while (0)
#define TL(i) do {} while (0)

constexpr int SPIN_LIMIT = 1 << 22;

__device__ __forceinline__ uint32_t smem_u32(const void* p) { return (uint32_t)__cvta_generic_to_shared(p); }
__device__ __forceinline__ void mbar_init(uint32_t bar, uint32_t cnt) {
    asm volatile("mbarrier.init.shared::cta.b64 [%0], %1;" ::"r"(bar), "r"(cnt) : "memory");
}
__device__ __forceinline__ void mbar_expect_tx(uint32_t bar, uint32_t bytes) {
    asm volatile("mbarrier.arrive.expect_tx.shared::cta.b64 _, [%0], %1;" ::"r"(bar), "r"(bytes) : "memory");
}
__device__ __forceinline__ void mbar_arrive(uint32_t bar) {
    asm volatile("mbarrier.arrive.shared::cta.b64 _, [%0];" ::"r"(bar) : "memory");
}
__device__ __forceinline__ void mbar_arrive8(uint32_t bar) {
    asm volatile("mbarrier.arrive.shared::cta.b64 _, [%0], 8;" ::"r"(bar) : "memory");
}
__device__ __forceinline__ void mbar_wait(uint32_t bar) {
    uint32_t done;
    int it = 0;
    do {
        asm volatile("{\n.reg .pred p;\nmbarrier.try_wait.parity.shared::cta.b64 p, [%1], 0;\nselp.u32 %0, 1, 0, p;\n}"
                     : "=r"(done) : "r"(bar) : "memory");
        if (++it > SPIN_LIMIT) __trap();
    } while (!done);
}
__device__ __forceinline__ uint32_t map_cta(uint32_t a, uint32_t rank) {
    uint32_t r; asm("mapa.shared::cluster.u32 %0, %1, %2;" : "=r"(r) : "r"(a), "r"(rank)); return r;
}
__device__ __forceinline__ void st_async32(uint32_t a, uint32_t v, uint32_t bar) {
    asm volatile("st.async.shared::cluster.mbarrier::complete_tx::bytes.b32 [%0], %1, [%2];" ::"r"(a), "r"(v), "r"(bar) : "memory");
}
__device__ __forceinline__ uint64_t evict_first() {
    uint64_t pol; asm volatile("createpolicy.fractional.L2::evict_first.b64 %0, 1.0;" : "=l"(pol)); return pol;
}
__device__ __forceinline__ void bulk_load(uint32_t dst, const void* src, uint32_t bytes, uint32_t bar, uint64_t pol) {
    asm volatile("cp.async.bulk.shared::cluster.global.mbarrier::complete_tx::bytes.L2::cache_hint [%0], [%1], %2, [%3], %4;"
                 ::"r"(dst), "l"(src), "r"(bytes), "r"(bar), "l"(pol) : "memory");
}
__device__ __forceinline__ void bulk_load_nohint(uint32_t dst, const void* src, uint32_t bytes, uint32_t bar) {
    asm volatile("cp.async.bulk.shared::cluster.global.mbarrier::complete_tx::bytes [%0], [%1], %2, [%3];"
                 ::"r"(dst), "l"(src), "r"(bytes), "r"(bar) : "memory");
}
__device__ __forceinline__ void bulk_load_pair(uint32_t dst, const void* src, uint32_t bytes, uint32_t bar) {
    asm volatile("cp.async.bulk.shared::cluster.global.mbarrier::complete_tx::bytes.multicast::cluster [%0], [%1], %2, [%3], %4;"
                 ::"r"(dst), "l"(src), "r"(bytes), "r"(bar), "h"((uint16_t)3) : "memory");
}
__device__ __forceinline__ void tma3d(uint32_t dst, const CUtensorMap* tm, int c0, int c1, int c2, uint32_t bar, uint64_t pol) {
    asm volatile("cp.async.bulk.tensor.3d.shared::cluster.global.mbarrier::complete_tx::bytes.L2::cache_hint [%0], [%1, {%3, %4, %5}], [%2], %6;"
                 ::"r"(dst), "l"(tm), "r"(bar), "r"(c0), "r"(c1), "r"(c2), "l"(pol) : "memory");
}
__device__ __forceinline__ void tma3d_pair(uint32_t dst, const CUtensorMap* tm, int c0, int c1, int c2, uint32_t bar, uint64_t pol) {
    asm volatile("cp.async.bulk.tensor.3d.shared::cluster.global.mbarrier::complete_tx::bytes.multicast::cluster.L2::cache_hint [%0], [%1, {%3, %4, %5}], [%2], %7, %6;"
                 ::"r"(dst), "l"(tm), "r"(bar), "r"(c0), "r"(c1), "r"(c2), "l"(pol), "h"((uint16_t)3) : "memory");
}
__device__ __forceinline__ void ldsm4(uint32_t a, uint32_t& r0, uint32_t& r1, uint32_t& r2, uint32_t& r3) {
    asm volatile("ldmatrix.sync.aligned.m8n8.x4.shared.b16 {%0,%1,%2,%3}, [%4];"
                 : "=r"(r0), "=r"(r1), "=r"(r2), "=r"(r3) : "r"(a) : "memory");
}
__device__ __forceinline__ void ldsm4t(uint32_t a, uint32_t& r0, uint32_t& r1, uint32_t& r2, uint32_t& r3) {
    asm volatile("ldmatrix.sync.aligned.m8n8.x4.trans.shared.b16 {%0,%1,%2,%3}, [%4];"
                 : "=r"(r0), "=r"(r1), "=r"(r2), "=r"(r3) : "r"(a) : "memory");
}
__device__ __forceinline__ void mma16816(float (&c)[4], uint32_t a0, uint32_t a1, uint32_t a2, uint32_t a3,
                                         uint32_t b0, uint32_t b1) {
    asm volatile("mma.sync.aligned.m16n8k16.row.col.f32.bf16.bf16.f32 {%0,%1,%2,%3}, {%4,%5,%6,%7}, {%8,%9}, {%0,%1,%2,%3};"
                 : "+f"(c[0]), "+f"(c[1]), "+f"(c[2]), "+f"(c[3])
                 : "r"(a0), "r"(a1), "r"(a2), "r"(a3), "r"(b0), "r"(b1));
}
__device__ __forceinline__ uint32_t lds32(uint32_t a) {
    uint32_t v; asm volatile("ld.shared.b32 %0, [%1];" : "=r"(v) : "r"(a) : "memory"); return v;
}
__device__ __forceinline__ float ldsf(uint32_t a) {
    float v; asm volatile("ld.shared.f32 %0, [%1];" : "=f"(v) : "r"(a) : "memory"); return v;
}
__device__ __forceinline__ float2 ldsf2(uint32_t a) {
    float2 v; asm volatile("ld.shared.v2.f32 {%0,%1}, [%2];" : "=f"(v.x), "=f"(v.y) : "r"(a) : "memory"); return v;
}
__device__ __forceinline__ float4 ldsf4(uint32_t a) {
    float4 v; asm volatile("ld.shared.v4.f32 {%0,%1,%2,%3}, [%4];" : "=f"(v.x), "=f"(v.y), "=f"(v.z), "=f"(v.w) : "r"(a) : "memory"); return v;
}
__device__ __forceinline__ uint4 lds128(uint32_t a) {
    uint4 v; asm volatile("ld.shared.v4.b32 {%0,%1,%2,%3}, [%4];" : "=r"(v.x), "=r"(v.y), "=r"(v.z), "=r"(v.w) : "r"(a) : "memory"); return v;
}
__device__ __forceinline__ uint4 lds128_if(uint32_t a, bool on) {
    uint4 v;
    asm volatile("{\n.reg .pred p;\nsetp.ne.u32 p, %5, 0;\n@p ld.shared.v4.b32 {%0,%1,%2,%3}, [%4];\n}"
                 : "=r"(v.x), "=r"(v.y), "=r"(v.z), "=r"(v.w) : "r"(a), "r"((uint32_t)on) : "memory");
    return v;
}
__device__ __forceinline__ void stsf_if(uint32_t a, float v, bool on) {
    asm volatile("{\n.reg .pred p;\nsetp.ne.u32 p, %2, 0;\n@p st.shared.f32 [%0], %1;\n}" ::"r"(a), "f"(v), "r"((uint32_t)on) : "memory");
}
__device__ __forceinline__ void sts16(uint32_t a, uint16_t v) { asm volatile("st.shared.b16 [%0], %1;" ::"r"(a), "h"(v) : "memory"); }
__device__ __forceinline__ void sts32(uint32_t a, uint32_t v) { asm volatile("st.shared.b32 [%0], %1;" ::"r"(a), "r"(v) : "memory"); }
__device__ __forceinline__ void stsf(uint32_t a, float v) { asm volatile("st.shared.f32 [%0], %1;" ::"r"(a), "f"(v) : "memory"); }
__device__ __forceinline__ void sts64(uint32_t a, uint32_t x, uint32_t y) {
    asm volatile("st.shared.v2.b32 [%0], {%1,%2};" ::"r"(a), "r"(x), "r"(y) : "memory");
}
__device__ __forceinline__ void sts128(uint32_t a, uint4 v) {
    asm volatile("st.shared.v4.b32 [%0], {%1,%2,%3,%4};" ::"r"(a), "r"(v.x), "r"(v.y), "r"(v.z), "r"(v.w) : "memory");
}
__device__ __forceinline__ uint32_t pack_bf16(float lo, float hi) {
    uint32_t r; asm("cvt.rn.bf16x2.f32 %0, %1, %2;" : "=r"(r) : "f"(hi), "f"(lo)); return r;
}
__device__ __forceinline__ float bf_lo(uint32_t v) { return __uint_as_float(v << 16); }
__device__ __forceinline__ float bf_hi(uint32_t v) { return __uint_as_float(v & 0xffff0000u); }
__device__ __forceinline__ float ex2(float x) { float y; asm("ex2.approx.ftz.f32 %0, %1;" : "=f"(y) : "f"(x)); return y; }
__device__ __forceinline__ uint32_t timer_ns() { uint32_t t; asm volatile("mov.u32 %0, %%globaltimer_lo;" : "=r"(t)); return t; }
__device__ __forceinline__ void bar_consumers() { asm volatile("bar.sync 1, 256;" ::: "memory"); }

__device__ __forceinline__ uint32_t tagf(float v, uint32_t tag) { return (__float_as_uint(v) & 0xffffff00u) | tag; }
__device__ __forceinline__ uint2 ld_rlx2(const float* p) {
    uint2 v; asm volatile("ld.relaxed.gpu.global.v2.b32 {%0,%1}, [%2];" : "=r"(v.x), "=r"(v.y) : "l"(p) : "memory"); return v;
}
__device__ __forceinline__ float untag(uint32_t v) { return __uint_as_float(v & 0xffffff00u); }

__device__ __forceinline__ uint32_t slot_off(int item) { return (uint32_t)(item % NSLOT) * SLOT; }

template <bool TRANS, bool RELEASE = true>
__device__ __forceinline__ void tile_mma(uint32_t sb, int item, uint32_t in, int w, int lane, float (&acc)[2][2]) {
    const int g = lane >> 2, t = lane & 3;
    float c[4][4];
#pragma unroll
    for (int i = 0; i < 16; i++) (&c[0][0])[i] = 0.f;
    uint32_t a[16];
    const uint32_t ia = in + (g & 3) * 272 + t * 4;
#pragma unroll
    for (int i = 0; i < 16; i++) a[i] = lds32(ia + i * 16);
    const uint32_t s0 = sb + slot_off(item), s1 = sb + slot_off(item + 1);
    if (TRANS) {
        const int r = (lane & 7) + (lane & 8);
        const int ch = 2 * (w & 3) + (lane >> 4);
        const uint32_t off = (w >> 2) * 8192 + r * 128 + ((ch ^ (lane & 7)) << 4);
#pragma unroll
        for (int kk = 0; kk < 8; kk++) {
            if ((kk & 3) == 0) mbar_wait(sb + SM_FULL + (item + (kk >> 2)) * 8);
            uint32_t r0, r1, r2, r3;
            ldsm4t(((kk >> 2) ? s1 : s0) + off + (kk & 3) * 2048, r0, r1, r2, r3);
            mma16816(c[2 * (kk & 1)],     a[2 * kk], 0u, a[2 * kk + 1], 0u, r0, r1);
            mma16816(c[2 * (kk & 1) + 1], a[2 * kk], 0u, a[2 * kk + 1], 0u, r2, r3);
        }
    } else {
        mbar_wait(sb + SM_FULL + (item + (w >> 2)) * 8);
        const int r = 16 * (w & 3) + (lane & 7) + ((lane >> 4) << 3);
        const uint32_t base = ((w >> 2) ? s1 : s0) + r * 128 + ((((lane >> 3) & 1) ^ (lane & 7)) << 4);
#pragma unroll
        for (int kk = 0; kk < 8; kk++) {
            uint32_t r0, r1, r2, r3;
            ldsm4((base ^ ((kk & 3) << 5)) + (kk >> 2) * 8192, r0, r1, r2, r3);
            mma16816(c[2 * (kk & 1)],     a[2 * kk], 0u, a[2 * kk + 1], 0u, r0, r1);
            mma16816(c[2 * (kk & 1) + 1], a[2 * kk], 0u, a[2 * kk + 1], 0u, r2, r3);
        }
    }
    if (RELEASE) {
        __syncwarp();
        if (lane == 0) {
            mbar_arrive(sb + SM_EMPTY + item * 8);
            mbar_arrive(sb + SM_EMPTY + (item + 1) * 8);
        }
    }
    acc[0][0] = c[0][0] + c[2][0]; acc[0][1] = c[0][1] + c[2][1];
    acc[1][0] = c[1][0] + c[3][0]; acc[1][1] = c[1][1] + c[3][1];
}

__device__ __forceinline__ void publish(float* dst, int w, int lane, const float (&acc)[2][2], uint32_t tag) {
    if (lane < 16)
        asm volatile("st.relaxed.gpu.global.v4.b32 [%0], {%1,%2,%3,%4};" ::"l"(dst + w * 64 + lane * 4),
                     "r"(tagf(acc[0][0], tag)), "r"(tagf(acc[0][1], tag)), "r"(tagf(acc[1][0], tag)), "r"(tagf(acc[1][1], tag)) : "memory");
}

__device__ __forceinline__ void gather(const float* part, uint32_t in, int tid, uint32_t tag) {
    const float* p = part + tid * 2;
    uint2 v0, v1, v2, v3;
    int it = 0;
    while (true) {
        v0 = ld_rlx2(p); v1 = ld_rlx2(p + 512); v2 = ld_rlx2(p + 1024); v3 = ld_rlx2(p + 1536);
        uint32_t bad = ((v0.x ^ tag) | (v0.y ^ tag) | (v1.x ^ tag) | (v1.y ^ tag) |
                        (v2.x ^ tag) | (v2.y ^ tag) | (v3.x ^ tag) | (v3.y ^ tag)) & 0xffu;
        if (__all_sync(0xffffffffu, bad == 0)) break;
        if (++it > SPIN_LIMIT) __trap();
    }
    float x = (untag(v0.x) + untag(v1.x)) + (untag(v2.x) + untag(v3.x));
    float y = (untag(v0.y) + untag(v1.y)) + (untag(v2.y) + untag(v3.y));
    sts32(in + ((tid >> 3) & 3) * 272 + (tid >> 5) * 32 + (tid & 1) * 16 + (tid & 6) * 2, pack_bf16(x, y));
    bar_consumers();
}

constexpr uint32_t EMPTY = 0xffffffffu;
__device__ __forceinline__ void st_rlx(uint32_t* p, uint32_t v) {
    asm volatile("st.relaxed.gpu.global.b32 [%0], %1;" ::"l"(p), "r"(v) : "memory");
}
__device__ __forceinline__ void st_rlx_if(uint64_t p, uint32_t v, bool on) {
    asm volatile("{\n.reg .pred p;\nsetp.ne.u32 p, %2, 0;\n@p st.relaxed.gpu.global.b32 [%0], %1;\n}" ::"l"(p), "r"(v), "r"((uint32_t)on) : "memory");
}
__device__ __forceinline__ void st_rlx2(uint32_t* p, uint32_t v0, uint32_t v1) {
    asm volatile("st.relaxed.gpu.global.v2.b32 [%0], {%1,%2};" ::"l"(p), "r"(v0), "r"(v1) : "memory");
}
__device__ __forceinline__ void ld_rlx4_if(uint4& v, const void* p, bool need) {
    asm volatile("{\n.reg .pred p;\nsetp.ne.u32 p, %5, 0;\n@p ld.relaxed.gpu.global.v4.b32 {%0,%1,%2,%3}, [%4];\n}"
                 : "+r"(v.x), "+r"(v.y), "+r"(v.z), "+r"(v.w) : "l"(p), "r"((uint32_t)need) : "memory");
}

template <int HALF, class F>
__device__ __forceinline__ bool refetch(uint4 (&x)[8], int lane, F addr) {
    uint32_t m[8], m0 = 0, m1 = 0;
#pragma unroll
    for (int i = 0; i < 8; i++) {
        m[i] = max(max(x[i].x, x[i].y), max(x[i].z, x[i].w));
        if (i < HALF) m0 = max(m0, m[i]); else m1 = max(m1, m[i]);
    }
    if (!__any_sync(0xffffffffu, (m0 == EMPTY && lane < 16) || m1 == EMPTY)) return false;
#pragma unroll
    for (int i = 0; i < 8; i++) ld_rlx4_if(x[i], addr(i), m[i] == EMPTY && (i >= HALF || lane < 16));
    return true;
}

__device__ __forceinline__ unsigned read_counter(const unsigned* cnt) {
    unsigned v;
    asm volatile("ld.relaxed.gpu.global.u32 %0, [%1];" : "=r"(v) : "l"(cnt) : "memory");
    return v;
}
__device__ __forceinline__ unsigned epoch_of(unsigned cnt) {
    asm volatile("" : "+r"(cnt) :: "memory");
    return cnt / NCTA + 1;
}
__device__ __forceinline__ uint32_t epoch_tag(unsigned epoch) { return (epoch & 0x7fu) | 0x80u; }

__device__ __forceinline__ void signal_and_wait(unsigned* cnt, unsigned target, int lane, uint32_t sb) {
    if (lane == 0) asm volatile("red.release.gpu.global.add.u32 [%0], 1;" ::"l"(cnt) : "memory");
    if (lane == 0) TL(30 + (((size_t)cnt >> 2) & 1));
    int it = 0;
    while (true) {
        unsigned v;
        asm volatile("ld.acquire.gpu.global.u32 %0, [%1];" : "=r"(v) : "l"(cnt) : "memory");
        if (__all_sync(0xffffffffu, (int)(v - target) >= 0)) break;
        if (++it > SPIN_LIMIT) __trap();
    }
    asm volatile("fence.proxy.async.global;" ::: "memory");
}

__global__ void __cluster_dims__(2, 1, 1) __launch_bounds__(NTHR, 1)
fused_decode_kernel(const __nv_bfloat16* __restrict__ xA, const __nv_bfloat16* __restrict__ xB,

                    const __nv_bfloat16* __restrict__ Kc, const __nv_bfloat16* __restrict__ Vc,
                    __nv_bfloat16* __restrict__ out, Scratch* gs, const __grid_constant__ Maps maps) {
    extern __shared__ __align__(1024) unsigned char smem_raw[];
    const uint32_t sb = smem_u32(smem_raw);
    const int tid = threadIdx.x, lane = tid & 31;
    const int cta = blockIdx.x, h = cta >> 2, j = cta & 3;
    const size_t kv_off = (size_t)blockIdx.x * 4096 * 128;
    if (tid == PFSTARTER) {
        asm volatile("cp.async.bulk.prefetch.L2.global [%0], %1;" ::"l"(Kc + kv_off), "r"(PFMODE == 2 ? 2 * SLOT : SLOT) : "memory");
        TLX(0);
    }
    if (tid == STARTER) {
        const uint64_t pol = evict_first();
#pragma unroll
        for (int i = 0; i < NFIRST; i++) mbar_init(sb + SM_FULL + i * 8, 1);
        asm volatile("fence.mbarrier_init.release.cluster;" ::: "memory");
#pragma unroll
        for (int i = 0; i < NFIRST; i++) {
            TLX(32 + i);
            mbar_expect_tx(sb + SM_FULL + i * 8, SLOT);
            tma3d(sb + i * SLOT, &maps.wqB, 0, j * 128 + i * 64, h * 2, sb + SM_FULL + i * 8, pol);
        }
    }
    uint32_t tnext = timer_ns() + (NFIRST + (PFMODE == 1 ? 0 : PFMODE == 2 ? 2 : 1)) * PACE - OFFS;
    const unsigned cnt1 = read_counter(&gs->cnt[1]);
    uint4 xv;
    if (tid < 128) {
        const __nv_bfloat16* x = (tid < 64 ? xB : xA) + ((tid >> 4) & 3) * 512 + j * 128 + (tid & 15) * 8;
        xv = __ldg(reinterpret_cast<const uint4*>(x));
    }
    if (tid == 0) TLX(21);
    const int w = __shfl_sync(0xffffffffu, tid >> 5, 0);
    const int pr = cta >> 1;
    const int slice = pr < 4 ? pr : pr < 36 ? 4 + ((pr - 4) & 7) * 4 + ((pr - 4) >> 3) : 36 + (pr - 36) % 7 * 4 + (pr - 36) / 7;

    if (w == 10) {
        const uint32_t tz = tnext - (NFIRST + 1) * PACE;
        if (lane == 0) sts64(sb + SM_PACE, tz, PACE * 16);
        asm volatile(BAR2 ::: "memory");
        if (lane == 0) {
            constexpr int win[] = {WINS / 1000000, WINS / 10000 % 100, WINS / 100 % 100, WINS % 100};
            constexpr int ls[] = {(int)(LSTAR / 1000000000 * 10), (int)(LSTAR / 1000000 % 1000 * 10), (int)(LSTAR / 1000 % 1000 * 10), (int)(LSTAR % 1000 * 10)};
            auto pos = [](int i) { return i < IT_Q ? i : i < IT_OP ? i - 2 : i - 4; };
            int slope = 0;
#pragma unroll
            for (int k = 0; k < 4; k++) {
                if (win[k] == 0) break;
                const int c = pos(win[k]);
                uint32_t acc = 0;
#pragma unroll
                for (int p = c; p < c + 4; p++) {
                    mbar_wait(sb + SM_FULL + (p < IT_Q ? p : p < IT_OP - 2 ? p + 2 : p + 4) * 8);
                    acc += timer_ns() - tz - p * PACE - (((p - ANCH) * slope) >> 4);
                }
                if (k == 0) mbar_wait(sb + SM_FULL + IT_Q * 8);
                asm volatile("red.relaxed.gpu.global.add.u32 [%0], %1;" ::"l"(&gs->late[k]), "r"((1u << 24) + min(acc >> 2, 65535u)) : "memory");
                uint32_t v;
                int it = 0;
                do { v = read_counter(&gs->late[k]); } while ((v >> 24) != NCTA && ++it < 1000);
                const int d = (v & 0xffffffu) >> 7;
                slope = max(-320, min(320, slope + (d - ls[k]) * (GAIN * 2) / (2 * (c - ANCH) + 3)));
                sts64(sb + SM_PACE, tz - ((ANCH * slope) >> 4), PACE * 16 + slope);
            }
        }
        return;
    }
    if (w >= 8) {
        if (w == 8) {
            asm volatile(BAR2 ::: "memory");
            const uint64_t pol = evict_first();
            int slot = NFIRST, tail = NFIRST - INFLIGHT;
            uint32_t np = NFIRST + 1, tap = 0;
            auto due = [&](uint32_t p) {
                uint32_t a, b;
                asm volatile("ld.volatile.shared.v2.b32 {%0,%1}, [%2];" : "=r"(a), "=r"(b) : "r"(sb + SM_PACE) : "memory");
                return a + ((p * b) >> 4);
            };
#pragma unroll 1
            for (int i = NFIRST; i < NITEM; i++) {
                const uint32_t dst = sb + slot * SLOT, bar = sb + SM_FULL + i * 8;
                if (++slot == NSLOT) slot = 0;
                if ((i & ~1) == IT_Q || (i & ~1) == IT_OP) continue;
                const bool ckv = i >= IT_C && i < IT_K1, wo = i >= IT_WO;
                const bool tiled = ckv || i < IT_K0 || i >= IT_WUV;
                const CUtensorMap* tm = &maps.wqB + (i < IT_K0 ? (i >> 1) : ckv ? 6 : wo ? 4 + (slice >> 5) : 3);
                const int c0 = wo ? (slice & 31) * 16 : i >= IT_WUV ? cta * 32 : 0;
                const int c1 = i < IT_K0 ? j * 128 + (i & 1) * 64 : ckv ? cta * 128 + (i - IT_C) * 16 : 0;
                const int c2 = i < IT_K0 ? h * 2 : ckv ? 0 : wo ? (i - IT_WO) * 4 + (j & 1) * 2 : i & 1;
                const int c = i < IT_Q ? i - IT_K0 : i < IT_V0 ? i - IT_K1 + 8 : i < IT_OP ? i - IT_V0 : i - IT_V1 + 8;
                const __nv_bfloat16* src = (i < IT_V0 ? Kc : Vc) + kv_off + (size_t)c * (SLOT / 2);
                if (i >= NSLOT) mbar_wait(sb + SM_EMPTY + (i - NSLOT) * 8);
                if (tail >= 0) mbar_wait(sb + SM_FULL + tail * 8);
                ++tail;
                if (tail == IT_Q || tail == IT_OP) tail += 2;
                if (i >= DRAIN_AT) mbar_wait(sb + SM_FULL + (i - DRAIN) * 8);
                if (i == NITEM - 1) mbar_wait(sb + SM_FULL + BAR_PEER * 8);
                if (i == NITEM - 1 - (slice < 32 ? AEARLY : BEARLY)) {
                    while (__all_sync(0xffffffffu, (int)(timer_ns() - (due(np) + tap - GLEAD)) < 0)) {}
                    asm volatile("bar.arrive 4, 64;" ::: "memory");
                }
                if (PFMODE == 1 || (PFMODE == 0 ? i != IT_K0 : (i & ~1) != IT_K0)) {
                    while (__all_sync(0xffffffffu, (int)(timer_ns() - (due(np) + tap)) < 0)) {}
                    ++np;
                    if (i == TAPER_AT) tap = TAPER;
                    tnext += PACE;
                    if (i >= TAPER_AT && i < TAPER_AT + TAPER_N) tnext += TAPER;
                }
                if (lane == 0) {
                    TLX(32 + i);
                    if (i == NITEM - 1) tma3d_pair(dst + (j & 1) * (IT_W2 - i) * SLOT, tm, c0, c1, c2, bar + (j & 1) * (IT_W2 - i) * 8, pol);
                    else if (tiled) tma3d(dst, tm, c0, c1, c2, bar, pol);
                    else bulk_load(dst, src, SLOT, bar, pol);
                }
            }
        } else {
            if (lane == 0) {
                mbar_init(sb + SM_FULL + IT_W2 * 8, 1);
                mbar_init(sb + SM_FULL + BAR_X * 8, 1);
                mbar_init(sb + SM_FULL + BAR_PEER * 8, 1);
                mbar_expect_tx(sb + SM_FULL + IT_W2 * 8, SLOT);
                mbar_expect_tx(sb + SM_FULL + BAR_X * 8, SLOT + 4096);
                mbar_expect_tx(sb + SM_FULL + BAR_PEER * 8, 8);
                asm volatile("fence.mbarrier_init.release.cluster;" ::: "memory");
            }
            if (lane < 6) asm volatile("prefetch.tensormap [%0];" ::"l"(&maps.wqA + lane) : "memory");
            asm volatile(BAR2 ::: "memory");
            asm volatile("bar.sync 3, 288;" ::: "memory");
            const unsigned epoch = epoch_of(cnt1);
            if (lane == 0) TL(9);
            signal_and_wait(&gs->cnt[0], epoch * NCTA, lane, sb);
            if (lane == 0) {
                TL(2);
                const uint4* q = gs->q[cta >> 5];
                uint32_t t1 = timer_ns();
#pragma unroll 1
                for (int i = 0; i < QN; i++) {
                    while ((int)(timer_ns() - t1) < 0) {}
                    t1 += QGAP;
                    bulk_load_nohint(sb + slot_off(IT_Q) + i * (2 * SLOT / QN), q + i * (2048 / QN), 2 * SLOT / QN,
                                     sb + SM_FULL + (IT_Q + i / (QN / 2)) * 8);
                }
            }
            asm volatile("bar.sync 3, 288;" ::: "memory");
            if (lane == 0) TL(13);
            signal_and_wait(&gs->cnt[1], epoch * NCTA, lane, sb);
            mbar_wait(sb + SM_EMPTY + (IT_OP - NSLOT) * 8);
            mbar_wait(sb + SM_EMPTY + (IT_OP + 1 - NSLOT) * 8);
            if (lane == 0) {
                TL(3);
                const uint4* op = gs->op[cta];
                bulk_load_nohint(sb + SM_MX, gs->stat[h], 1024, sb + SM_FULL + IT_OP * 8);
                uint32_t t1 = timer_ns();
#pragma unroll 1
                for (int i = 0; i < OPN; i++) {
                    while ((int)(timer_ns() - t1) < 0) {}
                    t1 += OPGAP;
                    bulk_load_nohint(sb + slot_off(IT_OP) + i * (2 * SLOT / OPN), op + i * (2048 / OPN), 2 * SLOT / OPN,
                                     sb + SM_FULL + (IT_OP + i / (OPN / 2)) * 8);
                }
            }
            mbar_wait(sb + SM_FULL + LATAT * 8);
            if (lane == 0) bulk_load_nohint(sb + SM_LAT, gs->lat[h], 4096, sb + SM_FULL + BAR_LAT * 8);
            mbar_wait(sb + SM_EMPTY + (IT_X - NSLOT) * 8);
            mbar_wait(sb + SM_EMPTY + (IT_X + 1 - NSLOT) * 8);
            asm volatile("bar.sync 4, 64;" ::: "memory");
            if (lane == 0) {
                TL(27);
                bulk_load_nohint(sb + slot_off(IT_X), gs->x[slice >> 5][(j & 1) * 12], SLOT + 4096, sb + SM_FULL + BAR_X * 8);
            }
        }
        const uint32_t oo  = __shfl_sync(0xffffffffu, (lane >> 3) * 2048 + slice * 32 + (j & 1) * 16 + (lane & 7) * 2, lane);
        const uint32_t src = __shfl_sync(0xffffffffu, sb + SM_FIN + ((j ^ w ^ 1) & 1) * 1536 + lane * 48, lane);
        const uint32_t sr2 = __shfl_sync(0xffffffffu, sb + SM_FIN + 3072 + lane * 80, lane);
        const uint32_t to  = w == 8 ? map_cta(sb, (j & 1) ^ 1) : sb;
        const uint32_t rcv = __shfl_sync(0xffffffffu, to + SM_RCV + lane * 4, lane);
        const uint32_t fin = __shfl_sync(0xffffffffu, to + SM_FULL + BAR_FIN * 8, lane);
        mbar_wait(sb + SM_FULL + (NITEM - 3) * 8);
        asm volatile("bar.sync 5, 320;" ::: "memory");
        const float4 p0 = ldsf4(src), p1 = ldsf4(src + 16);
        float sum = ((p0.x + p0.y) + (p0.z + p0.w)) + ((p1.x + p1.y) + (p1.z + p1.w));
        if (w == 8) {
            st_async32(rcv, __float_as_uint(sum), fin);
        } else {
            __nv_bfloat16* dst = reinterpret_cast<__nv_bfloat16*>(reinterpret_cast<char*>(out) + oo);
            mbar_wait(sb + SM_FULL + BAR_FIN * 8);
            if (lane == 0) TLX(154);
            sum += ldsf(rcv);
            asm volatile("bar.sync 7, 288;" ::: "memory");
            const float4 q0 = ldsf4(sr2), q1 = ldsf4(sr2 + 16), q2 = ldsf4(sr2 + 32), q3 = ldsf4(sr2 + 48);
            *dst = __float2bfloat16((((q0.x + sum) + q0.y) + (q0.z + q0.w) + ((q1.x + q1.y) + (q1.z + q1.w))) +
                                    (((q2.x + q2.y) + (q2.z + q2.w)) + ((q3.x + q3.y) + (q3.z + q3.w))));
            if (lane == 0) TLX(4);
        }
        return;
    }

    const int g = lane >> 2, t = lane & 3;
    const uint32_t in0 = sb + SM_IN0, in1 = sb + SM_IN1;
    auto xpos = [](int hh) { return (hh & 4) * 4 + (((hh >> 3) + (hh >> 2 & 1)) & 3) * 4 + (hh & 3); };
    const int ba = cta >> 5, ha = cta & 31;
    uint32_t* const ctx_dst = &gs->x[1][xpos(h)][(j * 4 + (w & 3)) * 16 + ((g ^ (w & 2)) & 3) * 4 + ((t - w) & 3)];
    uint32_t* const o_dst = &gs->x[0][xpos(ha)][ba * 64 + ((tid & 60) ^ ((ba & 1) * 16)) + ((t - g) & 3)];
    uint32_t* const lat_dst = &gs->lat[h][g & 3][j * 64 + ((w >> 1) ^ (g & 1)) * 16 + t * 4 + ((w * 2 ^ t) & 2)];
    {
        if (lane == 0) {
            const uint32_t bars = sb + (w < 4 ? SM_EMPTY : SM_FULL + NFIRST * 8) + (w & 3) * 14 * 8;
            const uint32_t cnt = w < 4 ? 8 : 1;
#pragma unroll
            for (int i = 0; i < 14; i++) mbar_init(bars + i * 8, cnt);
            if (w >= 4) {
#pragma unroll
                for (int i = 0; i < 14; i++)
                    mbar_expect_tx(bars + i * 8, (i == (IT_OP - NFIRST) % 14 && w == 4 + (IT_OP - NFIRST) / 14) ? SLOT + 1024 :
                                                 (i >= 12 && w == 7) ? (i == 12 ? 4096 : 128) : SLOT);
            }
            asm volatile("fence.mbarrier_init.release.cluster;" ::: "memory");
        }
        if (tid == 0) TL(22);
        asm volatile(BAR2 ::: "memory");
        if (lane < 16) st_rlx2(lat_dst, EMPTY, EMPTY);
        if (lane >= 16 && w < 4) st_rlx(ctx_dst, EMPTY);
        if (w >= 6) st_rlx(o_dst, EMPTY);
        if (cta == 0 && w == 5) st_rlx(&gs->late[lane], 0u);
        if (tid < 128) sts128((tid < 64 ? in0 : in1) + ((tid >> 4) & 3) * 272 + (tid & 15) * 16, xv);
    }
    bar_consumers();
    const uint32_t tag = epoch_tag(epoch_of(cnt1));
    if (tid == 0) TL(23);

    float acc[2][2];
    tile_mma<true>(sb, IT_WQB, in0, w, lane, acc);
    if (tid == 0) TL(24);
    publish(gs->part[0][cta], w, lane, acc, tag);
    if (tid == 0) TL(6);
    tile_mma<true>(sb, IT_WQA, in1, w, lane, acc);
    publish(gs->part[1][cta], w, lane, acc, tag);
    if (tid == 0) TL(7);
    bar_consumers();

    const float SC = 0.08838834764831845f * 1.4426950408889634f;
    gather(gs->part[0][h * 4], in0, tid, tag);
    if (tid == 0) TL(8);
    tile_mma<false>(sb, IT_WUK, in0, w, lane, acc);
    if (tid == 0) TL(25);
    if (lane < 16) {
        uint32_t* q = reinterpret_cast<uint32_t*>(gs->q[g]) + (2 * j + (w >> 2)) * 1024 + h * 32 + t;
        const int ch = 2 * (w & 3);
        q[((ch) ^ (h & 7)) * 4]     = pack_bf16(acc[0][0] * SC, acc[0][1] * SC);
        q[((ch + 1) ^ (h & 7)) * 4] = pack_bf16(acc[1][0] * SC, acc[1][1] * SC);
    }
    __syncwarp();
    asm volatile("bar.arrive 3, 288;" ::: "memory");
    gather(gs->part[1][ha * 4], in1, tid, tag);
    if (tid == 0) TL(28);

    uint32_t qf[16];
#pragma unroll
    for (int c = 0; c < 8; c++) {
        qf[2 * c]     = lds32(in1 + ba * 272 + ((c ^ g) << 4) + t * 4);
        qf[2 * c + 1] = lds32(in1 + ba * 272 + 128 + ((c ^ g) << 4) + t * 4);
    }
    const uint32_t sc_w = sb + SM_SC + w * 512;
    auto k_item = [&](int item, uint32_t sc) {
        mbar_wait(sb + SM_FULL + item * 8);
        const uint32_t base = sb + slot_off(item) + ((lane & 7) + (lane & 8)) * 256 + ((lane >> 4) << 7);
        float s[4][4];
#pragma unroll
        for (int T = 0; T < 4; T++) { s[T][0] = s[T][1] = s[T][2] = s[T][3] = 0.f; }
#pragma unroll
        for (int c = 0; c < 8; c++) {
            const uint32_t a = base + ((c ^ (lane & 7)) << 4);
#pragma unroll
            for (int T = 0; T < 4; T++) {
                uint32_t r0, r1, r2, r3;
                ldsm4(a + T * 4096, r0, r1, r2, r3);
                mma16816(s[T], r0, r1, r2, r3, qf[2 * c], qf[2 * c + 1]);
            }
        }
        __syncwarp();
        if (lane == 0) mbar_arrive8(sb + SM_EMPTY + item * 8);
        if (t == (g >> 1)) {
#pragma unroll
            for (int T = 0; T < 4; T++) {
                stsf(sc + (16 * T + g) * 4,     (g & 1) ? s[T][1] : s[T][0]);
                stsf(sc + (16 * T + g + 8) * 4, (g & 1) ? s[T][3] : s[T][2]);
            }
        }
    };
    k_item(IT_K0 + w, sc_w);
    if (tid == 224) TL(10);

    {
        float s[2][2][4];
#pragma unroll
        for (int i = 0; i < 16; i++) (&s[0][0][0])[i] = 0.f;
        mbar_wait(sb + SM_FULL + IT_Q * 8);
        mbar_wait(sb + SM_FULL + (IT_Q + 1) * 8);
        if (tid == 0) TLX(96 + IT_Q);
        mbar_wait(sb + SM_FULL + (IT_C + w) * 8);
        const uint32_t cb0 = sb + slot_off(IT_C + w) + ((lane & 7) + ((lane >> 4) << 3)) * 128;
        const uint32_t cx = (((lane >> 3) & 1) ^ (lane & 7)) << 4;
        const uint32_t qr = ((lane & 7) + (lane & 8)) * 128;
        const uint32_t qx = ((lane >> 4) ^ (lane & 7)) << 4;
#pragma unroll
        for (int cb = 0; cb < 8; cb++) {
            const uint32_t qb = sb + slot_off(IT_Q + (cb >> 2)) + (cb & 3) * 4096 + qr;
#pragma unroll
            for (int k4 = 0; k4 < 4; k4++) {
                uint32_t b0, b1, b2, b3, a0, a1, a2, a3;
                ldsm4(cb0 + cb * 2048 + (cx ^ (k4 << 5)), b0, b1, b2, b3);
                ldsm4(qb + (qx ^ (k4 << 5)), a0, a1, a2, a3);
                mma16816(s[0][0], a0, a1, a2, a3, b0, b1);
                mma16816(s[0][1], a0, a1, a2, a3, b2, b3);
                ldsm4(qb + 2048 + (qx ^ (k4 << 5)), a0, a1, a2, a3);
                mma16816(s[1][0], a0, a1, a2, a3, b0, b1);
                mma16816(s[1][1], a0, a1, a2, a3, b2, b3);
            }
        }
        __syncwarp();
        if (lane == 0) { mbar_arrive(sb + SM_EMPTY + IT_Q * 8); mbar_arrive(sb + SM_EMPTY + (IT_Q + 1) * 8); }
#pragma unroll
        for (int r = 0; r < 4; r++) {
            const int mt = r >> 1, hi = (r & 1) * 2;
            float m = fmaxf(fmaxf(s[mt][0][hi], s[mt][0][hi + 1]), fmaxf(s[mt][1][hi], s[mt][1][hi + 1]));
            m = fmaxf(m, __shfl_xor_sync(0xffffffffu, m, 1));
            m = fmaxf(m, __shfl_xor_sync(0xffffffffu, m, 2));
            if (t == 0) stsf(sb + SM_MX + (8 * r + g) * 32 + w * 4, m);
        }
        bar_consumers();
        if (tid == 0) TL(11);
        uint32_t pf[2][4];
#pragma unroll
        for (int r = 0; r < 4; r++) {
            const int mt = r >> 1, hi = r & 1;
            const float4 m0 = ldsf4(sb + SM_MX + (8 * r + g) * 32), m1 = ldsf4(sb + SM_MX + (8 * r + g) * 32 + 16);
            const float m = fmaxf(fmaxf(fmaxf(m0.x, m0.y), fmaxf(m0.z, m0.w)), fmaxf(fmaxf(m1.x, m1.y), fmaxf(m1.z, m1.w)));
            const uint32_t p0 = pack_bf16(ex2(s[mt][0][2 * hi] - m), ex2(s[mt][0][2 * hi + 1] - m));
            const uint32_t p1 = pack_bf16(ex2(s[mt][1][2 * hi] - m), ex2(s[mt][1][2 * hi + 1] - m));
            pf[mt][hi] = p0; pf[mt][2 + hi] = p1;
            float l = (bf_lo(p0) + bf_hi(p0)) + (bf_lo(p1) + bf_hi(p1));
            l += __shfl_xor_sync(0xffffffffu, l, 1);
            l += __shfl_xor_sync(0xffffffffu, l, 2);
            if (t == 0) stsf(sb + SM_SUM + (8 * r + g) * 32 + w * 4, l);
        }
        sts128(sb + SM_PF + (w * 2 + 0) * 512 + lane * 16, make_uint4(pf[0][0], pf[0][1], pf[0][2], pf[0][3]));
        sts128(sb + SM_PF + (w * 2 + 1) * 512 + lane * 16, make_uint4(pf[1][0], pf[1][1], pf[1][2], pf[1][3]));
        bar_consumers();
        if (w == 0) {
            const float4 m0 = ldsf4(sb + SM_MX + lane * 32), m1 = ldsf4(sb + SM_MX + lane * 32 + 16);
            const float4 l0 = ldsf4(sb + SM_SUM + lane * 32), l1 = ldsf4(sb + SM_SUM + lane * 32 + 16);
            const float m = fmaxf(fmaxf(fmaxf(m0.x, m0.y), fmaxf(m0.z, m0.w)), fmaxf(fmaxf(m1.x, m1.y), fmaxf(m1.z, m1.w)));
            const float l = ((l0.x + l0.y) + (l0.z + l0.w)) + ((l1.x + l1.y) + (l1.z + l1.w));
            gs->stat[lane][cta] = make_float2(m, l);
        }
        float o[2][8][4];
#pragma unroll
        for (int i = 0; i < 64; i++) (&o[0][0][0])[i] = 0.f;
        const uint32_t vr = w * 2048 + ((lane & 7) + (lane & 8)) * 128;
        const uint32_t vx = ((lane >> 4) ^ (lane & 7)) << 4;
#pragma unroll
        for (int ks = 0; ks < 8; ks++) {
            const uint4 p0 = lds128(sb + SM_PF + (ks * 2 + 0) * 512 + lane * 16);
            const uint4 p1 = lds128(sb + SM_PF + (ks * 2 + 1) * 512 + lane * 16);
            const uint32_t vb = sb + slot_off(IT_C + ks) + vr;
#pragma unroll
            for (int n2 = 0; n2 < 4; n2++) {
                uint32_t b0, b1, b2, b3;
                ldsm4t(vb + (vx ^ (n2 << 5)), b0, b1, b2, b3);
                mma16816(o[0][2 * n2],     p0.x, p0.y, p0.z, p0.w, b0, b1);
                mma16816(o[0][2 * n2 + 1], p0.x, p0.y, p0.z, p0.w, b2, b3);
                mma16816(o[1][2 * n2],     p1.x, p1.y, p1.z, p1.w, b0, b1);
                mma16816(o[1][2 * n2 + 1], p1.x, p1.y, p1.z, p1.w, b2, b3);
            }
            __syncwarp();
            if (lane == 0) mbar_arrive(sb + SM_EMPTY + (IT_C + ks) * 8);
        }
        if (tid == 0) TL(12);
        mbar_wait(sb + SM_FULL + (IT_K1 + STG_AT + (w >> STG_SH)) * 8);
#pragma unroll
        for (int r = 0; r < 4; r++) {
            const int mt = r >> 1, hi = (r & 1) * 2;
            uint4* dst = gs->op[(8 * r + g) * 4 + (w >> 1)] + (cta >> 6) * 1024 + (w & 1) * 512 + (cta & 63) * 8;
#pragma unroll
            for (int u = 0; u < 2; u++) {
                uint4 v;
                v.x = pack_bf16(o[mt][4 * u][hi],     o[mt][4 * u][hi + 1]);
                v.y = pack_bf16(o[mt][4 * u + 1][hi], o[mt][4 * u + 1][hi + 1]);
                v.z = pack_bf16(o[mt][4 * u + 2][hi], o[mt][4 * u + 2][hi + 1]);
                v.w = pack_bf16(o[mt][4 * u + 3][hi], o[mt][4 * u + 3][hi + 1]);
                dst[(t + 4 * u) ^ (cta & 7)] = v;
            }
        }
        if (tid == 0) TL(29);
        asm volatile("bar.arrive 3, 288;" ::: "memory");
    }

    k_item(IT_K1 + w, sc_w + 256);
    __syncwarp();
    {
        const float4 s = ldsf4(sc_w + lane * 16);
        float m = fmaxf(fmaxf(s.x, s.y), fmaxf(s.z, s.w));
#pragma unroll
        for (int d = 1; d < 32; d <<= 1) m = fmaxf(m, __shfl_xor_sync(0xffffffffu, m, d));
        if (lane == 0) stsf(sb + SM_ML + w * 4, m);
        bar_consumers();
        const float4 m0 = ldsf4(sb + SM_ML), m1 = ldsf4(sb + SM_ML + 16);
        m = fmaxf(fmaxf(fmaxf(m0.x, m0.y), fmaxf(m0.z, m0.w)), fmaxf(fmaxf(m1.x, m1.y), fmaxf(m1.z, m1.w))) * SC;
        const uint32_t p0 = pack_bf16(ex2(fmaf(s.x, SC, -m)), ex2(fmaf(s.y, SC, -m)));
        const uint32_t p1 = pack_bf16(ex2(fmaf(s.z, SC, -m)), ex2(fmaf(s.w, SC, -m)));
        float l = (bf_lo(p0) + bf_hi(p0)) + (bf_lo(p1) + bf_hi(p1));
#pragma unroll
        for (int d = 1; d < 32; d <<= 1) l += __shfl_xor_sync(0xffffffffu, l, d);
        if (lane == 0) stsf(sb + SM_ML + 32 + w * 4, l);
        sts64(sb + SM_PA + w * 256 + lane * 8, p0, p1);
        __syncwarp();
    }
    if (tid == 224) TL(14);

    float oa[4][4];
#pragma unroll
    for (int i = 0; i < 16; i++) (&oa[0][0])[i] = 0.f;
    auto v_item = [&](int item, uint32_t pa) {
        uint32_t p[8];
#pragma unroll
        for (int i = 0; i < 8; i++) p[i] = lds32(pa + i * 16 + t * 4);
        mbar_wait(sb + SM_FULL + item * 8);
        const uint32_t base = sb + slot_off(item) + ((lane & 7) + ((lane >> 4) << 3)) * 256 + ((lane & 8) << 4);
#pragma unroll
        for (int c = 0; c < 8; c++) {
            const uint32_t a = base + ((c ^ (lane & 7)) << 4);
            const uint32_t mask = ((c == (g ^ (2 * t))) ? 0x0000ffffu : 0u) | ((c == (g ^ (2 * t + 1))) ? 0xffff0000u : 0u);
#pragma unroll
            for (int T = 0; T < 4; T++) {
                uint32_t r0, r1, r2, r3;
                ldsm4t(a + T * 4096, r0, r1, r2, r3);
                mma16816(oa[T], r0, r1, r2, r3, p[2 * T] & mask, p[2 * T + 1] & mask);
            }
        }
        __syncwarp();
        if (lane == 0) mbar_arrive8(sb + SM_EMPTY + item * 8);
    };
    v_item(IT_V0 + w, sb + SM_PA + w * 256);
    if (tid == 224) TL(15);

    mbar_wait(sb + SM_FULL + IT_OP * 8);
    if (tid == 0) TLX(96 + IT_OP);
    if (w < 4) {
        const float2 st = ldsf2(sb + SM_MX + tid * 8);
        float m = st.x;
#pragma unroll
        for (int d = 1; d < 32; d <<= 1) m = fmaxf(m, __shfl_xor_sync(0xffffffffu, m, d));
        const uint32_t wb = pack_bf16(ex2(st.x - m), 0.f);
        float l = bf_lo(wb) * st.y;
#pragma unroll
        for (int d = 1; d < 32; d <<= 1) l += __shfl_xor_sync(0xffffffffu, l, d);
#pragma unroll
        for (int bb = 0; bb < 4; bb++) sts16(in0 + bb * 272 + tid * 2, bb == w ? (uint16_t)wb : (uint16_t)0);
        if (lane == 0) stsf(sb + SM_ML + 64 + w * 4, 1.f / l);
    }
    bar_consumers();
    tile_mma<true>(sb, IT_OP, in0, w, lane, acc);
    if (lane < 16) {
        const float inv = ldsf(sb + SM_ML + 64 + g * 4);
        const uint32_t v0 = pack_bf16(acc[0][0] * inv, acc[0][1] * inv), v1 = pack_bf16(acc[1][0] * inv, acc[1][1] * inv);
        st_rlx2(lat_dst, (t & 1) ? v1 : v0, (t & 1) ? v0 : v1);
    }
    if (tid == 0) TL(19);

    {
        const float4 l0 = ldsf4(sb + SM_ML + 32), l1 = ldsf4(sb + SM_ML + 48);
        const float inv = 1.f / (((l0.x + l0.y) + (l0.z + l0.w)) + ((l1.x + l1.y) + (l1.z + l1.w)));
        v_item(IT_V1 + w, sb + SM_PA + w * 256 + 128);
        const uint32_t so = sb + SM_PF + w * 512 + (16 * t + g) * 4;
        stsf(so,       (oa[0][0] + oa[1][0]) + (oa[2][0] + oa[3][0]));
        stsf(so + 32,  (oa[0][1] + oa[1][1]) + (oa[2][1] + oa[3][1]));
        stsf(so + 256, (oa[0][2] + oa[1][2]) + (oa[2][2] + oa[3][2]));
        stsf(so + 288, (oa[0][3] + oa[1][3]) + (oa[2][3] + oa[3][3]));
        if (w < 6) {
            asm volatile("bar.arrive 1, 256;" ::: "memory");
        } else {
            bar_consumers();
            float x = 0.f, y = 0.f;
#pragma unroll
            for (int i = 0; i < 8; i++) {
                const float2 v = ldsf2(sb + SM_PF + i * 512 + (tid & 63) * 8);
                x += v.x; y += v.y;
            }
            st_rlx(o_dst, pack_bf16(x * inv, y * inv));
            if (lane == 0) {
                const uint32_t to = map_cta(sb, w & 1);
                st_async32(to + SM_RCV + 128 + (j & 1) * 4, 0u, to + SM_FULL + BAR_PEER * 8);
            }
            if (tid == 224) TL(17);
        }
    }

    if (w < 4) {
        const uint32_t lo = (g & 3) * 1024 + (g >> 2) * 512 + (g & 1) * 64 + t * 16;
        const int wd = ((lane >> 2 & 2) + (lane >> 4)) ^ (lane >> 1 & 3);
        const uint32_t base = sb + ((lane & 6) * 4 + wd * 2 + (lane & 1)) * 64 + (((w ^ wd) & 3) << 4);
        const uint64_t dst = __shfl_sync(0xffffffffu, (unsigned long long)ctx_dst, lane);
        mbar_wait(sb + SM_FULL + BAR_LAT * 8);
        uint4 a[8];
#pragma unroll
        for (int i = 0; i < 8; i++) a[i] = lds128(sb + SM_LAT + (lo ^ (i * 64)));
        int it = 0;
        while (refetch<0>(a, lane, [&](int i) { return (const char*)gs->lat[h] + (lo ^ (i * 64)); }))
            if (++it > SPIN_LIMIT) __trap();
        float v0 = 0.f, v1 = 0.f;
#pragma unroll
        for (int i = 0; i < 2; i++) {
            float c[4][4];
#pragma unroll
            for (int k = 0; k < 16; k++) (&c[0][0])[k] = 0.f;
            c[0][0] = v0; c[0][1] = v1;
            mbar_wait(sb + SM_FULL + (IT_WUV + i) * 8);
#pragma unroll
            for (int kk = 0; kk < 8; kk++) {
                uint32_t r0, r1, r2, r3;
                ldsm4t(base + slot_off(IT_WUV + i) + kk * 2048, r0, r1, r2, r3);
                mma16816(c[2 * (kk & 1)],     a[kk].x, a[kk].y, a[kk].z, a[kk].w, r0, r1);
                mma16816(c[2 * (kk & 1) + 1], a[kk].x, a[kk].y, a[kk].z, a[kk].w, r2, r3);
            }
            v0 = (c[0][0] + c[1][2]) + (c[2][0] + c[3][2]);
            v1 = (c[0][1] + c[1][3]) + (c[2][1] + c[3][3]);
            if (i == 0) { v0 = __shfl_xor_sync(0xffffffffu, v0, 16); v1 = __shfl_xor_sync(0xffffffffu, v1, 16); }
        }
        st_rlx_if(dst, pack_bf16(v0, v1), lane >= 16);
        if (tid == 0) TL(16);
    }

    {
        const bool isB = slice >= 32;
        const int r = j & 1;
        const uint32_t xl = isB ? t * 64 + (((g ^ (t & 2)) & 3) << 4) : (g & 3) * 256 + ((g & 1) * 4 + t) * 16;
        const uint32_t cs = isB ? 256 : 64;
        const uint32_t xo = r * 8192 + (w >> 1) * 1024 + (w & 1) * 2 * cs + xl, xz = (1 - r) * 12288 + w * 1024 + (g >> 2) * 2 * cs + xl;
        auto xoff = [&](int i) { return i < 6 ? (i >> 1) * 4096 + (xo ^ ((i & 1) * cs)) : xz ^ ((i & 1) * cs); };
        const char* src = (const char*)gs->x[slice >> 5][r * 12];
        uint32_t off[2], ofz[2];
#pragma unroll
        for (int u = 0; u < 2; u++) {
            const int tt = (lane & 7) >> 1;
            const int row = 8 * tt + 2 * ((2 * u + (lane >> 4) + tt) & 3) + (lane & 1);
            off[u] = sb + w * 2048 + row * 32 + ((((lane >> 3) ^ (row >> 2)) & 1) << 4);
            ofz[u] = __shfl_sync(0xffffffffu, sb + (w < 4 ? slot_off(IT_WO + 3) : slot_off(IT_W2)) + (w & 3) * 4096 + (lane & 8) * 256 +
                                              row * 32 + (((r ^ (row >> 2)) & 1) << 4), lane);
        }
        const uint32_t fin = __shfl_sync(0xffffffffu, sb + SM_FIN + (t & 1) * 768 + g * 48 + ((w ^ (t & 1)) << 2), lane);
        const uint32_t fi2 = __shfl_sync(0xffffffffu, sb + SM_FIN + 3072 + (t & 1) * 1280 + g * 80 + (((w * 2 + (t >> 1)) ^ (t * 2 & 2)) << 2), lane);
        uint32_t a[2][4][4];
        uint4 x[8];
        float c[4][4];
        auto load_w = [&](int i) {
            mbar_wait(sb + SM_FULL + (i < 3 ? IT_WO + i : w < 4 ? IT_WO + 3 : IT_W2) * 8);
#pragma unroll
            for (int q = 0; q < 4; q++)
                ldsm4t((i < 3 ? slot_off(IT_WO + i) + off[q & 1] : ofz[q & 1]) + (q >> 1) * 1024,
                       a[i & 1][q][0], a[i & 1][q][1], a[i & 1][q][2], a[i & 1][q][3]);
        };
        auto mma_w = [&](int i) {
#pragma unroll
            for (int q = 0; q < 4; q++) {
                if (i == 0 || i == 3) c[q][0] = c[q][1] = c[q][2] = c[q][3] = 0.f;
                mma16816(c[q], a[i & 1][q][0], a[i & 1][q][1], a[i & 1][q][2], a[i & 1][q][3],
                         (q & 1) ? x[2 * i + (q >> 1)].z : x[2 * i + (q >> 1)].x, (q & 1) ? x[2 * i + (q >> 1)].w : x[2 * i + (q >> 1)].y);
            }
        };
        load_w(0); load_w(1);
        mbar_wait(sb + SM_FULL + BAR_X * 8);
        if (tid == 224) TLX(20);
#pragma unroll
        for (int i = 0; i < 8; i++) x[i] = lds128_if(sb + slot_off(IT_X) + xoff(i), i >= 6 || lane < 16);
        int it = 0;
        while (true) {
            mma_w(0); mma_w(1);
            if (!refetch<6>(x, lane, [&](int i) { return src + xoff(i); })) break;
            if (++it > SPIN_LIMIT) __trap();
        }
        load_w(2);
        mma_w(2);
#pragma unroll
        for (int e = 0; e < 4; e++) stsf_if(fin + (e >> 1) * 1536 + (e & 1) * 384, (c[0][e] + c[1][e]) + (c[2][e] + c[3][e]), t < 2);
        asm volatile("bar.arrive 5, 320;" ::: "memory");
        if (tid == 0) TLX(18);
        load_w(3);
        mma_w(3);
#pragma unroll
        for (int e = 0; e < 2; e++) {
            const float lo = (c[0][e] + c[1][e]) + (c[2][e] + c[3][e]), hi = (c[0][e + 2] + c[1][e + 2]) + (c[2][e + 2] + c[3][e + 2]);
            stsf(fi2 + e * 640, t < 2 ? lo : hi);
        }
        asm volatile("bar.arrive 7, 288;" ::: "memory");
        if (tid == 224) TLX(26);
    }
}

typedef CUresult (*EncodeTiledFn)(CUtensorMap*, CUtensorMapDataType, cuuint32_t, void*, const cuuint64_t*,
                                  const cuuint64_t*, const cuuint32_t*, const cuuint32_t*, CUtensorMapInterleave,
                                  CUtensorMapSwizzle, CUtensorMapL2promotion, CUtensorMapFloatOOBfill);

void encode_map(EncodeTiledFn enc, CUtensorMap* tm, const void* p, cuuint64_t cols, cuuint64_t rows,
                cuuint32_t brows, cuuint32_t bblk) {
    cuuint64_t dims[3] = {64, rows, cols / 64};
    cuuint64_t strides[2] = {cols * 2, 128};
    cuuint32_t box[3] = {64, brows, bblk};
    cuuint32_t es[3] = {1, 1, 1};
    enc(tm, CU_TENSOR_MAP_DATA_TYPE_BFLOAT16, 3, const_cast<void*>(p), dims, strides, box, es,
        CU_TENSOR_MAP_INTERLEAVE_NONE, CU_TENSOR_MAP_SWIZZLE_128B, CU_TENSOR_MAP_L2_PROMOTION_L2_256B,
        CU_TENSOR_MAP_FLOAT_OOB_FILL_NONE);
}

void encode_slice_map(EncodeTiledFn enc, CUtensorMap* tm, const void* p, cuuint64_t cols, cuuint64_t rows, cuuint32_t bcols) {
    cuuint64_t dims[3] = {cols, 256, rows / 256};
    cuuint64_t strides[2] = {cols * 2, cols * 512};
    cuuint32_t box[3] = {bcols, 256, 32 / bcols};
    cuuint32_t es[3] = {1, 1, 1};
    enc(tm, CU_TENSOR_MAP_DATA_TYPE_BFLOAT16, 3, const_cast<void*>(p), dims, strides, box, es, CU_TENSOR_MAP_INTERLEAVE_NONE,
        bcols == 16 ? CU_TENSOR_MAP_SWIZZLE_32B : CU_TENSOR_MAP_SWIZZLE_64B, CU_TENSOR_MAP_L2_PROMOTION_L2_128B,
        CU_TENSOR_MAP_FLOAT_OOB_FILL_NONE);
}

}

extern "C" void kernel_launch(void* const* d_in, const int* in_sizes, int n_in, void* d_out, int out_size) {
    (void)in_sizes; (void)n_in; (void)out_size;
    static EncodeTiledFn enc = nullptr;
    static Scratch* gs = nullptr;
    if (!enc) {
        cudaGetSymbolAddress((void**)&gs, g_scratch);
        void* fn = nullptr;
        cudaDriverEntryPointQueryResult qr;
        cudaGetDriverEntryPoint("cuTensorMapEncodeTiled", &fn, cudaEnableDefault, &qr);
        enc = (EncodeTiledFn)fn;
        cudaFuncSetAttribute(fused_decode_kernel, cudaFuncAttributeMaxDynamicSharedMemorySize, SM_END);
    }
    Maps maps;
    encode_map(enc, &maps.wqB, d_in[7], 4096, 512, 64, 2);
    encode_map(enc, &maps.wqA, d_in[3], 4096, 512, 64, 2);
    encode_map(enc, &maps.wuk, d_in[8], 4096, 512, 64, 2);
    encode_slice_map(enc, &maps.wuv, d_in[9], 4096, 512, 32);
    encode_slice_map(enc, &maps.woB, d_in[10], 512, 4096, 16);
    encode_slice_map(enc, &maps.woA, d_in[4], 512, 4096, 16);
    encode_map(enc, &maps.ckv, d_in[6], 512, 16384, 16, 8);
    fused_decode_kernel<<<NCTA, NTHR, SM_END>>>((const __nv_bfloat16*)d_in[0], (const __nv_bfloat16*)d_in[5],
                                                (const __nv_bfloat16*)d_in[1] + 3072 * 128, (const __nv_bfloat16*)d_in[2] + 3072 * 128,
                                                (__nv_bfloat16*)d_out, gs, maps);
}
```

```cpp
#include <cuda_runtime.h>
#include <cuda_bf16.h>
#include <cuda.h>
#include <stdint.h>

namespace {

constexpr int NCTA   = 128;
constexpr int NSLOT  = 13;
constexpr int SLOT   = 16384;
constexpr int NITEM  = 56;
#define INFLIGHT 4
#define ADAPT
#define PACE 644
#define OFFS 600
#define STAG 0
#define OWAIT 0
#define FINMODE 1
#define FINDELAY 0
#define NFIRST 2
#define STARTER 256
#define CTXWAIT 0
#define LATAT 46
#define TAPER 250
#define TAPER_AT 49
#define TAPER_N 1
#define STG_AT 2
#define STG_SH 1
#define OPN 8
#define OPGAP 200
#define QN 2
#define QGAP 0
#define PFSTARTER 288
#define KPF 0
#define LSU0 2
#define Q1 0
#define T2 0
#define PFIRST (LSU0 == 2 ? 4 : 2)
#define GLEAD 150
#define AEARLY 0
#define BEARLY 0
#define DRAIN_AT 99
#define DRAIN 2
#define AWAIT 0
#define NPOLL 4
#define FGAP 170
#define FDEL 0
#define LSTAR 186183189180ll
#define WINS 10223342
#define PROMO_WO 2
#define PROMO_UV 2
#define PROMO_C 3
#define GAIN 11
#define ANCH 0
constexpr int NTHR   = 352;
#define BAR2 "bar.sync 2, 352;"

constexpr int IT_WQB = 0, IT_WQA = 2, IT_WUK = 4, IT_K0 = 6, IT_Q = 14, IT_C = 16, IT_K1 = 24, IT_V0 = 32,
              IT_OP = 40, IT_V1 = 42, IT_WUV = 50, IT_WO = 52;
constexpr int IT_X = 56;
constexpr int IT_W2 = 58;
constexpr int BAR_LAT = 56, BAR_FIN = 57, BAR_X = 59, BAR_PEER = 60;

constexpr int SM_FULL  = NSLOT * SLOT;
constexpr int SM_EMPTY = SM_FULL + 512;
constexpr int SM_IN0   = SM_EMPTY + 512;
constexpr int SM_IN1   = SM_IN0 + 1088;
constexpr int SM_SC    = SM_IN1 + 1088;
constexpr int SM_PA    = SM_SC + 4096;
constexpr int SM_PF    = SM_PA + 2048;
constexpr int SM_MX    = SM_PF + 8192;
constexpr int SM_ML    = SM_MX + 1024;
constexpr int SM_RCV   = SM_ML + 128;
constexpr int SM_PACE  = SM_RCV + 144;
constexpr int SM_END   = SM_PACE + 32;
constexpr int SM_LAT   = SM_PF + 4096;
constexpr int SM_FIN   = SM_SC;
constexpr int SM_SUM   = SM_IN0;
static_assert(SM_END <= 232448, "smem");

struct Maps { CUtensorMap wqB, wqA, wuk, wuv, woA, woB, ckv;
};

struct Scratch {
    unsigned cnt[32];
    unsigned late[32];
    float    part[2][NCTA][512];
    uint32_t x[2][32][256];
    uint32_t lat[32][4][256];
    uint4    q[4][2048];
    uint4    op[NCTA][2048];
    float2   stat[32][128];
};
__device__ __align__(128) Scratch g_scratch;
#define TLX(i) do {} while (0)
#define TL(i) do {} while (0)

constexpr int SPIN_LIMIT = 1 << 22;

__device__ __forceinline__ uint32_t smem_u32(const void* p) { return (uint32_t)__cvta_generic_to_shared(p); }
__device__ __forceinline__ void mbar_init(uint32_t bar, uint32_t cnt) {
    asm volatile("mbarrier.init.shared::cta.b64 [%0], %1;" ::"r"(bar), "r"(cnt) : "memory");
}
__device__ __forceinline__ void mbar_expect_tx(uint32_t bar, uint32_t bytes) {
    asm volatile("mbarrier.arrive.expect_tx.shared::cta.b64 _, [%0], %1;" ::"r"(bar), "r"(bytes) : "memory");
}
__device__ __forceinline__ void mbar_arrive(uint32_t bar) {
    asm volatile("mbarrier.arrive.shared::cta.b64 _, [%0];" ::"r"(bar) : "memory");
}
__device__ __forceinline__ void mbar_arrive8(uint32_t bar) {
    asm volatile("mbarrier.arrive.shared::cta.b64 _, [%0], 8;" ::"r"(bar) : "memory");
}
__device__ __forceinline__ void mbar_wait(uint32_t bar) {
    uint32_t done;
    int it = 0;
    do {
        asm volatile("{\n.reg .pred p;\nmbarrier.try_wait.parity.shared::cta.b64 p, [%1], 0;\nselp.u32 %0, 1, 0, p;\n}"
                     : "=r"(done) : "r"(bar) : "memory");
        if (++it > SPIN_LIMIT) __trap();
    } while (!done);
}
__device__ __forceinline__ uint32_t map_cta(uint32_t a, uint32_t rank) {
    uint32_t r; asm("mapa.shared::cluster.u32 %0, %1, %2;" : "=r"(r) : "r"(a), "r"(rank)); return r;
}
__device__ __forceinline__ void st_async32(uint32_t a, uint32_t v, uint32_t bar) {
    asm volatile("st.async.shared::cluster.mbarrier::complete_tx::bytes.b32 [%0], %1, [%2];" ::"r"(a), "r"(v), "r"(bar) : "memory");
}
__device__ __forceinline__ uint64_t evict_first() {
    uint64_t pol; asm volatile("createpolicy.fractional.L2::evict_first.b64 %0, 1.0;" : "=l"(pol)); return pol;
}
__device__ __forceinline__ void bulk_load(uint32_t dst, const void* src, uint32_t bytes, uint32_t bar, uint64_t pol) {
    asm volatile("cp.async.bulk.shared::cluster.global.mbarrier::complete_tx::bytes.L2::cache_hint [%0], [%1], %2, [%3], %4;"
                 ::"r"(dst), "l"(src), "r"(bytes), "r"(bar), "l"(pol) : "memory");
}
__device__ __forceinline__ void bulk_load_nohint(uint32_t dst, const void* src, uint32_t bytes, uint32_t bar) {
    asm volatile("cp.async.bulk.shared::cluster.global.mbarrier::complete_tx::bytes [%0], [%1], %2, [%3];"
                 ::"r"(dst), "l"(src), "r"(bytes), "r"(bar) : "memory");
}
__device__ __forceinline__ void bulk_load_pair(uint32_t dst, const void* src, uint32_t bytes, uint32_t bar) {
    asm volatile("cp.async.bulk.shared::cluster.global.mbarrier::complete_tx::bytes.multicast::cluster [%0], [%1], %2, [%3], %4;"
                 ::"r"(dst), "l"(src), "r"(bytes), "r"(bar), "h"((uint16_t)3) : "memory");
}
__device__ __forceinline__ void tma3d(uint32_t dst, const CUtensorMap* tm, int c0, int c1, int c2, uint32_t bar, uint64_t pol) {
    asm volatile("cp.async.bulk.tensor.3d.shared::cluster.global.mbarrier::complete_tx::bytes.L2::cache_hint [%0], [%1, {%3, %4, %5}], [%2], %6;"
                 ::"r"(dst), "l"(tm), "r"(bar), "r"(c0), "r"(c1), "r"(c2), "l"(pol) : "memory");
}
__device__ __forceinline__ void tma3d_pair(uint32_t dst, const CUtensorMap* tm, int c0, int c1, int c2, uint32_t bar, uint64_t pol) {
    asm volatile("cp.async.bulk.tensor.3d.shared::cluster.global.mbarrier::complete_tx::bytes.multicast::cluster.L2::cache_hint [%0], [%1, {%3, %4, %5}], [%2], %7, %6;"
                 ::"r"(dst), "l"(tm), "r"(bar), "r"(c0), "r"(c1), "r"(c2), "l"(pol), "h"((uint16_t)3) : "memory");
}
__device__ __forceinline__ void ldsm4(uint32_t a, uint32_t& r0, uint32_t& r1, uint32_t& r2, uint32_t& r3) {
    asm volatile("ldmatrix.sync.aligned.m8n8.x4.shared.b16 {%0,%1,%2,%3}, [%4];"
                 : "=r"(r0), "=r"(r1), "=r"(r2), "=r"(r3) : "r"(a) : "memory");
}
__device__ __forceinline__ void ldsm4t(uint32_t a, uint32_t& r0, uint32_t& r1, uint32_t& r2, uint32_t& r3) {
    asm volatile("ldmatrix.sync.aligned.m8n8.x4.trans.shared.b16 {%0,%1,%2,%3}, [%4];"
                 : "=r"(r0), "=r"(r1), "=r"(r2), "=r"(r3) : "r"(a) : "memory");
}
__device__ __forceinline__ void mma16816(float (&c)[4], uint32_t a0, uint32_t a1, uint32_t a2, uint32_t a3,
                                         uint32_t b0, uint32_t b1) {
    asm volatile("mma.sync.aligned.m16n8k16.row.col.f32.bf16.bf16.f32 {%0,%1,%2,%3}, {%4,%5,%6,%7}, {%8,%9}, {%0,%1,%2,%3};"
                 : "+f"(c[0]), "+f"(c[1]), "+f"(c[2]), "+f"(c[3])
                 : "r"(a0), "r"(a1), "r"(a2), "r"(a3), "r"(b0), "r"(b1));
}
__device__ __forceinline__ uint32_t lds32(uint32_t a) {
    uint32_t v; asm volatile("ld.shared.b32 %0, [%1];" : "=r"(v) : "r"(a) : "memory"); return v;
}
__device__ __forceinline__ float ldsf(uint32_t a) {
    float v; asm volatile("ld.shared.f32 %0, [%1];" : "=f"(v) : "r"(a) : "memory"); return v;
}
__device__ __forceinline__ float2 ldsf2(uint32_t a) {
    float2 v; asm volatile("ld.shared.v2.f32 {%0,%1}, [%2];" : "=f"(v.x), "=f"(v.y) : "r"(a) : "memory"); return v;
}
__device__ __forceinline__ float4 ldsf4(uint32_t a) {
    float4 v; asm volatile("ld.shared.v4.f32 {%0,%1,%2,%3}, [%4];" : "=f"(v.x), "=f"(v.y), "=f"(v.z), "=f"(v.w) : "r"(a) : "memory"); return v;
}
__device__ __forceinline__ uint4 lds128(uint32_t a) {
    uint4 v; asm volatile("ld.shared.v4.b32 {%0,%1,%2,%3}, [%4];" : "=r"(v.x), "=r"(v.y), "=r"(v.z), "=r"(v.w) : "r"(a) : "memory"); return v;
}
__device__ __forceinline__ uint4 lds128_if(uint32_t a, bool on) {
    uint4 v;
    asm volatile("{\n.reg .pred p;\nsetp.ne.u32 p, %5, 0;\n@p ld.shared.v4.b32 {%0,%1,%2,%3}, [%4];\n}"
                 : "=r"(v.x), "=r"(v.y), "=r"(v.z), "=r"(v.w) : "r"(a), "r"((uint32_t)on) : "memory");
    return v;
}
__device__ __forceinline__ void stsf_if(uint32_t a, float v, bool on) {
    asm volatile("{\n.reg .pred p;\nsetp.ne.u32 p, %2, 0;\n@p st.shared.f32 [%0], %1;\n}" ::"r"(a), "f"(v), "r"((uint32_t)on) : "memory");
}
__device__ __forceinline__ void sts16(uint32_t a, uint16_t v) { asm volatile("st.shared.b16 [%0], %1;" ::"r"(a), "h"(v) : "memory"); }
__device__ __forceinline__ void sts32(uint32_t a, uint32_t v) { asm volatile("st.shared.b32 [%0], %1;" ::"r"(a), "r"(v) : "memory"); }
__device__ __forceinline__ void stsf(uint32_t a, float v) { asm volatile("st.shared.f32 [%0], %1;" ::"r"(a), "f"(v) : "memory"); }
__device__ __forceinline__ void sts64(uint32_t a, uint32_t x, uint32_t y) {
    asm volatile("st.shared.v2.b32 [%0], {%1,%2};" ::"r"(a), "r"(x), "r"(y) : "memory");
}
__device__ __forceinline__ void sts128(uint32_t a, uint4 v) {
    asm volatile("st.shared.v4.b32 [%0], {%1,%2,%3,%4};" ::"r"(a), "r"(v.x), "r"(v.y), "r"(v.z), "r"(v.w) : "memory");
}
__device__ __forceinline__ uint32_t pack_bf16(float lo, float hi) {
    uint32_t r; asm("cvt.rn.bf16x2.f32 %0, %1, %2;" : "=r"(r) : "f"(hi), "f"(lo)); return r;
}
__device__ __forceinline__ float bf_lo(uint32_t v) { return __uint_as_float(v << 16); }
__device__ __forceinline__ float bf_hi(uint32_t v) { return __uint_as_float(v & 0xffff0000u); }
__device__ __forceinline__ float ex2(float x) { float y; asm("ex2.approx.ftz.f32 %0, %1;" : "=f"(y) : "f"(x)); return y; }
__device__ __forceinline__ uint32_t timer_ns() { uint32_t t; asm volatile("mov.u32 %0, %%globaltimer_lo;" : "=r"(t)); return t; }
__device__ __forceinline__ void bar_consumers() { asm volatile("bar.sync 1, 256;" ::: "memory"); }

__device__ __forceinline__ uint32_t tagf(float v, uint32_t tag) { return (__float_as_uint(v) & 0xffffff00u) | tag; }
__device__ __forceinline__ uint2 ld_rlx2(const float* p) {
    uint2 v; asm volatile("ld.relaxed.gpu.global.v2.b32 {%0,%1}, [%2];" : "=r"(v.x), "=r"(v.y) : "l"(p) : "memory"); return v;
}
__device__ __forceinline__ float untag(uint32_t v) { return __uint_as_float(v & 0xffffff00u); }

__device__ __forceinline__ uint32_t slot_off(int item) { return (uint32_t)(item % NSLOT) * SLOT; }

template <bool TRANS, bool WAIT = true>
__device__ __forceinline__ void tile_mma(uint32_t sb, int item, uint32_t in, int w, int lane, float (&acc)[2][2]) {
    const int g = lane >> 2, t = lane & 3;
    float c[4][4];
#pragma unroll
    for (int i = 0; i < 16; i++) (&c[0][0])[i] = 0.f;
    uint32_t a[16];
    const uint32_t ia = in + (g & 3) * 272 + t * 4;
#pragma unroll
    for (int i = 0; i < 16; i++) a[i] = lds32(ia + i * 16);
    const uint32_t s0 = sb + slot_off(item), s1 = sb + slot_off(item + 1);
    if (TRANS) {
        const int r = (lane & 7) + (lane & 8);
        const int ch = 2 * (w & 3) + (lane >> 4);
        const uint32_t off = (WAIT ? (w >> 2) * 8192 + r * 128 : (w >> 2) * 128 + r * 256) + ((ch ^ (lane & 7)) << 4);
#pragma unroll
        for (int kk = 0; kk < 8; kk++) {
            if (WAIT && (kk & 3) == 0) mbar_wait(sb + SM_FULL + (item + (kk >> 2)) * 8);
            uint32_t r0, r1, r2, r3;
            ldsm4t(((kk >> 2) ? s1 : s0) + off + (kk & 3) * (WAIT ? 2048 : 4096), r0, r1, r2, r3);
            mma16816(c[2 * (kk & 1)],     a[2 * kk], 0u, a[2 * kk + 1], 0u, r0, r1);
            mma16816(c[2 * (kk & 1) + 1], a[2 * kk], 0u, a[2 * kk + 1], 0u, r2, r3);
        }
    } else {
        mbar_wait(sb + SM_FULL + (item + (w >> 2)) * 8);
        const int r = 16 * (w & 3) + (lane & 7) + ((lane >> 4) << 3);
        const uint32_t base = ((w >> 2) ? s1 : s0) + r * 128 + ((((lane >> 3) & 1) ^ (lane & 7)) << 4);
#pragma unroll
        for (int kk = 0; kk < 8; kk++) {
            uint32_t r0, r1, r2, r3;
            ldsm4((base ^ ((kk & 3) << 5)) + (kk >> 2) * 8192, r0, r1, r2, r3);
            mma16816(c[2 * (kk & 1)],     a[2 * kk], 0u, a[2 * kk + 1], 0u, r0, r1);
            mma16816(c[2 * (kk & 1) + 1], a[2 * kk], 0u, a[2 * kk + 1], 0u, r2, r3);
        }
    }
    __syncwarp();
    if (lane == 0) {
        mbar_arrive(sb + SM_EMPTY + item * 8);
        mbar_arrive(sb + SM_EMPTY + (item + 1) * 8);
    }
    acc[0][0] = c[0][0] + c[2][0]; acc[0][1] = c[0][1] + c[2][1];
    acc[1][0] = c[1][0] + c[3][0]; acc[1][1] = c[1][1] + c[3][1];
}

__device__ __forceinline__ void publish(float* dst, int w, int lane, const float (&acc)[2][2], uint32_t tag) {
    if (lane < 16)
        asm volatile("st.relaxed.gpu.global.v4.b32 [%0], {%1,%2,%3,%4};" ::"l"(dst + w * 64 + lane * 4),
                     "r"(tagf(acc[0][0], tag)), "r"(tagf(acc[0][1], tag)), "r"(tagf(acc[1][0], tag)), "r"(tagf(acc[1][1], tag)) : "memory");
}

__device__ __forceinline__ void gather(const float* part, uint32_t in, int tid, uint32_t tag) {
    const float* p = part + tid * 2;
    uint2 v0, v1, v2, v3;
    int it = 0;
    while (true) {
        v0 = ld_rlx2(p); v1 = ld_rlx2(p + 512); v2 = ld_rlx2(p + 1024); v3 = ld_rlx2(p + 1536);
        uint32_t bad = ((v0.x ^ tag) | (v0.y ^ tag) | (v1.x ^ tag) | (v1.y ^ tag) |
                        (v2.x ^ tag) | (v2.y ^ tag) | (v3.x ^ tag) | (v3.y ^ tag)) & 0xffu;
        if (__all_sync(0xffffffffu, bad == 0)) break;
        if (++it > SPIN_LIMIT) __trap();
    }
    float x = (untag(v0.x) + untag(v1.x)) + (untag(v2.x) + untag(v3.x));
    float y = (untag(v0.y) + untag(v1.y)) + (untag(v2.y) + untag(v3.y));
    sts32(in + ((tid >> 3) & 3) * 272 + (tid >> 5) * 32 + (tid & 1) * 16 + (tid & 6) * 2, pack_bf16(x, y));
    bar_consumers();
}

constexpr uint32_t EMPTY = 0xffffffffu;
__device__ __forceinline__ void st_rlx(uint32_t* p, uint32_t v) {
    asm volatile("st.relaxed.gpu.global.b32 [%0], %1;" ::"l"(p), "r"(v) : "memory");
}
__device__ __forceinline__ void st_rlx_if(uint64_t p, uint32_t v, bool on) {
    asm volatile("{\n.reg .pred p;\nsetp.ne.u32 p, %2, 0;\n@p st.relaxed.gpu.global.b32 [%0], %1;\n}" ::"l"(p), "r"(v), "r"((uint32_t)on) : "memory");
}
__device__ __forceinline__ void st_rlx2(uint32_t* p, uint32_t v0, uint32_t v1) {
    asm volatile("st.relaxed.gpu.global.v2.b32 [%0], {%1,%2};" ::"l"(p), "r"(v0), "r"(v1) : "memory");
}
__device__ __forceinline__ void ld_rlx4_if(uint4& v, const void* p, bool need) {
    asm volatile("{\n.reg .pred p;\nsetp.ne.u32 p, %5, 0;\n@p ld.relaxed.gpu.global.v4.b32 {%0,%1,%2,%3}, [%4];\n}"
                 : "+r"(v.x), "+r"(v.y), "+r"(v.z), "+r"(v.w) : "l"(p), "r"((uint32_t)need) : "memory");
}

template <int HALF, class F>
__device__ __forceinline__ bool refetch(uint4 (&x)[8], int lane, F addr) {
    uint32_t m[8], m0 = 0, m1 = 0;
#pragma unroll
    for (int i = 0; i < 8; i++) {
        m[i] = max(max(x[i].x, x[i].y), max(x[i].z, x[i].w));
        if (i < HALF) m0 = max(m0, m[i]); else m1 = max(m1, m[i]);
    }
    if (!__any_sync(0xffffffffu, (m0 == EMPTY && lane < 16) || m1 == EMPTY)) return false;
#pragma unroll
    for (int i = 0; i < 8; i++) ld_rlx4_if(x[i], addr(i), m[i] == EMPTY && (i >= HALF || lane < 16));
    return true;
}

__device__ __forceinline__ unsigned read_counter(const unsigned* cnt) {
    unsigned v;
    asm volatile("ld.relaxed.gpu.global.u32 %0, [%1];" : "=r"(v) : "l"(cnt) : "memory");
    return v;
}
__device__ __forceinline__ unsigned epoch_of(unsigned cnt) {
    asm volatile("" : "+r"(cnt) :: "memory");
    return cnt / NCTA + 1;
}
__device__ __forceinline__ uint32_t epoch_tag(unsigned epoch) { return (epoch & 0x7fu) | 0x80u; }

__device__ __forceinline__ void signal_and_wait(unsigned* cnt, unsigned target, int lane, uint32_t sb) {
    if (lane == 0) asm volatile("red.release.gpu.global.add.u32 [%0], 1;" ::"l"(cnt) : "memory");
    if (lane == 0) TL(30 + (((size_t)cnt >> 2) & 1));
    int it = 0;
    while (true) {
        unsigned v;
        asm volatile("ld.acquire.gpu.global.u32 %0, [%1];" : "=r"(v) : "l"(cnt) : "memory");
        if (__all_sync(0xffffffffu, (int)(v - target) >= 0)) break;
        if (++it > SPIN_LIMIT) __trap();
    }
    asm volatile("fence.proxy.async.global;" ::: "memory");
}

__global__ void __cluster_dims__(2, 1, 1) __launch_bounds__(NTHR, 1)
fused_decode_kernel(const __nv_bfloat16* __restrict__ xA, const __nv_bfloat16* __restrict__ xB,
                    const __nv_bfloat16* __restrict__ wqB, const __nv_bfloat16* __restrict__ wqA,
                    const __nv_bfloat16* __restrict__ Kc, const __nv_bfloat16* __restrict__ Vc,
                    __nv_bfloat16* __restrict__ out, Scratch* gs, const __grid_constant__ Maps maps) {
    extern __shared__ __align__(1024) unsigned char smem_raw[];
    const uint32_t sb = smem_u32(smem_raw);
    const int tid = threadIdx.x, lane = tid & 31;
    const int cta = blockIdx.x, h = cta >> 2, j = cta & 3;
    const size_t kv_off = (size_t)blockIdx.x * 4096 * 128;
    const uint32_t trow = threadIdx.x >> 4;
    const uint32_t tile_src = trow * (8192 - 256) + (threadIdx.x * 16 + ((blockIdx.x * 0x100040u) & 0x301f00u));
    const uint32_t tile_dst = sb + ((threadIdx.x ^ (trow & 7)) << 4);
    auto lsu_tile = [&](const __nv_bfloat16* W, int item) {
#pragma unroll
        for (int q = 0; q < 8; q++)
            asm volatile("cp.async.cg.shared.global [%0], [%1], 16;" ::"r"(tile_dst + item * SLOT + q * 4096),
                         "l"(reinterpret_cast<const char*>(W + q * 16 * 4096) + tile_src) : "memory");
        asm volatile("cp.async.commit_group;" ::: "memory");
    };
    if (tid < 256) lsu_tile(wqB, IT_WQB);
    if (tid == 0) TLX(32);
    if (tid == PFSTARTER) {
        if (KPF) asm volatile("cp.async.bulk.prefetch.L2.global [%0], %1;" ::"l"(Kc + kv_off), "r"(SLOT) : "memory");
        TLX(0);
    }
    uint32_t tnext = timer_ns() + (NFIRST + KPF) * PACE - OFFS;
    const unsigned cnt1 = read_counter(&gs->cnt[1]);
    uint4 xv;
    if (tid < 128) {
        const __nv_bfloat16* x = (tid < 64 ? xB : xA) + ((tid >> 4) & 3) * 512 + j * 128 + (tid & 15) * 8;
        xv = __ldg(reinterpret_cast<const uint4*>(x));
    }
    if (tid == 0) TLX(21);
    const int w = __shfl_sync(0xffffffffu, tid >> 5, 0);
    const int pr = cta >> 1;
    const int slice = pr < 4 ? pr : pr < 36 ? 4 + ((pr - 4) & 7) * 4 + ((pr - 4) >> 3) : 36 + (pr - 36) % 7 * 4 + (pr - 36) / 7;

#define STAGM 0
    const int stag = ((STAGM == 0 ? (cta & 1) * 3 : STAGM == 1 ? slice & 3 : STAGM == 2 ? (slice >> 2) & 3 : (slice & 1) * 2 + (cta & 1)) * 2 - 3) * STAG / 6;
    if (w == 10) {
        const uint32_t tz = tnext - (NFIRST + KPF) * PACE + stag;
        if (lane == 0) sts64(sb + SM_PACE, tz, PACE * 16);
        asm volatile(BAR2 ::: "memory");
        if (lane == 0) {
            constexpr int win[] = {WINS / 1000000, WINS / 10000 % 100, WINS / 100 % 100, WINS % 100};
            constexpr int ls[] = {(int)(LSTAR / 1000000000 * 10), (int)(LSTAR / 1000000 % 1000 * 10), (int)(LSTAR / 1000 % 1000 * 10), (int)(LSTAR % 1000 * 10)};
            auto pos = [](int i) { return i < IT_Q ? i : i < IT_OP ? i - 2 : i - 4; };
            int slope = 0;
#pragma unroll
            for (int k = 0; k < 4; k++) {
                if (win[k] == 0) break;
                const int c = pos(win[k]);
                uint32_t acc = 0;
#pragma unroll
                for (int p = c; p < c + 4; p++) {
                    mbar_wait(sb + SM_FULL + (p < IT_Q ? p : p < IT_OP - 2 ? p + 2 : p + 4) * 8);
                    acc += timer_ns() - tz - p * PACE - (((p - ANCH) * slope) >> 4);
                }
                if (k == 0) mbar_wait(sb + SM_FULL + IT_Q * 8);
                asm volatile("red.relaxed.gpu.global.add.u32 [%0], %1;" ::"l"(&gs->late[k]), "r"((1u << 24) + min(acc >> 2, 65535u)) : "memory");
                uint32_t v;
                int it = 0;
                do { v = read_counter(&gs->late[k]); } while ((v >> 24) != NCTA && ++it < 1000);
                const int d = (v & 0xffffffu) >> 7;
                slope = max(-320, min(320, slope + (d - ls[k]) * (GAIN * 2) / (2 * (c - ANCH) + 3)));
                sts64(sb + SM_PACE, tz - ((ANCH * slope) >> 4), PACE * 16 + slope);
            }
        }
        return;
    }
    if (w >= 8) {
        if (w == 8) {
            asm volatile(BAR2 ::: "memory");
            const uint64_t pol = evict_first();
            int slot = PFIRST, tail = PFIRST - INFLIGHT;
            uint32_t np = PFIRST + KPF, tap = 0;
            auto due = [&](uint32_t p) {
                uint32_t a, b;
                asm volatile("ld.volatile.shared.v2.b32 {%0,%1}, [%2];" : "=r"(a), "=r"(b) : "r"(sb + SM_PACE) : "memory");
                return a + ((p * b) >> 4);
            };
#pragma unroll 1
            for (int i = PFIRST; i < NITEM; i++) {
                const uint32_t dst = sb + slot * SLOT, bar = sb + SM_FULL + i * 8;
                if (++slot == NSLOT) slot = 0;
                if ((i & ~1) == IT_Q || (i & ~1) == IT_OP) continue;
                const bool ckv = i >= IT_C && i < IT_K1, wo = i >= IT_WO;
                const bool tiled = ckv || i < IT_K0 || i >= IT_WUV;
                const CUtensorMap* tm = &maps.wqB + (i < IT_K0 ? (i >> 1) : ckv ? 6 : wo ? 4 + (slice >> 5) : 3);
                const int c0 = wo ? (slice & 31) * 16 : i >= IT_WUV ? cta * 32 : 0;
                const int c1 = i < IT_K0 ? j * 128 + (i & 1) * 64 : ckv ? cta * 128 + (i - IT_C) * 16 : 0;
                const int c2 = i < IT_K0 ? h * 2 : ckv ? 0 : wo ? (i - IT_WO) * 4 + (j & 1) * 2 : i & 1;
                const int c = i < IT_Q ? i - IT_K0 : i < IT_V0 ? i - IT_K1 + 8 : i < IT_OP ? i - IT_V0 : i - IT_V1 + 8;
                const __nv_bfloat16* src = (i < IT_V0 ? Kc : Vc) + kv_off + (size_t)c * (SLOT / 2);
                if (i >= NSLOT) mbar_wait(sb + SM_EMPTY + (i - NSLOT) * 8);
                if (tail >= 2 * LSU0) mbar_wait(sb + SM_FULL + tail * 8);
                ++tail;
                if (tail == IT_Q || tail == IT_OP) tail += 2;
                if (i >= DRAIN_AT) mbar_wait(sb + SM_FULL + (i - DRAIN) * 8);
                if (i == NITEM - 1) mbar_wait(sb + SM_FULL + BAR_PEER * 8);
                if (i == NITEM - 1 - (slice < 32 ? AEARLY : BEARLY)) {
                    while (__all_sync(0xffffffffu, (int)(timer_ns() - (due(np) + tap - GLEAD)) < 0)) {}
                    asm volatile("bar.arrive 4, 64;" ::: "memory");
                }
                if (!KPF || i != IT_K0) {
                    while (__all_sync(0xffffffffu, (int)(timer_ns() - (due(np) + tap)) < 0)) {}
                    ++np;
                    if (i == TAPER_AT) tap = TAPER - stag;
                    tnext += PACE;
                    if (i >= TAPER_AT && i < TAPER_AT + TAPER_N) tnext += TAPER;
                }
                if (lane == 0) {
                    TLX(32 + i);
                    if (i == NITEM - 1) tma3d_pair(dst + (j & 1) * (IT_W2 - i) * SLOT, tm, c0, c1, c2, bar + (j & 1) * (IT_W2 - i) * 8, pol);
                    else if (tiled) tma3d(dst, tm, c0, c1, c2, bar, pol);
                    else bulk_load(dst, src, SLOT, bar, pol);
                }
            }
        } else {
            if (lane == 0) {
                mbar_init(sb + SM_FULL + IT_W2 * 8, 1);
                mbar_init(sb + SM_FULL + BAR_X * 8, 1);
                mbar_init(sb + SM_FULL + BAR_PEER * 8, 1);
                mbar_expect_tx(sb + SM_FULL + IT_W2 * 8, SLOT);
                mbar_expect_tx(sb + SM_FULL + BAR_X * 8, SLOT + 4096);
                mbar_expect_tx(sb + SM_FULL + BAR_PEER * 8, 8);
                asm volatile("fence.mbarrier_init.release.cluster;" ::: "memory");
            }
            if (lane < sizeof(Maps) / 128 - 1) asm volatile("prefetch.tensormap [%0];" ::"l"(&maps.wqA + lane) : "memory");
            asm volatile(BAR2 ::: "memory");
            asm volatile("bar.sync 3, 288;" ::: "memory");
            const unsigned epoch = epoch_of(cnt1);
            if (lane == 0) TL(9);
            signal_and_wait(&gs->cnt[0], epoch * NCTA, lane, sb);
            if (lane == 0) {
                TL(2);
                const uint4* q = gs->q[cta >> 5];
                uint32_t t1 = timer_ns();
#pragma unroll 1
                for (int i = 0; i < QN; i++) {
                    while ((int)(timer_ns() - t1) < 0) {}
                    t1 += QGAP;
                    bulk_load_nohint(sb + slot_off(IT_Q) + i * (2 * SLOT / QN), q + i * (2048 / QN), 2 * SLOT / QN,
                                     sb + SM_FULL + (IT_Q + i / (QN / 2)) * 8);
                }
            }
            asm volatile("bar.sync 3, 288;" ::: "memory");
            if (lane == 0) TL(13);
            signal_and_wait(&gs->cnt[1], epoch * NCTA, lane, sb);
            mbar_wait(sb + SM_EMPTY + (IT_OP - NSLOT) * 8);
            mbar_wait(sb + SM_EMPTY + (IT_OP + 1 - NSLOT) * 8);
            if (lane == 0) {
                TL(3);
                const uint4* op = gs->op[cta];
                bulk_load_nohint(sb + SM_MX, gs->stat[h], 1024, sb + SM_FULL + IT_OP * 8);
                uint32_t t1 = timer_ns();
#pragma unroll 1
                for (int i = 0; i < OPN; i++) {
                    while ((int)(timer_ns() - t1) < 0) {}
                    t1 += OPGAP;
                    bulk_load_nohint(sb + slot_off(IT_OP) + i * (2 * SLOT / OPN), op + i * (2048 / OPN), 2 * SLOT / OPN,
                                     sb + SM_FULL + (IT_OP + i / (OPN / 2)) * 8);
                }
            }
            mbar_wait(sb + SM_FULL + LATAT * 8);
            if (lane == 0) bulk_load_nohint(sb + SM_LAT, gs->lat[h], 4096, sb + SM_FULL + BAR_LAT * 8);
            mbar_wait(sb + SM_EMPTY + (IT_X - NSLOT) * 8);
            mbar_wait(sb + SM_EMPTY + (IT_X + 1 - NSLOT) * 8);
            asm volatile("bar.sync 4, 64;" ::: "memory");
            if (lane == 0) {
                TL(27);
                bulk_load_nohint(sb + slot_off(IT_X), gs->x[slice >> 5][(j & 1) * 12], SLOT + 4096, sb + SM_FULL + BAR_X * 8);
            }
        }
        const uint32_t oo  = __shfl_sync(0xffffffffu, (lane >> 3) * 2048 + slice * 32 + (j & 1) * 16 + (lane & 7) * 2, lane);
        const uint32_t src = __shfl_sync(0xffffffffu, sb + SM_FIN + ((j ^ w ^ 1) & 1) * 1536 + lane * 48, lane);
        const uint32_t sr2 = __shfl_sync(0xffffffffu, sb + SM_FIN + 3072 + lane * 80, lane);
        const uint32_t to  = w == 8 ? map_cta(sb, (j & 1) ^ 1) : sb;
        const uint32_t rcv = __shfl_sync(0xffffffffu, to + SM_RCV + lane * 4, lane);
        const uint32_t fin = __shfl_sync(0xffffffffu, to + SM_FULL + BAR_FIN * 8, lane);
        mbar_wait(sb + SM_FULL + (NITEM - 3) * 8);
        asm volatile("bar.sync 5, 320;" ::: "memory");
        const float4 p0 = ldsf4(src), p1 = ldsf4(src + 16);
        float sum = ((p0.x + p0.y) + (p0.z + p0.w)) + ((p1.x + p1.y) + (p1.z + p1.w));
        if (w == 8) {
            st_async32(rcv, __float_as_uint(sum), fin);
        } else {
            __nv_bfloat16* dst = reinterpret_cast<__nv_bfloat16*>(reinterpret_cast<char*>(out) + oo);
            mbar_wait(sb + SM_FULL + BAR_FIN * 8);
            if (lane == 0) TLX(154);
            sum += ldsf(rcv);
            asm volatile("bar.sync 7, 288;" ::: "memory");
            const float4 q0 = ldsf4(sr2), q1 = ldsf4(sr2 + 16), q2 = ldsf4(sr2 + 32), q3 = ldsf4(sr2 + 48);
            *dst = __float2bfloat16((((q0.x + sum) + q0.y) + (q0.z + q0.w) + ((q1.x + q1.y) + (q1.z + q1.w))) +
                                    (((q2.x + q2.y) + (q2.z + q2.w)) + ((q3.x + q3.y) + (q3.z + q3.w))));
            if (lane == 0) TLX(4);
        }
        return;
    }

    const int g = lane >> 2, t = lane & 3;
    const uint32_t in0 = sb + SM_IN0, in1 = sb + SM_IN1;
    auto xpos = [](int hh) { return (hh & 4) * 4 + (((hh >> 3) + (hh >> 2 & 1)) & 3) * 4 + (hh & 3); };
    const int ba = cta >> 5, ha = cta & 31;
    uint32_t* const ctx_dst = &gs->x[1][xpos(h)][(j * 4 + (w & 3)) * 16 + ((g ^ (w & 2)) & 3) * 4 + ((t - w) & 3)];
    uint32_t* const o_dst = &gs->x[0][xpos(ha)][ba * 64 + ((tid & 60) ^ ((ba & 1) * 16)) + ((t - g) & 3)];
    uint32_t* const lat_dst = &gs->lat[h][g & 3][j * 64 + ((w >> 1) ^ (g & 1)) * 16 + t * 4 + ((w * 2 ^ t) & 2)];
    {
        if (lane == 0) {
            const uint32_t bars = sb + (w < 4 ? SM_EMPTY : SM_FULL + NFIRST * 8) + (w & 3) * 14 * 8;
            const uint32_t cnt = w < 4 ? 8 : 1;
#pragma unroll
            for (int i = 0; i < 14; i++) mbar_init(bars + i * 8, cnt);
            if (w >= 4) {
#pragma unroll
                for (int i = 0; i < 14; i++)
                    mbar_expect_tx(bars + i * 8, (i == (IT_OP - NFIRST) % 14 && w == 4 + (IT_OP - NFIRST) / 14) ? SLOT + 1024 :
                                                 (i >= 12 && w == 7) ? (i == 12 ? 4096 : 128) : SLOT);
            }
            asm volatile("fence.mbarrier_init.release.cluster;" ::: "memory");
        }
        if (tid == 0) TL(22);
        if (T2) while (__all_sync(0xffffffffu, (int)(timer_ns() - (tnext - ((NFIRST + KPF) * PACE - OFFS) + T2)) < 0)) {}
        if (tid == 0) { TLX(34); TLX(35); }
        lsu_tile(wqA, IT_WQA);
        asm volatile(BAR2 ::: "memory");
        if (lane < 16) st_rlx2(lat_dst, EMPTY, EMPTY);
        if (lane >= 16 && w < 4) st_rlx(ctx_dst, EMPTY);
        if (w >= 6) st_rlx(o_dst, EMPTY);
        if (cta == 0 && w == 5) st_rlx(&gs->late[lane], 0u);
        if (tid < 128) sts128((tid < 64 ? in0 : in1) + ((tid >> 4) & 3) * 272 + (tid & 15) * 16, xv);
        if (LSU0) asm volatile("cp.async.wait_group %0;" ::"n"(LSU0 - 1) : "memory");
    }
    bar_consumers();
    const uint32_t tag = epoch_tag(epoch_of(cnt1));
    if (tid == 0) TL(23);

    float acc[2][2];
    tile_mma<true, !LSU0>(sb, IT_WQB, in0, w, lane, acc);
    if (tid == 0) TL(24);
    publish(gs->part[0][cta], w, lane, acc, tag);
    if (tid == 0) TL(6);
    asm volatile("cp.async.wait_group 0;" ::: "memory");
    bar_consumers();
    if (tid == 0) { TLX(98); TLX(99); }
    tile_mma<true, LSU0 != 2>(sb, IT_WQA, in1, w, lane, acc);
    publish(gs->part[1][cta], w, lane, acc, tag);
    if (tid == 0) TL(7);
    bar_consumers();

    const float SC = 0.08838834764831845f * 1.4426950408889634f;
    gather(gs->part[0][h * 4], in0, tid, tag);
    if (tid == 0) TL(8);
    tile_mma<false>(sb, IT_WUK, in0, w, lane, acc);
    if (tid == 0) TL(25);
    if (lane < 16) {
        uint32_t* q = reinterpret_cast<uint32_t*>(gs->q[g]) + (2 * j + (w >> 2)) * 1024 + h * 32 + t;
        const int ch = 2 * (w & 3);
        q[((ch) ^ (h & 7)) * 4]     = pack_bf16(acc[0][0] * SC, acc[0][1] * SC);
        q[((ch + 1) ^ (h & 7)) * 4] = pack_bf16(acc[1][0] * SC, acc[1][1] * SC);
    }
    __syncwarp();
    asm volatile("bar.arrive 3, 288;" ::: "memory");
    gather(gs->part[1][ha * 4], in1, tid, tag);
    if (tid == 0) TL(28);

    uint32_t qf[16];
#pragma unroll
    for (int c = 0; c < 8; c++) {
        qf[2 * c]     = lds32(in1 + ba * 272 + ((c ^ g) << 4) + t * 4);
        qf[2 * c + 1] = lds32(in1 + ba * 272 + 128 + ((c ^ g) << 4) + t * 4);
    }
    const uint32_t sc_w = sb + SM_SC + w * 512;
    auto k_item = [&](int item, uint32_t sc) {
        mbar_wait(sb + SM_FULL + item * 8);
        const uint32_t base = sb + slot_off(item) + ((lane & 7) + (lane & 8)) * 256 + ((lane >> 4) << 7);
        float s[4][4];
#pragma unroll
        for (int T = 0; T < 4; T++) { s[T][0] = s[T][1] = s[T][2] = s[T][3] = 0.f; }
#pragma unroll
        for (int c = 0; c < 8; c++) {
            const uint32_t a = base + ((c ^ (lane & 7)) << 4);
#pragma unroll
            for (int T = 0; T < 4; T++) {
                uint32_t r0, r1, r2, r3;
                ldsm4(a + T * 4096, r0, r1, r2, r3);
                mma16816(s[T], r0, r1, r2, r3, qf[2 * c], qf[2 * c + 1]);
            }
        }
        __syncwarp();
        if (lane == 0) mbar_arrive8(sb + SM_EMPTY + item * 8);
        if (t == (g >> 1)) {
#pragma unroll
            for (int T = 0; T < 4; T++) {
                stsf(sc + (16 * T + g) * 4,     (g & 1) ? s[T][1] : s[T][0]);
                stsf(sc + (16 * T + g + 8) * 4, (g & 1) ? s[T][3] : s[T][2]);
            }
        }
    };
    k_item(IT_K0 + w, sc_w);
    if (tid == 224) TL(10);

    {
        float s[2][2][4];
#pragma unroll
        for (int i = 0; i < 16; i++) (&s[0][0][0])[i] = 0.f;
        mbar_wait(sb + SM_FULL + IT_Q * 8);
        mbar_wait(sb + SM_FULL + (IT_Q + 1) * 8);
        if (tid == 0) TLX(96 + IT_Q);
        mbar_wait(sb + SM_FULL + (IT_C + w) * 8);
        const uint32_t cb0 = sb + slot_off(IT_C + w) + ((lane & 7) + ((lane >> 4) << 3)) * 128;
        const uint32_t cx = (((lane >> 3) & 1) ^ (lane & 7)) << 4;
        const uint32_t qr = ((lane & 7) + (lane & 8)) * 128;
        const uint32_t qx = ((lane >> 4) ^ (lane & 7)) << 4;
#pragma unroll
        for (int cb = 0; cb < 8; cb++) {
            const uint32_t qb = sb + slot_off(IT_Q + (cb >> 2)) + (cb & 3) * 4096 + qr;
#pragma unroll
            for (int k4 = 0; k4 < 4; k4++) {
                uint32_t b0, b1, b2, b3, a0, a1, a2, a3;
                ldsm4(cb0 + cb * 2048 + (cx ^ (k4 << 5)), b0, b1, b2, b3);
                ldsm4(qb + (qx ^ (k4 << 5)), a0, a1, a2, a3);
                mma16816(s[0][0], a0, a1, a2, a3, b0, b1);
                mma16816(s[0][1], a0, a1, a2, a3, b2, b3);
                ldsm4(qb + 2048 + (qx ^ (k4 << 5)), a0, a1, a2, a3);
                mma16816(s[1][0], a0, a1, a2, a3, b0, b1);
                mma16816(s[1][1], a0, a1, a2, a3, b2, b3);
            }
        }
        __syncwarp();
        if (lane == 0) { mbar_arrive(sb + SM_EMPTY + IT_Q * 8); mbar_arrive(sb + SM_EMPTY + (IT_Q + 1) * 8); }
#pragma unroll
        for (int r = 0; r < 4; r++) {
            const int mt = r >> 1, hi = (r & 1) * 2;
            float m = fmaxf(fmaxf(s[mt][0][hi], s[mt][0][hi + 1]), fmaxf(s[mt][1][hi], s[mt][1][hi + 1]));
            m = fmaxf(m, __shfl_xor_sync(0xffffffffu, m, 1));
            m = fmaxf(m, __shfl_xor_sync(0xffffffffu, m, 2));
            if (t == 0) stsf(sb + SM_MX + (8 * r + g) * 32 + w * 4, m);
        }
        bar_consumers();
        if (tid == 0) TL(11);
        uint32_t pf[2][4];
#pragma unroll
        for (int r = 0; r < 4; r++) {
            const int mt = r >> 1, hi = r & 1;
            const float4 m0 = ldsf4(sb + SM_MX + (8 * r + g) * 32), m1 = ldsf4(sb + SM_MX + (8 * r + g) * 32 + 16);
            const float m = fmaxf(fmaxf(fmaxf(m0.x, m0.y), fmaxf(m0.z, m0.w)), fmaxf(fmaxf(m1.x, m1.y), fmaxf(m1.z, m1.w)));
            const uint32_t p0 = pack_bf16(ex2(s[mt][0][2 * hi] - m), ex2(s[mt][0][2 * hi + 1] - m));
            const uint32_t p1 = pack_bf16(ex2(s[mt][1][2 * hi] - m), ex2(s[mt][1][2 * hi + 1] - m));
            pf[mt][hi] = p0; pf[mt][2 + hi] = p1;
            float l = (bf_lo(p0) + bf_hi(p0)) + (bf_lo(p1) + bf_hi(p1));
            l += __shfl_xor_sync(0xffffffffu, l, 1);
            l += __shfl_xor_sync(0xffffffffu, l, 2);
            if (t == 0) stsf(sb + SM_SUM + (8 * r + g) * 32 + w * 4, l);
        }
        sts128(sb + SM_PF + (w * 2 + 0) * 512 + lane * 16, make_uint4(pf[0][0], pf[0][1], pf[0][2], pf[0][3]));
        sts128(sb + SM_PF + (w * 2 + 1) * 512 + lane * 16, make_uint4(pf[1][0], pf[1][1], pf[1][2], pf[1][3]));
        bar_consumers();
        if (w == 0) {
            const float4 m0 = ldsf4(sb + SM_MX + lane * 32), m1 = ldsf4(sb + SM_MX + lane * 32 + 16);
            const float4 l0 = ldsf4(sb + SM_SUM + lane * 32), l1 = ldsf4(sb + SM_SUM + lane * 32 + 16);
            const float m = fmaxf(fmaxf(fmaxf(m0.x, m0.y), fmaxf(m0.z, m0.w)), fmaxf(fmaxf(m1.x, m1.y), fmaxf(m1.z, m1.w)));
            const float l = ((l0.x + l0.y) + (l0.z + l0.w)) + ((l1.x + l1.y) + (l1.z + l1.w));
            gs->stat[lane][cta] = make_float2(m, l);
        }
        float o[2][8][4];
#pragma unroll
        for (int i = 0; i < 64; i++) (&o[0][0][0])[i] = 0.f;
        const uint32_t vr = w * 2048 + ((lane & 7) + (lane & 8)) * 128;
        const uint32_t vx = ((lane >> 4) ^ (lane & 7)) << 4;
#pragma unroll
        for (int ks = 0; ks < 8; ks++) {
            const uint4 p0 = lds128(sb + SM_PF + (ks * 2 + 0) * 512 + lane * 16);
            const uint4 p1 = lds128(sb + SM_PF + (ks * 2 + 1) * 512 + lane * 16);
            const uint32_t vb = sb + slot_off(IT_C + ks) + vr;
#pragma unroll
            for (int n2 = 0; n2 < 4; n2++) {
                uint32_t b0, b1, b2, b3;
                ldsm4t(vb + (vx ^ (n2 << 5)), b0, b1, b2, b3);
                mma16816(o[0][2 * n2],     p0.x, p0.y, p0.z, p0.w, b0, b1);
                mma16816(o[0][2 * n2 + 1], p0.x, p0.y, p0.z, p0.w, b2, b3);
                mma16816(o[1][2 * n2],     p1.x, p1.y, p1.z, p1.w, b0, b1);
                mma16816(o[1][2 * n2 + 1], p1.x, p1.y, p1.z, p1.w, b2, b3);
            }
            __syncwarp();
            if (lane == 0) mbar_arrive(sb + SM_EMPTY + (IT_C + ks) * 8);
        }
        if (tid == 0) TL(12);
        mbar_wait(sb + SM_FULL + (IT_K1 + STG_AT + (w >> STG_SH)) * 8);
#pragma unroll
        for (int r = 0; r < 4; r++) {
            const int mt = r >> 1, hi = (r & 1) * 2;
            uint4* dst = gs->op[(8 * r + g) * 4 + (w >> 1)] + (cta >> 6) * 1024 + (w & 1) * 512 + (cta & 63) * 8;
#pragma unroll
            for (int u = 0; u < 2; u++) {
                uint4 v;
                v.x = pack_bf16(o[mt][4 * u][hi],     o[mt][4 * u][hi + 1]);
                v.y = pack_bf16(o[mt][4 * u + 1][hi], o[mt][4 * u + 1][hi + 1]);
                v.z = pack_bf16(o[mt][4 * u + 2][hi], o[mt][4 * u + 2][hi + 1]);
                v.w = pack_bf16(o[mt][4 * u + 3][hi], o[mt][4 * u + 3][hi + 1]);
                dst[(t + 4 * u) ^ (cta & 7)] = v;
            }
        }
        if (tid == 0) TL(29);
        asm volatile("bar.arrive 3, 288;" ::: "memory");
    }

    k_item(IT_K1 + w, sc_w + 256);
    __syncwarp();
    {
        const float4 s = ldsf4(sc_w + lane * 16);
        float m = fmaxf(fmaxf(s.x, s.y), fmaxf(s.z, s.w));
#pragma unroll
        for (int d = 1; d < 32; d <<= 1) m = fmaxf(m, __shfl_xor_sync(0xffffffffu, m, d));
        if (lane == 0) stsf(sb + SM_ML + w * 4, m);
        bar_consumers();
        const float4 m0 = ldsf4(sb + SM_ML), m1 = ldsf4(sb + SM_ML + 16);
        m = fmaxf(fmaxf(fmaxf(m0.x, m0.y), fmaxf(m0.z, m0.w)), fmaxf(fmaxf(m1.x, m1.y), fmaxf(m1.z, m1.w))) * SC;
        const uint32_t p0 = pack_bf16(ex2(fmaf(s.x, SC, -m)), ex2(fmaf(s.y, SC, -m)));
        const uint32_t p1 = pack_bf16(ex2(fmaf(s.z, SC, -m)), ex2(fmaf(s.w, SC, -m)));
        float l = (bf_lo(p0) + bf_hi(p0)) + (bf_lo(p1) + bf_hi(p1));
#pragma unroll
        for (int d = 1; d < 32; d <<= 1) l += __shfl_xor_sync(0xffffffffu, l, d);
        if (lane == 0) stsf(sb + SM_ML + 32 + w * 4, l);
        sts64(sb + SM_PA + w * 256 + lane * 8, p0, p1);
        __syncwarp();
    }
    if (tid == 224) TL(14);

    float oa[4][4];
#pragma unroll
    for (int i = 0; i < 16; i++) (&oa[0][0])[i] = 0.f;
    auto v_item = [&](int item, uint32_t pa) {
        uint32_t p[8];
#pragma unroll
        for (int i = 0; i < 8; i++) p[i] = lds32(pa + i * 16 + t * 4);
        mbar_wait(sb + SM_FULL + item * 8);
        const uint32_t base = sb + slot_off(item) + ((lane & 7) + ((lane >> 4) << 3)) * 256 + ((lane & 8) << 4);
#pragma unroll
        for (int c = 0; c < 8; c++) {
            const uint32_t a = base + ((c ^ (lane & 7)) << 4);
            const uint32_t mask = ((c == (g ^ (2 * t))) ? 0x0000ffffu : 0u) | ((c == (g ^ (2 * t + 1))) ? 0xffff0000u : 0u);
#pragma unroll
            for (int T = 0; T < 4; T++) {
                uint32_t r0, r1, r2, r3;
                ldsm4t(a + T * 4096, r0, r1, r2, r3);
                mma16816(oa[T], r0, r1, r2, r3, p[2 * T] & mask, p[2 * T + 1] & mask);
            }
        }
        __syncwarp();
        if (lane == 0) mbar_arrive8(sb + SM_EMPTY + item * 8);
    };
    v_item(IT_V0 + w, sb + SM_PA + w * 256);
    if (tid == 224) TL(15);

    mbar_wait(sb + SM_FULL + IT_OP * 8);
    if (tid == 0) TLX(96 + IT_OP);
    if (w < 4) {
        const float2 st = ldsf2(sb + SM_MX + tid * 8);
        float m = st.x;
#pragma unroll
        for (int d = 1; d < 32; d <<= 1) m = fmaxf(m, __shfl_xor_sync(0xffffffffu, m, d));
        const uint32_t wb = pack_bf16(ex2(st.x - m), 0.f);
        float l = bf_lo(wb) * st.y;
#pragma unroll
        for (int d = 1; d < 32; d <<= 1) l += __shfl_xor_sync(0xffffffffu, l, d);
#pragma unroll
        for (int bb = 0; bb < 4; bb++) sts16(in0 + bb * 272 + tid * 2, bb == w ? (uint16_t)wb : (uint16_t)0);
        if (lane == 0) stsf(sb + SM_ML + 64 + w * 4, 1.f / l);
    }
    bar_consumers();
    tile_mma<true>(sb, IT_OP, in0, w, lane, acc);
    if (lane < 16) {
        const float inv = ldsf(sb + SM_ML + 64 + g * 4);
        const uint32_t v0 = pack_bf16(acc[0][0] * inv, acc[0][1] * inv), v1 = pack_bf16(acc[1][0] * inv, acc[1][1] * inv);
        st_rlx2(lat_dst, (t & 1) ? v1 : v0, (t & 1) ? v0 : v1);
    }
    if (tid == 0) TL(19);

    {
        const float4 l0 = ldsf4(sb + SM_ML + 32), l1 = ldsf4(sb + SM_ML + 48);
        const float inv = 1.f / (((l0.x + l0.y) + (l0.z + l0.w)) + ((l1.x + l1.y) + (l1.z + l1.w)));
        v_item(IT_V1 + w, sb + SM_PA + w * 256 + 128);
        const uint32_t so = sb + SM_PF + w * 512 + (16 * t + g) * 4;
        stsf(so,       (oa[0][0] + oa[1][0]) + (oa[2][0] + oa[3][0]));
        stsf(so + 32,  (oa[0][1] + oa[1][1]) + (oa[2][1] + oa[3][1]));
        stsf(so + 256, (oa[0][2] + oa[1][2]) + (oa[2][2] + oa[3][2]));
        stsf(so + 288, (oa[0][3] + oa[1][3]) + (oa[2][3] + oa[3][3]));
        if (w < 6) {
            asm volatile("bar.arrive 1, 256;" ::: "memory");
        } else {
            bar_consumers();
            float x = 0.f, y = 0.f;
#pragma unroll
            for (int i = 0; i < 8; i++) {
                const float2 v = ldsf2(sb + SM_PF + i * 512 + (tid & 63) * 8);
                x += v.x; y += v.y;
            }
            st_rlx(o_dst, pack_bf16(x * inv, y * inv));
            if (lane == 0) {
                const uint32_t to = map_cta(sb, w & 1);
                st_async32(to + SM_RCV + 128 + (j & 1) * 4, 0u, to + SM_FULL + BAR_PEER * 8);
            }
            if (tid == 224) TL(17);
        }
    }

    if (w < 4) {
        const uint32_t lo = (g & 3) * 1024 + (g >> 2) * 512 + (g & 1) * 64 + t * 16;
        const int wd = ((lane >> 2 & 2) + (lane >> 4)) ^ (lane >> 1 & 3);
        const uint32_t base = sb + ((lane & 6) * 4 + wd * 2 + (lane & 1)) * 64 + (((w ^ wd) & 3) << 4);
        const uint64_t dst = __shfl_sync(0xffffffffu, (unsigned long long)ctx_dst, lane);
        mbar_wait(sb + SM_FULL + BAR_LAT * 8);
        uint4 a[8];
#pragma unroll
        for (int i = 0; i < 8; i++) a[i] = lds128(sb + SM_LAT + (lo ^ (i * 64)));
        int it = 0;
        while (refetch<0>(a, lane, [&](int i) { return (const char*)gs->lat[h] + (lo ^ (i * 64)); }))
            if (++it > SPIN_LIMIT) __trap();
        float v0 = 0.f, v1 = 0.f;
#pragma unroll
        for (int i = 0; i < 2; i++) {
            float c[4][4];
#pragma unroll
            for (int k = 0; k < 16; k++) (&c[0][0])[k] = 0.f;
            c[0][0] = v0; c[0][1] = v1;
            mbar_wait(sb + SM_FULL + (IT_WUV + i) * 8);
#pragma unroll
            for (int kk = 0; kk < 8; kk++) {
                uint32_t r0, r1, r2, r3;
                ldsm4t(base + slot_off(IT_WUV + i) + kk * 2048, r0, r1, r2, r3);
                mma16816(c[2 * (kk & 1)],     a[kk].x, a[kk].y, a[kk].z, a[kk].w, r0, r1);
                mma16816(c[2 * (kk & 1) + 1], a[kk].x, a[kk].y, a[kk].z, a[kk].w, r2, r3);
            }
            v0 = (c[0][0] + c[1][2]) + (c[2][0] + c[3][2]);
            v1 = (c[0][1] + c[1][3]) + (c[2][1] + c[3][3]);
            if (i == 0) { v0 = __shfl_xor_sync(0xffffffffu, v0, 16); v1 = __shfl_xor_sync(0xffffffffu, v1, 16); }
        }
        st_rlx_if(dst, pack_bf16(v0, v1), lane >= 16);
        if (tid == 0) TL(16);
    }

    {
        const bool isB = slice >= 32;
        const int r = j & 1;
        const uint32_t xl = isB ? t * 64 + (((g ^ (t & 2)) & 3) << 4) : (g & 3) * 256 + ((g & 1) * 4 + t) * 16;
        const uint32_t cs = isB ? 256 : 64;
        const uint32_t xo = r * 8192 + (w >> 1) * 1024 + (w & 1) * 2 * cs + xl, xz = (1 - r) * 12288 + w * 1024 + (g >> 2) * 2 * cs + xl;
        auto xoff = [&](int i) { return i < 6 ? (i >> 1) * 4096 + (xo ^ ((i & 1) * cs)) : xz ^ ((i & 1) * cs); };
        const char* src = (const char*)gs->x[slice >> 5][r * 12];
        uint32_t off[2], ofz[2];
#pragma unroll
        for (int u = 0; u < 2; u++) {
            const int tt = (lane & 7) >> 1;
            const int row = 8 * tt + 2 * ((2 * u + (lane >> 4) + tt) & 3) + (lane & 1);
            off[u] = sb + w * 2048 + row * 32 + ((((lane >> 3) ^ (row >> 2)) & 1) << 4);
            ofz[u] = __shfl_sync(0xffffffffu, sb + (w < 4 ? slot_off(IT_WO + 3) : slot_off(IT_W2)) + (w & 3) * 4096 + (lane & 8) * 256 +
                                              row * 32 + (((r ^ (row >> 2)) & 1) << 4), lane);
        }
        const uint32_t fin = __shfl_sync(0xffffffffu, sb + SM_FIN + (t & 1) * 768 + g * 48 + ((w ^ (t & 1)) << 2), lane);
        const uint32_t fi2 = __shfl_sync(0xffffffffu, sb + SM_FIN + 3072 + (t & 1) * 1280 + g * 80 + (((w * 2 + (t >> 1)) ^ (t * 2 & 2)) << 2), lane);
        uint32_t a[2][4][4];
        uint4 x[8];
        float c[4][4];
        auto load_w = [&](int i) {
            mbar_wait(sb + SM_FULL + (i < 3 ? IT_WO + i : w < 4 ? IT_WO + 3 : IT_W2) * 8);
#pragma unroll
            for (int q = 0; q < 4; q++)
                ldsm4t((i < 3 ? slot_off(IT_WO + i) + off[q & 1] : ofz[q & 1]) + (q >> 1) * 1024,
                       a[i & 1][q][0], a[i & 1][q][1], a[i & 1][q][2], a[i & 1][q][3]);
        };
        auto mma_w = [&](int i) {
#pragma unroll
            for (int q = 0; q < 4; q++) {
                if (i == 0 || i == 3) c[q][0] = c[q][1] = c[q][2] = c[q][3] = 0.f;
                mma16816(c[q], a[i & 1][q][0], a[i & 1][q][1], a[i & 1][q][2], a[i & 1][q][3],
                         (q & 1) ? x[2 * i + (q >> 1)].z : x[2 * i + (q >> 1)].x, (q & 1) ? x[2 * i + (q >> 1)].w : x[2 * i + (q >> 1)].y);
            }
        };
        load_w(0); load_w(1);
        mbar_wait(sb + SM_FULL + BAR_X * 8);
        if (tid == 224) TLX(20);
#pragma unroll
        for (int i = 0; i < 8; i++) x[i] = lds128_if(sb + slot_off(IT_X) + xoff(i), i >= 6 || lane < 16);
        int it = 0;
        while (true) {
            mma_w(0); mma_w(1);
            if (!refetch<6>(x, lane, [&](int i) { return src + xoff(i); })) break;
            if (++it > SPIN_LIMIT) __trap();
        }
        load_w(2);
        mma_w(2);
#pragma unroll
        for (int e = 0; e < 4; e++) stsf_if(fin + (e >> 1) * 1536 + (e & 1) * 384, (c[0][e] + c[1][e]) + (c[2][e] + c[3][e]), t < 2);
        asm volatile("bar.arrive 5, 320;" ::: "memory");
        if (tid == 0) TLX(18);
        load_w(3);
        mma_w(3);
#pragma unroll
        for (int e = 0; e < 2; e++) {
            const float lo = (c[0][e] + c[1][e]) + (c[2][e] + c[3][e]), hi = (c[0][e + 2] + c[1][e + 2]) + (c[2][e + 2] + c[3][e + 2]);
            stsf(fi2 + e * 640, t < 2 ? lo : hi);
        }
        asm volatile("bar.arrive 7, 288;" ::: "memory");
        if (tid == 224) TLX(26);
    }
}

typedef CUresult (*EncodeTiledFn)(CUtensorMap*, CUtensorMapDataType, cuuint32_t, void*, const cuuint64_t*,
                                  const cuuint64_t*, const cuuint32_t*, const cuuint32_t*, CUtensorMapInterleave,
                                  CUtensorMapSwizzle, CUtensorMapL2promotion, CUtensorMapFloatOOBfill);

void encode_map(EncodeTiledFn enc, CUtensorMap* tm, const void* p, cuuint64_t cols, cuuint64_t rows,
                cuuint32_t brows, cuuint32_t bblk) {
    cuuint64_t dims[3] = {64, rows, cols / 64};
    cuuint64_t strides[2] = {cols * 2, 128};
    cuuint32_t box[3] = {64, brows, bblk};
    cuuint32_t es[3] = {1, 1, 1};
    enc(tm, CU_TENSOR_MAP_DATA_TYPE_BFLOAT16, 3, const_cast<void*>(p), dims, strides, box, es,
        CU_TENSOR_MAP_INTERLEAVE_NONE, CU_TENSOR_MAP_SWIZZLE_128B, (CUtensorMapL2promotion)PROMO_C,
        CU_TENSOR_MAP_FLOAT_OOB_FILL_NONE);
}

void encode_slice_map(EncodeTiledFn enc, CUtensorMap* tm, const void* p, cuuint64_t cols, cuuint64_t rows, cuuint32_t bcols) {
    cuuint64_t dims[3] = {cols, 256, rows / 256};
    cuuint64_t strides[2] = {cols * 2, cols * 512};
    cuuint32_t box[3] = {bcols, 256, 32 / bcols};
    cuuint32_t es[3] = {1, 1, 1};
    enc(tm, CU_TENSOR_MAP_DATA_TYPE_BFLOAT16, 3, const_cast<void*>(p), dims, strides, box, es, CU_TENSOR_MAP_INTERLEAVE_NONE,
        bcols == 16 ? CU_TENSOR_MAP_SWIZZLE_32B : CU_TENSOR_MAP_SWIZZLE_64B, (CUtensorMapL2promotion)(bcols == 16 ? PROMO_WO : PROMO_UV),
        CU_TENSOR_MAP_FLOAT_OOB_FILL_NONE);
}

}

extern "C" void kernel_launch(void* const* d_in, const int* in_sizes, int n_in, void* d_out, int out_size) {
    (void)in_sizes; (void)n_in; (void)out_size;
    static EncodeTiledFn enc = nullptr;
    static Scratch* gs = nullptr;
    if (!enc) {
        cudaGetSymbolAddress((void**)&gs, g_scratch);
        void* fn = nullptr;
        cudaDriverEntryPointQueryResult qr;
        cudaGetDriverEntryPoint("cuTensorMapEncodeTiled", &fn, cudaEnableDefault, &qr);
        enc = (EncodeTiledFn)fn;
        cudaFuncSetAttribute(fused_decode_kernel, cudaFuncAttributeMaxDynamicSharedMemorySize, SM_END);
    }
    Maps maps;
    encode_map(enc, &maps.wqB, d_in[7], 4096, 512, 64, 2);
    encode_map(enc, &maps.wqA, d_in[3], 4096, 512, 64, 2);
    encode_map(enc, &maps.wuk, d_in[8], 4096, 512, 64, 2);
    encode_slice_map(enc, &maps.wuv, d_in[9], 4096, 512, 32);
    encode_slice_map(enc, &maps.woB, d_in[10], 512, 4096, 16);
    encode_slice_map(enc, &maps.woA, d_in[4], 512, 4096, 16);
    encode_map(enc, &maps.ckv, d_in[6], 512, 16384, 16, 8);
    fused_decode_kernel<<<NCTA, NTHR, SM_END>>>((const __nv_bfloat16*)d_in[0], (const __nv_bfloat16*)d_in[5],
                                                (const __nv_bfloat16*)d_in[7], (const __nv_bfloat16*)d_in[3],
                                                (const __nv_bfloat16*)d_in[1] + 3072 * 128, (const __nv_bfloat16*)d_in[2] + 3072 * 128,
                                                (__nv_bfloat16*)d_out, gs, maps);
}
```

```cpp
#include <cuda_runtime.h>
#include <cuda_bf16.h>
#include <cuda.h>
#include <stdint.h>

namespace {

constexpr int NCTA   = 128;
constexpr int NSLOT  = 13;
constexpr int SLOT   = 16384;
constexpr int NITEM  = 56;
constexpr int NTHR   = 352;

constexpr int INFLIGHT = 4;
constexpr int PACE     = 644;
constexpr int LEAD     = 600;
constexpr int TAPER    = 250;
constexpr int XLEAD    = 150;
constexpr int OPGAP    = 200;
constexpr int NWIN     = 4;
__device__ constexpr int win_pos(int k)  { return k == 0 ? 10 : k == 1 ? 20 : k == 2 ? 31 : 38; }
__device__ constexpr int win_late(int k) { return k == 0 ? 1860 : k == 1 ? 1830 : k == 2 ? 1890 : 1800; }
constexpr int GAIN     = 11;

constexpr int IT_WQB = 0, IT_WQA = 2, IT_WUK = 4, IT_K0 = 6, IT_Q = 14, IT_C = 16, IT_K1 = 24, IT_V0 = 32,
              IT_OP = 40, IT_V1 = 42, IT_WUV = 50, IT_WO = 52;
constexpr int IT_X = 56;
constexpr int IT_W2 = 58;
constexpr int BAR_LAT = 56, BAR_FIN = 57, BAR_X = 59, BAR_PEER = 60;

constexpr int SM_FULL  = NSLOT * SLOT;
constexpr int SM_EMPTY = SM_FULL + 512;
constexpr int SM_IN0   = SM_EMPTY + 512;
constexpr int SM_IN1   = SM_IN0 + 1088;
constexpr int SM_SC    = SM_IN1 + 1088;
constexpr int SM_PA    = SM_SC + 4096;
constexpr int SM_PF    = SM_PA + 2048;
constexpr int SM_MX    = SM_PF + 8192;
constexpr int SM_ML    = SM_MX + 1024;
constexpr int SM_RCV   = SM_ML + 128;
constexpr int SM_PACE  = SM_RCV + 144;
constexpr int SM_END   = SM_PACE + 32;
constexpr int SM_LAT   = SM_PF + 4096;
constexpr int SM_FIN   = SM_SC;
constexpr int SM_SUM   = SM_IN0;
static_assert(SM_END <= 232448, "smem");

struct Maps { CUtensorMap wuk, wuv, woA, woB, ckv; };

struct Scratch {
    unsigned cnt[32];
    unsigned late[32];
    float    part[2][NCTA][512];
    uint32_t x[2][32][256];
    uint32_t lat[32][4][256];
    uint4    q[4][2048];
    uint4    op[NCTA][2048];
    float2   stat[32][128];
};
__device__ __align__(128) Scratch g_scratch;

constexpr int SPIN_LIMIT = 1 << 22;

__device__ __forceinline__ uint32_t smem_u32(const void* p) { return (uint32_t)__cvta_generic_to_shared(p); }
__device__ __forceinline__ void mbar_init(uint32_t bar, uint32_t cnt) {
    asm volatile("mbarrier.init.shared::cta.b64 [%0], %1;" ::"r"(bar), "r"(cnt) : "memory");
}
__device__ __forceinline__ void mbar_expect_tx(uint32_t bar, uint32_t bytes) {
    asm volatile("mbarrier.arrive.expect_tx.shared::cta.b64 _, [%0], %1;" ::"r"(bar), "r"(bytes) : "memory");
}
__device__ __forceinline__ void mbar_arrive(uint32_t bar) {
    asm volatile("mbarrier.arrive.shared::cta.b64 _, [%0];" ::"r"(bar) : "memory");
}
__device__ __forceinline__ void mbar_arrive8(uint32_t bar) {
    asm volatile("mbarrier.arrive.shared::cta.b64 _, [%0], 8;" ::"r"(bar) : "memory");
}
__device__ __forceinline__ void mbar_wait(uint32_t bar) {
    uint32_t done;
    int it = 0;
    do {
        asm volatile("{\n.reg .pred p;\nmbarrier.try_wait.parity.shared::cta.b64 p, [%1], 0;\nselp.u32 %0, 1, 0, p;\n}"
                     : "=r"(done) : "r"(bar) : "memory");
        if (++it > SPIN_LIMIT) __trap();
    } while (!done);
}
__device__ __forceinline__ uint32_t map_cta(uint32_t a, uint32_t rank) {
    uint32_t r; asm("mapa.shared::cluster.u32 %0, %1, %2;" : "=r"(r) : "r"(a), "r"(rank)); return r;
}
__device__ __forceinline__ void st_async32(uint32_t a, uint32_t v, uint32_t bar) {
    asm volatile("st.async.shared::cluster.mbarrier::complete_tx::bytes.b32 [%0], %1, [%2];" ::"r"(a), "r"(v), "r"(bar) : "memory");
}
__device__ __forceinline__ uint64_t evict_first() {
    uint64_t pol; asm volatile("createpolicy.fractional.L2::evict_first.b64 %0, 1.0;" : "=l"(pol)); return pol;
}
__device__ __forceinline__ void bulk_load(uint32_t dst, const void* src, uint32_t bytes, uint32_t bar, uint64_t pol) {
    asm volatile("cp.async.bulk.shared::cluster.global.mbarrier::complete_tx::bytes.L2::cache_hint [%0], [%1], %2, [%3], %4;"
                 ::"r"(dst), "l"(src), "r"(bytes), "r"(bar), "l"(pol) : "memory");
}
__device__ __forceinline__ void bulk_load_nohint(uint32_t dst, const void* src, uint32_t bytes, uint32_t bar) {
    asm volatile("cp.async.bulk.shared::cluster.global.mbarrier::complete_tx::bytes [%0], [%1], %2, [%3];"
                 ::"r"(dst), "l"(src), "r"(bytes), "r"(bar) : "memory");
}
__device__ __forceinline__ void tma3d(uint32_t dst, const CUtensorMap* tm, int c0, int c1, int c2, uint32_t bar, uint64_t pol) {
    asm volatile("cp.async.bulk.tensor.3d.shared::cluster.global.mbarrier::complete_tx::bytes.L2::cache_hint [%0], [%1, {%3, %4, %5}], [%2], %6;"
                 ::"r"(dst), "l"(tm), "r"(bar), "r"(c0), "r"(c1), "r"(c2), "l"(pol) : "memory");
}
__device__ __forceinline__ void tma3d_pair(uint32_t dst, const CUtensorMap* tm, int c0, int c1, int c2, uint32_t bar, uint64_t pol) {
    asm volatile("cp.async.bulk.tensor.3d.shared::cluster.global.mbarrier::complete_tx::bytes.multicast::cluster.L2::cache_hint [%0], [%1, {%3, %4, %5}], [%2], %7, %6;"
                 ::"r"(dst), "l"(tm), "r"(bar), "r"(c0), "r"(c1), "r"(c2), "l"(pol), "h"((uint16_t)3) : "memory");
}
__device__ __forceinline__ void ldsm4(uint32_t a, uint32_t& r0, uint32_t& r1, uint32_t& r2, uint32_t& r3) {
    asm volatile("ldmatrix.sync.aligned.m8n8.x4.shared.b16 {%0,%1,%2,%3}, [%4];"
                 : "=r"(r0), "=r"(r1), "=r"(r2), "=r"(r3) : "r"(a) : "memory");
}
__device__ __forceinline__ void ldsm4t(uint32_t a, uint32_t& r0, uint32_t& r1, uint32_t& r2, uint32_t& r3) {
    asm volatile("ldmatrix.sync.aligned.m8n8.x4.trans.shared.b16 {%0,%1,%2,%3}, [%4];"
                 : "=r"(r0), "=r"(r1), "=r"(r2), "=r"(r3) : "r"(a) : "memory");
}
__device__ __forceinline__ void mma16816(float (&c)[4], uint32_t a0, uint32_t a1, uint32_t a2, uint32_t a3,
                                         uint32_t b0, uint32_t b1) {
    asm volatile("mma.sync.aligned.m16n8k16.row.col.f32.bf16.bf16.f32 {%0,%1,%2,%3}, {%4,%5,%6,%7}, {%8,%9}, {%0,%1,%2,%3};"
                 : "+f"(c[0]), "+f"(c[1]), "+f"(c[2]), "+f"(c[3])
                 : "r"(a0), "r"(a1), "r"(a2), "r"(a3), "r"(b0), "r"(b1));
}
__device__ __forceinline__ uint32_t lds32(uint32_t a) {
    uint32_t v; asm volatile("ld.shared.b32 %0, [%1];" : "=r"(v) : "r"(a) : "memory"); return v;
}
__device__ __forceinline__ float ldsf(uint32_t a) {
    float v; asm volatile("ld.shared.f32 %0, [%1];" : "=f"(v) : "r"(a) : "memory"); return v;
}
__device__ __forceinline__ float2 ldsf2(uint32_t a) {
    float2 v; asm volatile("ld.shared.v2.f32 {%0,%1}, [%2];" : "=f"(v.x), "=f"(v.y) : "r"(a) : "memory"); return v;
}
__device__ __forceinline__ float4 ldsf4(uint32_t a) {
    float4 v; asm volatile("ld.shared.v4.f32 {%0,%1,%2,%3}, [%4];" : "=f"(v.x), "=f"(v.y), "=f"(v.z), "=f"(v.w) : "r"(a) : "memory"); return v;
}
__device__ __forceinline__ uint4 lds128(uint32_t a) {
    uint4 v; asm volatile("ld.shared.v4.b32 {%0,%1,%2,%3}, [%4];" : "=r"(v.x), "=r"(v.y), "=r"(v.z), "=r"(v.w) : "r"(a) : "memory"); return v;
}
__device__ __forceinline__ uint4 lds128_if(uint32_t a, bool on) {
    uint4 v;
    asm volatile("{\n.reg .pred p;\nsetp.ne.u32 p, %5, 0;\n@p ld.shared.v4.b32 {%0,%1,%2,%3}, [%4];\n}"
                 : "=r"(v.x), "=r"(v.y), "=r"(v.z), "=r"(v.w) : "r"(a), "r"((uint32_t)on) : "memory");
    return v;
}
__device__ __forceinline__ void stsf_if(uint32_t a, float v, bool on) {
    asm volatile("{\n.reg .pred p;\nsetp.ne.u32 p, %2, 0;\n@p st.shared.f32 [%0], %1;\n}" ::"r"(a), "f"(v), "r"((uint32_t)on) : "memory");
}
__device__ __forceinline__ void sts16(uint32_t a, uint16_t v) { asm volatile("st.shared.b16 [%0], %1;" ::"r"(a), "h"(v) : "memory"); }
__device__ __forceinline__ void sts32(uint32_t a, uint32_t v) { asm volatile("st.shared.b32 [%0], %1;" ::"r"(a), "r"(v) : "memory"); }
__device__ __forceinline__ void stsf(uint32_t a, float v) { asm volatile("st.shared.f32 [%0], %1;" ::"r"(a), "f"(v) : "memory"); }
__device__ __forceinline__ void sts64(uint32_t a, uint32_t x, uint32_t y) {
    asm volatile("st.shared.v2.b32 [%0], {%1,%2};" ::"r"(a), "r"(x), "r"(y) : "memory");
}
__device__ __forceinline__ void sts128(uint32_t a, uint4 v) {
    asm volatile("st.shared.v4.b32 [%0], {%1,%2,%3,%4};" ::"r"(a), "r"(v.x), "r"(v.y), "r"(v.z), "r"(v.w) : "memory");
}
__device__ __forceinline__ uint32_t pack_bf16(float lo, float hi) {
    uint32_t r; asm("cvt.rn.bf16x2.f32 %0, %1, %2;" : "=r"(r) : "f"(hi), "f"(lo)); return r;
}
__device__ __forceinline__ float bf_lo(uint32_t v) { return __uint_as_float(v << 16); }
__device__ __forceinline__ float bf_hi(uint32_t v) { return __uint_as_float(v & 0xffff0000u); }
__device__ __forceinline__ float ex2(float x) { float y; asm("ex2.approx.ftz.f32 %0, %1;" : "=f"(y) : "f"(x)); return y; }
__device__ __forceinline__ uint32_t timer_ns() { uint32_t t; asm volatile("mov.u32 %0, %%globaltimer_lo;" : "=r"(t)); return t; }
__device__ __forceinline__ void bar_consumers() { asm volatile("bar.sync 1, 256;" ::: "memory"); }
__device__ __forceinline__ void bar_setup() { asm volatile("bar.sync 2, 352;" ::: "memory"); }

__device__ __forceinline__ uint32_t tagf(float v, uint32_t tag) { return (__float_as_uint(v) & 0xffffff00u) | tag; }
__device__ __forceinline__ uint2 ld_rlx2(const float* p) {
    uint2 v; asm volatile("ld.relaxed.gpu.global.v2.b32 {%0,%1}, [%2];" : "=r"(v.x), "=r"(v.y) : "l"(p) : "memory"); return v;
}
__device__ __forceinline__ float untag(uint32_t v) { return __uint_as_float(v & 0xffffff00u); }

__device__ __forceinline__ uint32_t slot_off(int item) { return (uint32_t)(item % NSLOT) * SLOT; }

template <bool TRANS, bool TMA = true>
__device__ __forceinline__ void tile_mma(uint32_t sb, int item, uint32_t in, int w, int lane, float (&acc)[2][2]) {
    const int g = lane >> 2, t = lane & 3;
    float c[4][4];
#pragma unroll
    for (int i = 0; i < 16; i++) (&c[0][0])[i] = 0.f;
    uint32_t a[16];
    const uint32_t ia = in + (g & 3) * 272 + t * 4;
#pragma unroll
    for (int i = 0; i < 16; i++) a[i] = lds32(ia + i * 16);
    const uint32_t s0 = sb + slot_off(item), s1 = sb + slot_off(item + 1);
    if (TRANS) {
        const int r = (lane & 7) + (lane & 8);
        const int ch = 2 * (w & 3) + (lane >> 4);
        const uint32_t off = (TMA ? (w >> 2) * 8192 + r * 128 : (w >> 2) * 128 + r * 256) + ((ch ^ (lane & 7)) << 4);
#pragma unroll
        for (int kk = 0; kk < 8; kk++) {
            if (TMA && (kk & 3) == 0) mbar_wait(sb + SM_FULL + (item + (kk >> 2)) * 8);
            uint32_t r0, r1, r2, r3;
            ldsm4t(((kk >> 2) ? s1 : s0) + off + (kk & 3) * (TMA ? 2048 : 4096), r0, r1, r2, r3);
            mma16816(c[2 * (kk & 1)],     a[2 * kk], 0u, a[2 * kk + 1], 0u, r0, r1);
            mma16816(c[2 * (kk & 1) + 1], a[2 * kk], 0u, a[2 * kk + 1], 0u, r2, r3);
        }
    } else {
        mbar_wait(sb + SM_FULL + (item + (w >> 2)) * 8);
        const int r = 16 * (w & 3) + (lane & 7) + ((lane >> 4) << 3);
        const uint32_t base = ((w >> 2) ? s1 : s0) + r * 128 + ((((lane >> 3) & 1) ^ (lane & 7)) << 4);
#pragma unroll
        for (int kk = 0; kk < 8; kk++) {
            uint32_t r0, r1, r2, r3;
            ldsm4((base ^ ((kk & 3) << 5)) + (kk >> 2) * 8192, r0, r1, r2, r3);
            mma16816(c[2 * (kk & 1)],     a[2 * kk], 0u, a[2 * kk + 1], 0u, r0, r1);
            mma16816(c[2 * (kk & 1) + 1], a[2 * kk], 0u, a[2 * kk + 1], 0u, r2, r3);
        }
    }
    __syncwarp();
    if (lane == 0) {
        mbar_arrive(sb + SM_EMPTY + item * 8);
        mbar_arrive(sb + SM_EMPTY + (item + 1) * 8);
    }
    acc[0][0] = c[0][0] + c[2][0]; acc[0][1] = c[0][1] + c[2][1];
    acc[1][0] = c[1][0] + c[3][0]; acc[1][1] = c[1][1] + c[3][1];
}

__device__ __forceinline__ void publish(float* dst, int w, int lane, const float (&acc)[2][2], uint32_t tag) {
    if (lane < 16)
        asm volatile("st.relaxed.gpu.global.v4.b32 [%0], {%1,%2,%3,%4};" ::"l"(dst + w * 64 + lane * 4),
                     "r"(tagf(acc[0][0], tag)), "r"(tagf(acc[0][1], tag)), "r"(tagf(acc[1][0], tag)), "r"(tagf(acc[1][1], tag)) : "memory");
}

__device__ __forceinline__ void gather(const float* part, uint32_t in, int tid, uint32_t tag) {
    const float* p = part + tid * 2;
    uint2 v0, v1, v2, v3;
    int it = 0;
    while (true) {
        v0 = ld_rlx2(p); v1 = ld_rlx2(p + 512); v2 = ld_rlx2(p + 1024); v3 = ld_rlx2(p + 1536);
        uint32_t bad = ((v0.x ^ tag) | (v0.y ^ tag) | (v1.x ^ tag) | (v1.y ^ tag) |
                        (v2.x ^ tag) | (v2.y ^ tag) | (v3.x ^ tag) | (v3.y ^ tag)) & 0xffu;
        if (__all_sync(0xffffffffu, bad == 0)) break;
        if (++it > SPIN_LIMIT) __trap();
    }
    float x = (untag(v0.x) + untag(v1.x)) + (untag(v2.x) + untag(v3.x));
    float y = (untag(v0.y) + untag(v1.y)) + (untag(v2.y) + untag(v3.y));
    sts32(in + ((tid >> 3) & 3) * 272 + (tid >> 5) * 32 + (tid & 1) * 16 + (tid & 6) * 2, pack_bf16(x, y));
    bar_consumers();
}

constexpr uint32_t EMPTY = 0xffffffffu;
__device__ __forceinline__ void st_rlx(uint32_t* p, uint32_t v) {
    asm volatile("st.relaxed.gpu.global.b32 [%0], %1;" ::"l"(p), "r"(v) : "memory");
}
__device__ __forceinline__ void st_rlx_if(uint64_t p, uint32_t v, bool on) {
    asm volatile("{\n.reg .pred p;\nsetp.ne.u32 p, %2, 0;\n@p st.relaxed.gpu.global.b32 [%0], %1;\n}" ::"l"(p), "r"(v), "r"((uint32_t)on) : "memory");
}
__device__ __forceinline__ void st_rlx2(uint32_t* p, uint32_t v0, uint32_t v1) {
    asm volatile("st.relaxed.gpu.global.v2.b32 [%0], {%1,%2};" ::"l"(p), "r"(v0), "r"(v1) : "memory");
}
__device__ __forceinline__ void ld_rlx4_if(uint4& v, const void* p, bool need) {
    asm volatile("{\n.reg .pred p;\nsetp.ne.u32 p, %5, 0;\n@p ld.relaxed.gpu.global.v4.b32 {%0,%1,%2,%3}, [%4];\n}"
                 : "+r"(v.x), "+r"(v.y), "+r"(v.z), "+r"(v.w) : "l"(p), "r"((uint32_t)need) : "memory");
}

template <int HALF, class F>
__device__ __forceinline__ bool refetch(uint4 (&x)[8], int lane, F addr) {
    uint32_t m[8], m0 = 0, m1 = 0;
#pragma unroll
    for (int i = 0; i < 8; i++) {
        m[i] = max(max(x[i].x, x[i].y), max(x[i].z, x[i].w));
        if (i < HALF) m0 = max(m0, m[i]); else m1 = max(m1, m[i]);
    }
    if (!__any_sync(0xffffffffu, (m0 == EMPTY && lane < 16) || m1 == EMPTY)) return false;
#pragma unroll
    for (int i = 0; i < 8; i++) ld_rlx4_if(x[i], addr(i), m[i] == EMPTY && (i >= HALF || lane < 16));
    return true;
}

__device__ __forceinline__ unsigned read_counter(const unsigned* cnt) {
    unsigned v;
    asm volatile("ld.relaxed.gpu.global.u32 %0, [%1];" : "=r"(v) : "l"(cnt) : "memory");
    return v;
}
__device__ __forceinline__ unsigned epoch_of(unsigned cnt) {
    asm volatile("" : "+r"(cnt) :: "memory");
    return cnt / NCTA + 1;
}
__device__ __forceinline__ uint32_t epoch_tag(unsigned epoch) { return (epoch & 0x7fu) | 0x80u; }

__device__ __forceinline__ void signal_and_wait(unsigned* cnt, unsigned target, int lane) {
    if (lane == 0) asm volatile("red.release.gpu.global.add.u32 [%0], 1;" ::"l"(cnt) : "memory");
    int it = 0;
    while (true) {
        unsigned v;
        asm volatile("ld.acquire.gpu.global.u32 %0, [%1];" : "=r"(v) : "l"(cnt) : "memory");
        if (__all_sync(0xffffffffu, (int)(v - target) >= 0)) break;
        if (++it > SPIN_LIMIT) __trap();
    }
    asm volatile("fence.proxy.async.global;" ::: "memory");
}

__global__ void __cluster_dims__(2, 1, 1) __launch_bounds__(NTHR, 1)
fused_decode_kernel(const __nv_bfloat16* __restrict__ xA, const __nv_bfloat16* __restrict__ xB,
                    const __nv_bfloat16* __restrict__ wqB, const __nv_bfloat16* __restrict__ wqA,
                    const __nv_bfloat16* __restrict__ Kc, const __nv_bfloat16* __restrict__ Vc,
                    __nv_bfloat16* __restrict__ out, Scratch* gs, const __grid_constant__ Maps maps) {
    extern __shared__ __align__(1024) unsigned char smem_raw[];
    const uint32_t sb = smem_u32(smem_raw);
    const int tid = threadIdx.x, lane = tid & 31;
    const int cta = blockIdx.x, h = cta >> 2, j = cta & 3;
    const size_t kv_off = (size_t)blockIdx.x * 4096 * 128;
    const uint32_t trow = threadIdx.x >> 4;
    const uint32_t tile_src = trow * (8192 - 256) + (threadIdx.x * 16 + ((blockIdx.x * 0x100040u) & 0x301f00u));
    const uint32_t tile_dst = sb + ((threadIdx.x ^ (trow & 7)) << 4);
    auto lsu_tile = [&](const __nv_bfloat16* W, int item) {
#pragma unroll
        for (int q = 0; q < 8; q++)
            asm volatile("cp.async.cg.shared.global [%0], [%1], 16;" ::"r"(tile_dst + item * SLOT + q * 4096),
                         "l"(reinterpret_cast<const char*>(W + q * 16 * 4096) + tile_src) : "memory");
        asm volatile("cp.async.commit_group;" ::: "memory");
    };
    if (tid < 256) lsu_tile(wqB, IT_WQB);
    const uint32_t tz = timer_ns() - LEAD;
    const unsigned cnt1 = read_counter(&gs->cnt[1]);
    uint4 xv;
    if (tid < 128) {
        const __nv_bfloat16* x = (tid < 64 ? xB : xA) + ((tid >> 4) & 3) * 512 + j * 128 + (tid & 15) * 8;
        xv = __ldg(reinterpret_cast<const uint4*>(x));
    }
    const int w = __shfl_sync(0xffffffffu, tid >> 5, 0);
    const int pr = cta >> 1;
    const int slice = pr < 4 ? pr : pr < 36 ? 4 + ((pr - 4) & 7) * 4 + ((pr - 4) >> 3) : 36 + (pr - 36) % 7 * 4 + (pr - 36) / 7;

    if (w == 10) {
        if (lane == 0) sts64(sb + SM_PACE, tz, PACE * 16);
        bar_setup();
        if (lane == 0) {
            int slope = 0;
#pragma unroll
            for (int k = 0; k < NWIN; k++) {
                const int c = win_pos(k);
                uint32_t acc = 0;
#pragma unroll
                for (int p = c; p < c + 4; p++) {
                    mbar_wait(sb + SM_FULL + (p < IT_Q ? p : p < IT_OP - 2 ? p + 2 : p + 4) * 8);
                    acc += timer_ns() - tz - p * PACE - ((p * slope) >> 4);
                }
                if (k == 0) mbar_wait(sb + SM_FULL + IT_Q * 8);
                asm volatile("red.relaxed.gpu.global.add.u32 [%0], %1;" ::"l"(&gs->late[k]), "r"((1u << 24) + min(acc >> 2, 65535u)) : "memory");
                uint32_t v;
                int it = 0;
                do { v = read_counter(&gs->late[k]); } while ((v >> 24) != NCTA && ++it < 1000);
                const int late = (v & 0xffffffu) / NCTA;
                slope = max(-320, min(320, slope + (late - win_late(k)) * (GAIN * 2) / (2 * c + 3)));
                sts64(sb + SM_PACE, tz, PACE * 16 + slope);
            }
        }
        return;
    }
    if (w >= 8) {
        if (w == 8) {
            bar_setup();
            const uint64_t pol = evict_first();
            int slot = IT_WUK, tail = IT_WUK - INFLIGHT;
            uint32_t np = IT_WUK, tap = 0;
            auto due = [&](uint32_t p) {
                uint32_t a, b;
                asm volatile("ld.volatile.shared.v2.b32 {%0,%1}, [%2];" : "=r"(a), "=r"(b) : "r"(sb + SM_PACE) : "memory");
                return a + ((p * b) >> 4);
            };
#pragma unroll 1
            for (int i = IT_WUK; i < NITEM; i++) {
                const uint32_t dst = sb + slot * SLOT, bar = sb + SM_FULL + i * 8;
                if (++slot == NSLOT) slot = 0;
                if ((i & ~1) == IT_Q || (i & ~1) == IT_OP) continue;
                const bool ckv = i >= IT_C && i < IT_K1, wo = i >= IT_WO;
                const bool tiled = ckv || i < IT_K0 || i >= IT_WUV;
                const CUtensorMap* tm = &maps.wuk + (i < IT_K0 ? 0 : ckv ? 4 : wo ? 2 + (slice >> 5) : 1);
                const int c0 = wo ? (slice & 31) * 16 : i >= IT_WUV ? cta * 32 : 0;
                const int c1 = i < IT_K0 ? j * 128 + (i & 1) * 64 : ckv ? cta * 128 + (i - IT_C) * 16 : 0;
                const int c2 = i < IT_K0 ? h * 2 : ckv ? 0 : wo ? (i - IT_WO) * 4 + (j & 1) * 2 : i & 1;
                const int c = i < IT_Q ? i - IT_K0 : i < IT_V0 ? i - IT_K1 + 8 : i < IT_OP ? i - IT_V0 : i - IT_V1 + 8;
                const __nv_bfloat16* src = (i < IT_V0 ? Kc : Vc) + kv_off + (size_t)c * (SLOT / 2);
                if (i >= NSLOT) mbar_wait(sb + SM_EMPTY + (i - NSLOT) * 8);
                if (tail >= IT_WUK) mbar_wait(sb + SM_FULL + tail * 8);
                ++tail;
                if (tail == IT_Q || tail == IT_OP) tail += 2;
                if (i == NITEM - 1) {
                    mbar_wait(sb + SM_FULL + BAR_PEER * 8);
                    while (__all_sync(0xffffffffu, (int)(timer_ns() - (due(np) + tap - XLEAD)) < 0)) {}
                    asm volatile("bar.arrive 4, 64;" ::: "memory");
                }
                while (__all_sync(0xffffffffu, (int)(timer_ns() - (due(np) + tap)) < 0)) {}
                ++np;
                if (i == IT_WUV - 1) tap = TAPER;
                if (lane == 0) {
                    if (i == NITEM - 1) tma3d_pair(dst + (j & 1) * (IT_W2 - i) * SLOT, tm, c0, c1, c2, bar + (j & 1) * (IT_W2 - i) * 8, pol);
                    else if (tiled) tma3d(dst, tm, c0, c1, c2, bar, pol);
                    else bulk_load(dst, src, SLOT, bar, pol);
                }
            }
        } else {
            if (lane == 0) {
                mbar_init(sb + SM_FULL + IT_W2 * 8, 1);
                mbar_init(sb + SM_FULL + BAR_X * 8, 1);
                mbar_init(sb + SM_FULL + BAR_PEER * 8, 1);
                mbar_expect_tx(sb + SM_FULL + IT_W2 * 8, SLOT);
                mbar_expect_tx(sb + SM_FULL + BAR_X * 8, SLOT + 4096);
                mbar_expect_tx(sb + SM_FULL + BAR_PEER * 8, 8);
                asm volatile("fence.mbarrier_init.release.cluster;" ::: "memory");
            }
            if (lane < sizeof(Maps) / 128) asm volatile("prefetch.tensormap [%0];" ::"l"(&maps.wuk + lane) : "memory");
            bar_setup();
            asm volatile("bar.sync 3, 288;" ::: "memory");
            const unsigned epoch = epoch_of(cnt1);
            signal_and_wait(&gs->cnt[0], epoch * NCTA, lane);
            if (lane == 0) {
                const uint4* q = gs->q[cta >> 5];
                bulk_load_nohint(sb + slot_off(IT_Q), q, SLOT, sb + SM_FULL + IT_Q * 8);
                bulk_load_nohint(sb + slot_off(IT_Q + 1), q + 1024, SLOT, sb + SM_FULL + (IT_Q + 1) * 8);
            }
            asm volatile("bar.sync 3, 288;" ::: "memory");
            signal_and_wait(&gs->cnt[1], epoch * NCTA, lane);
            mbar_wait(sb + SM_EMPTY + (IT_OP - NSLOT) * 8);
            mbar_wait(sb + SM_EMPTY + (IT_OP + 1 - NSLOT) * 8);
            if (lane == 0) {
                const uint4* op = gs->op[cta];
                bulk_load_nohint(sb + SM_MX, gs->stat[h], 1024, sb + SM_FULL + IT_OP * 8);
                uint32_t t1 = timer_ns();
#pragma unroll 1
                for (int i = 0; i < 8; i++) {
                    while ((int)(timer_ns() - t1) < 0) {}
                    t1 += OPGAP;
                    bulk_load_nohint(sb + slot_off(IT_OP) + i * 4096, op + i * 256, 4096, sb + SM_FULL + (IT_OP + i / 4) * 8);
                }
            }
            mbar_wait(sb + SM_FULL + (IT_V1 + 4) * 8);
            if (lane == 0) bulk_load_nohint(sb + SM_LAT, gs->lat[h], 4096, sb + SM_FULL + BAR_LAT * 8);
            mbar_wait(sb + SM_EMPTY + (IT_X - NSLOT) * 8);
            mbar_wait(sb + SM_EMPTY + (IT_X + 1 - NSLOT) * 8);
            asm volatile("bar.sync 4, 64;" ::: "memory");
            if (lane == 0)
                bulk_load_nohint(sb + slot_off(IT_X), gs->x[slice >> 5][(j & 1) * 12], SLOT + 4096, sb + SM_FULL + BAR_X * 8);
        }
        const uint32_t oo  = __shfl_sync(0xffffffffu, (lane >> 3) * 2048 + slice * 32 + (j & 1) * 16 + (lane & 7) * 2, lane);
        const uint32_t src = __shfl_sync(0xffffffffu, sb + SM_FIN + ((j ^ w ^ 1) & 1) * 1536 + lane * 48, lane);
        const uint32_t sr2 = __shfl_sync(0xffffffffu, sb + SM_FIN + 3072 + lane * 80, lane);
        const uint32_t to  = w == 8 ? map_cta(sb, (j & 1) ^ 1) : sb;
        const uint32_t rcv = __shfl_sync(0xffffffffu, to + SM_RCV + lane * 4, lane);
        const uint32_t fin = __shfl_sync(0xffffffffu, to + SM_FULL + BAR_FIN * 8, lane);
        mbar_wait(sb + SM_FULL + (NITEM - 3) * 8);
        asm volatile("bar.sync 5, 320;" ::: "memory");
        const float4 p0 = ldsf4(src), p1 = ldsf4(src + 16);
        float sum = ((p0.x + p0.y) + (p0.z + p0.w)) + ((p1.x + p1.y) + (p1.z + p1.w));
        if (w == 8) {
            st_async32(rcv, __float_as_uint(sum), fin);
        } else {
            __nv_bfloat16* dst = reinterpret_cast<__nv_bfloat16*>(reinterpret_cast<char*>(out) + oo);
            mbar_wait(sb + SM_FULL + BAR_FIN * 8);
            sum += ldsf(rcv);
            asm volatile("bar.sync 7, 288;" ::: "memory");
            const float4 q0 = ldsf4(sr2), q1 = ldsf4(sr2 + 16), q2 = ldsf4(sr2 + 32), q3 = ldsf4(sr2 + 48);
            *dst = __float2bfloat16((((q0.x + sum) + q0.y) + (q0.z + q0.w) + ((q1.x + q1.y) + (q1.z + q1.w))) +
                                    (((q2.x + q2.y) + (q2.z + q2.w)) + ((q3.x + q3.y) + (q3.z + q3.w))));
        }
        return;
    }

    const int g = lane >> 2, t = lane & 3;
    const uint32_t in0 = sb + SM_IN0, in1 = sb + SM_IN1;
    auto xpos = [](int hh) { return (hh & 4) * 4 + (((hh >> 3) + (hh >> 2 & 1)) & 3) * 4 + (hh & 3); };
    const int ba = cta >> 5, ha = cta & 31;
    uint32_t* const ctx_dst = &gs->x[1][xpos(h)][(j * 4 + (w & 3)) * 16 + ((g ^ (w & 2)) & 3) * 4 + ((t - w) & 3)];
    uint32_t* const o_dst = &gs->x[0][xpos(ha)][ba * 64 + ((tid & 60) ^ ((ba & 1) * 16)) + ((t - g) & 3)];
    uint32_t* const lat_dst = &gs->lat[h][g & 3][j * 64 + ((w >> 1) ^ (g & 1)) * 16 + t * 4 + ((w * 2 ^ t) & 2)];
    {
        if (lane == 0) {
            const uint32_t bars = sb + (w < 4 ? SM_EMPTY : SM_FULL + 2 * 8) + (w & 3) * 14 * 8;
            const uint32_t cnt = w < 4 ? 8 : 1;
#pragma unroll
            for (int i = 0; i < 14; i++) mbar_init(bars + i * 8, cnt);
            if (w >= 4) {
#pragma unroll
                for (int i = 0; i < 14; i++)
                    mbar_expect_tx(bars + i * 8, (i == (IT_OP - 2) % 14 && w == 4 + (IT_OP - 2) / 14) ? SLOT + 1024 :
                                                 (i >= 12 && w == 7) ? (i == 12 ? 4096 : 128) : SLOT);
            }
            asm volatile("fence.mbarrier_init.release.cluster;" ::: "memory");
        }
        lsu_tile(wqA, IT_WQA);
        bar_setup();
        if (lane < 16) st_rlx2(lat_dst, EMPTY, EMPTY);
        if (lane >= 16 && w < 4) st_rlx(ctx_dst, EMPTY);
        if (w >= 6) st_rlx(o_dst, EMPTY);
        if (cta == 0 && w == 5) st_rlx(&gs->late[lane], 0u);
        if (tid < 128) sts128((tid < 64 ? in0 : in1) + ((tid >> 4) & 3) * 272 + (tid & 15) * 16, xv);
        asm volatile("cp.async.wait_group 1;" ::: "memory");
    }
    bar_consumers();
    const uint32_t tag = epoch_tag(epoch_of(cnt1));

    float acc[2][2];
    tile_mma<true, false>(sb, IT_WQB, in0, w, lane, acc);
    publish(gs->part[0][cta], w, lane, acc, tag);
    asm volatile("cp.async.wait_group 0;" ::: "memory");
    bar_consumers();
    tile_mma<true, false>(sb, IT_WQA, in1, w, lane, acc);
    publish(gs->part[1][cta], w, lane, acc, tag);
    bar_consumers();

    const float SC = 0.08838834764831845f * 1.4426950408889634f;
    gather(gs->part[0][h * 4], in0, tid, tag);
    tile_mma<false>(sb, IT_WUK, in0, w, lane, acc);
    if (lane < 16) {
        uint32_t* q = reinterpret_cast<uint32_t*>(gs->q[g]) + (2 * j + (w >> 2)) * 1024 + h * 32 + t;
        const int ch = 2 * (w & 3);
        q[((ch) ^ (h & 7)) * 4]     = pack_bf16(acc[0][0] * SC, acc[0][1] * SC);
        q[((ch + 1) ^ (h & 7)) * 4] = pack_bf16(acc[1][0] * SC, acc[1][1] * SC);
    }
    __syncwarp();
    asm volatile("bar.arrive 3, 288;" ::: "memory");
    gather(gs->part[1][ha * 4], in1, tid, tag);

    uint32_t qf[16];
#pragma unroll
    for (int c = 0; c < 8; c++) {
        qf[2 * c]     = lds32(in1 + ba * 272 + ((c ^ g) << 4) + t * 4);
        qf[2 * c + 1] = lds32(in1 + ba * 272 + 128 + ((c ^ g) << 4) + t * 4);
    }
    const uint32_t sc_w = sb + SM_SC + w * 512;
    auto k_item = [&](int item, uint32_t sc) {
        mbar_wait(sb + SM_FULL + item * 8);
        const uint32_t base = sb + slot_off(item) + ((lane & 7) + (lane & 8)) * 256 + ((lane >> 4) << 7);
        float s[4][4];
#pragma unroll
        for (int T = 0; T < 4; T++) { s[T][0] = s[T][1] = s[T][2] = s[T][3] = 0.f; }
#pragma unroll
        for (int c = 0; c < 8; c++) {
            const uint32_t a = base + ((c ^ (lane & 7)) << 4);
#pragma unroll
            for (int T = 0; T < 4; T++) {
                uint32_t r0, r1, r2, r3;
                ldsm4(a + T * 4096, r0, r1, r2, r3);
                mma16816(s[T], r0, r1, r2, r3, qf[2 * c], qf[2 * c + 1]);
            }
        }
        __syncwarp();
        if (lane == 0) mbar_arrive8(sb + SM_EMPTY + item * 8);
        if (t == (g >> 1)) {
#pragma unroll
            for (int T = 0; T < 4; T++) {
                stsf(sc + (16 * T + g) * 4,     (g & 1) ? s[T][1] : s[T][0]);
                stsf(sc + (16 * T + g + 8) * 4, (g & 1) ? s[T][3] : s[T][2]);
            }
        }
    };
    k_item(IT_K0 + w, sc_w);

    {
        float s[2][2][4];
#pragma unroll
        for (int i = 0; i < 16; i++) (&s[0][0][0])[i] = 0.f;
        mbar_wait(sb + SM_FULL + IT_Q * 8);
        mbar_wait(sb + SM_FULL + (IT_Q + 1) * 8);
        mbar_wait(sb + SM_FULL + (IT_C + w) * 8);
        const uint32_t cb0 = sb + slot_off(IT_C + w) + ((lane & 7) + ((lane >> 4) << 3)) * 128;
        const uint32_t cx = (((lane >> 3) & 1) ^ (lane & 7)) << 4;
        const uint32_t qr = ((lane & 7) + (lane & 8)) * 128;
        const uint32_t qx = ((lane >> 4) ^ (lane & 7)) << 4;
#pragma unroll
        for (int cb = 0; cb < 8; cb++) {
            const uint32_t qb = sb + slot_off(IT_Q + (cb >> 2)) + (cb & 3) * 4096 + qr;
#pragma unroll
            for (int k4 = 0; k4 < 4; k4++) {
                uint32_t b0, b1, b2, b3, a0, a1, a2, a3;
                ldsm4(cb0 + cb * 2048 + (cx ^ (k4 << 5)), b0, b1, b2, b3);
                ldsm4(qb + (qx ^ (k4 << 5)), a0, a1, a2, a3);
                mma16816(s[0][0], a0, a1, a2, a3, b0, b1);
                mma16816(s[0][1], a0, a1, a2, a3, b2, b3);
                ldsm4(qb + 2048 + (qx ^ (k4 << 5)), a0, a1, a2, a3);
                mma16816(s[1][0], a0, a1, a2, a3, b0, b1);
                mma16816(s[1][1], a0, a1, a2, a3, b2, b3);
            }
        }
        __syncwarp();
        if (lane == 0) { mbar_arrive(sb + SM_EMPTY + IT_Q * 8); mbar_arrive(sb + SM_EMPTY + (IT_Q + 1) * 8); }
#pragma unroll
        for (int r = 0; r < 4; r++) {
            const int mt = r >> 1, hi = (r & 1) * 2;
            float m = fmaxf(fmaxf(s[mt][0][hi], s[mt][0][hi + 1]), fmaxf(s[mt][1][hi], s[mt][1][hi + 1]));
            m = fmaxf(m, __shfl_xor_sync(0xffffffffu, m, 1));
            m = fmaxf(m, __shfl_xor_sync(0xffffffffu, m, 2));
            if (t == 0) stsf(sb + SM_MX + (8 * r + g) * 32 + w * 4, m);
        }
        bar_consumers();
        uint32_t pf[2][4];
#pragma unroll
        for (int r = 0; r < 4; r++) {
            const int mt = r >> 1, hi = r & 1;
            const float4 m0 = ldsf4(sb + SM_MX + (8 * r + g) * 32), m1 = ldsf4(sb + SM_MX + (8 * r + g) * 32 + 16);
            const float m = fmaxf(fmaxf(fmaxf(m0.x, m0.y), fmaxf(m0.z, m0.w)), fmaxf(fmaxf(m1.x, m1.y), fmaxf(m1.z, m1.w)));
            const uint32_t p0 = pack_bf16(ex2(s[mt][0][2 * hi] - m), ex2(s[mt][0][2 * hi + 1] - m));
            const uint32_t p1 = pack_bf16(ex2(s[mt][1][2 * hi] - m), ex2(s[mt][1][2 * hi + 1] - m));
            pf[mt][hi] = p0; pf[mt][2 + hi] = p1;
            float l = (bf_lo(p0) + bf_hi(p0)) + (bf_lo(p1) + bf_hi(p1));
            l += __shfl_xor_sync(0xffffffffu, l, 1);
            l += __shfl_xor_sync(0xffffffffu, l, 2);
            if (t == 0) stsf(sb + SM_SUM + (8 * r + g) * 32 + w * 4, l);
        }
        sts128(sb + SM_PF + (w * 2 + 0) * 512 + lane * 16, make_uint4(pf[0][0], pf[0][1], pf[0][2], pf[0][3]));
        sts128(sb + SM_PF + (w * 2 + 1) * 512 + lane * 16, make_uint4(pf[1][0], pf[1][1], pf[1][2], pf[1][3]));
        bar_consumers();
        if (w == 0) {
            const float4 m0 = ldsf4(sb + SM_MX + lane * 32), m1 = ldsf4(sb + SM_MX + lane * 32 + 16);
            const float4 l0 = ldsf4(sb + SM_SUM + lane * 32), l1 = ldsf4(sb + SM_SUM + lane * 32 + 16);
            const float m = fmaxf(fmaxf(fmaxf(m0.x, m0.y), fmaxf(m0.z, m0.w)), fmaxf(fmaxf(m1.x, m1.y), fmaxf(m1.z, m1.w)));
            const float l = ((l0.x + l0.y) + (l0.z + l0.w)) + ((l1.x + l1.y) + (l1.z + l1.w));
            gs->stat[lane][cta] = make_float2(m, l);
        }
        float o[2][8][4];
#pragma unroll
        for (int i = 0; i < 64; i++) (&o[0][0][0])[i] = 0.f;
        const uint32_t vr = w * 2048 + ((lane & 7) + (lane & 8)) * 128;
        const uint32_t vx = ((lane >> 4) ^ (lane & 7)) << 4;
#pragma unroll
        for (int ks = 0; ks < 8; ks++) {
            const uint4 p0 = lds128(sb + SM_PF + (ks * 2 + 0) * 512 + lane * 16);
            const uint4 p1 = lds128(sb + SM_PF + (ks * 2 + 1) * 512 + lane * 16);
            const uint32_t vb = sb + slot_off(IT_C + ks) + vr;
#pragma unroll
            for (int n2 = 0; n2 < 4; n2++) {
                uint32_t b0, b1, b2, b3;
                ldsm4t(vb + (vx ^ (n2 << 5)), b0, b1, b2, b3);
                mma16816(o[0][2 * n2],     p0.x, p0.y, p0.z, p0.w, b0, b1);
                mma16816(o[0][2 * n2 + 1], p0.x, p0.y, p0.z, p0.w, b2, b3);
                mma16816(o[1][2 * n2],     p1.x, p1.y, p1.z, p1.w, b0, b1);
                mma16816(o[1][2 * n2 + 1], p1.x, p1.y, p1.z, p1.w, b2, b3);
            }
            __syncwarp();
            if (lane == 0) mbar_arrive(sb + SM_EMPTY + (IT_C + ks) * 8);
        }
        mbar_wait(sb + SM_FULL + (IT_K1 + 2 + (w >> 1)) * 8);
#pragma unroll
        for (int r = 0; r < 4; r++) {
            const int mt = r >> 1, hi = (r & 1) * 2;
            uint4* dst = gs->op[(8 * r + g) * 4 + (w >> 1)] + (cta >> 6) * 1024 + (w & 1) * 512 + (cta & 63) * 8;
#pragma unroll
            for (int u = 0; u < 2; u++) {
                uint4 v;
                v.x = pack_bf16(o[mt][4 * u][hi],     o[mt][4 * u][hi + 1]);
                v.y = pack_bf16(o[mt][4 * u + 1][hi], o[mt][4 * u + 1][hi + 1]);
                v.z = pack_bf16(o[mt][4 * u + 2][hi], o[mt][4 * u + 2][hi + 1]);
                v.w = pack_bf16(o[mt][4 * u + 3][hi], o[mt][4 * u + 3][hi + 1]);
                dst[(t + 4 * u) ^ (cta & 7)] = v;
            }
        }
        asm volatile("bar.arrive 3, 288;" ::: "memory");
    }

    k_item(IT_K1 + w, sc_w + 256);
    __syncwarp();
    {
        const float4 s = ldsf4(sc_w + lane * 16);
        float m = fmaxf(fmaxf(s.x, s.y), fmaxf(s.z, s.w));
#pragma unroll
        for (int d = 1; d < 32; d <<= 1) m = fmaxf(m, __shfl_xor_sync(0xffffffffu, m, d));
        if (lane == 0) stsf(sb + SM_ML + w * 4, m);
        bar_consumers();
        const float4 m0 = ldsf4(sb + SM_ML), m1 = ldsf4(sb + SM_ML + 16);
        m = fmaxf(fmaxf(fmaxf(m0.x, m0.y), fmaxf(m0.z, m0.w)), fmaxf(fmaxf(m1.x, m1.y), fmaxf(m1.z, m1.w))) * SC;
        const uint32_t p0 = pack_bf16(ex2(fmaf(s.x, SC, -m)), ex2(fmaf(s.y, SC, -m)));
        const uint32_t p1 = pack_bf16(ex2(fmaf(s.z, SC, -m)), ex2(fmaf(s.w, SC, -m)));
        float l = (bf_lo(p0) + bf_hi(p0)) + (bf_lo(p1) + bf_hi(p1));
#pragma unroll
        for (int d = 1; d < 32; d <<= 1) l += __shfl_xor_sync(0xffffffffu, l, d);
        if (lane == 0) stsf(sb + SM_ML + 32 + w * 4, l);
        sts64(sb + SM_PA + w * 256 + lane * 8, p0, p1);
        __syncwarp();
    }

    float oa[4][4];
#pragma unroll
    for (int i = 0; i < 16; i++) (&oa[0][0])[i] = 0.f;
    auto v_item = [&](int item, uint32_t pa) {
        uint32_t p[8];
#pragma unroll
        for (int i = 0; i < 8; i++) p[i] = lds32(pa + i * 16 + t * 4);
        mbar_wait(sb + SM_FULL + item * 8);
        const uint32_t base = sb + slot_off(item) + ((lane & 7) + ((lane >> 4) << 3)) * 256 + ((lane & 8) << 4);
#pragma unroll
        for (int c = 0; c < 8; c++) {
            const uint32_t a = base + ((c ^ (lane & 7)) << 4);
            const uint32_t mask = ((c == (g ^ (2 * t))) ? 0x0000ffffu : 0u) | ((c == (g ^ (2 * t + 1))) ? 0xffff0000u : 0u);
#pragma unroll
            for (int T = 0; T < 4; T++) {
                uint32_t r0, r1, r2, r3;
                ldsm4t(a + T * 4096, r0, r1, r2, r3);
                mma16816(oa[T], r0, r1, r2, r3, p[2 * T] & mask, p[2 * T + 1] & mask);
            }
        }
        __syncwarp();
        if (lane == 0) mbar_arrive8(sb + SM_EMPTY + item * 8);
    };
    v_item(IT_V0 + w, sb + SM_PA + w * 256);

    mbar_wait(sb + SM_FULL + IT_OP * 8);
    if (w < 4) {
        const float2 st = ldsf2(sb + SM_MX + tid * 8);
        float m = st.x;
#pragma unroll
        for (int d = 1; d < 32; d <<= 1) m = fmaxf(m, __shfl_xor_sync(0xffffffffu, m, d));
        const uint32_t wb = pack_bf16(ex2(st.x - m), 0.f);
        float l = bf_lo(wb) * st.y;
#pragma unroll
        for (int d = 1; d < 32; d <<= 1) l += __shfl_xor_sync(0xffffffffu, l, d);
#pragma unroll
        for (int bb = 0; bb < 4; bb++) sts16(in0 + bb * 272 + tid * 2, bb == w ? (uint16_t)wb : (uint16_t)0);
        if (lane == 0) stsf(sb + SM_ML + 64 + w * 4, 1.f / l);
    }
    bar_consumers();
    tile_mma<true>(sb, IT_OP, in0, w, lane, acc);
    if (lane < 16) {
        const float inv = ldsf(sb + SM_ML + 64 + g * 4);
        const uint32_t v0 = pack_bf16(acc[0][0] * inv, acc[0][1] * inv), v1 = pack_bf16(acc[1][0] * inv, acc[1][1] * inv);
        st_rlx2(lat_dst, (t & 1) ? v1 : v0, (t & 1) ? v0 : v1);
    }

    {
        const float4 l0 = ldsf4(sb + SM_ML + 32), l1 = ldsf4(sb + SM_ML + 48);
        const float inv = 1.f / (((l0.x + l0.y) + (l0.z + l0.w)) + ((l1.x + l1.y) + (l1.z + l1.w)));
        v_item(IT_V1 + w, sb + SM_PA + w * 256 + 128);
        const uint32_t so = sb + SM_PF + w * 512 + (16 * t + g) * 4;
        stsf(so,       (oa[0][0] + oa[1][0]) + (oa[2][0] + oa[3][0]));
        stsf(so + 32,  (oa[0][1] + oa[1][1]) + (oa[2][1] + oa[3][1]));
        stsf(so + 256, (oa[0][2] + oa[1][2]) + (oa[2][2] + oa[3][2]));
        stsf(so + 288, (oa[0][3] + oa[1][3]) + (oa[2][3] + oa[3][3]));
        if (w < 6) {
            asm volatile("bar.arrive 1, 256;" ::: "memory");
        } else {
            bar_consumers();
            float x = 0.f, y = 0.f;
#pragma unroll
            for (int i = 0; i < 8; i++) {
                const float2 v = ldsf2(sb + SM_PF + i * 512 + (tid & 63) * 8);
                x += v.x; y += v.y;
            }
            st_rlx(o_dst, pack_bf16(x * inv, y * inv));
            if (lane == 0) {
                const uint32_t to = map_cta(sb, w & 1);
                st_async32(to + SM_RCV + 128 + (j & 1) * 4, 0u, to + SM_FULL + BAR_PEER * 8);
            }
        }
    }

    if (w < 4) {
        const uint32_t lo = (g & 3) * 1024 + (g >> 2) * 512 + (g & 1) * 64 + t * 16;
        const int wd = ((lane >> 2 & 2) + (lane >> 4)) ^ (lane >> 1 & 3);
        const uint32_t base = sb + ((lane & 6) * 4 + wd * 2 + (lane & 1)) * 64 + (((w ^ wd) & 3) << 4);
        const uint64_t dst = __shfl_sync(0xffffffffu, (unsigned long long)ctx_dst, lane);
        mbar_wait(sb + SM_FULL + BAR_LAT * 8);
        uint4 a[8];
#pragma unroll
        for (int i = 0; i < 8; i++) a[i] = lds128(sb + SM_LAT + (lo ^ (i * 64)));
        int it = 0;
        while (refetch<0>(a, lane, [&](int i) { return (const char*)gs->lat[h] + (lo ^ (i * 64)); }))
            if (++it > SPIN_LIMIT) __trap();
        float v0 = 0.f, v1 = 0.f;
#pragma unroll
        for (int i = 0; i < 2; i++) {
            float c[4][4];
#pragma unroll
            for (int k = 0; k < 16; k++) (&c[0][0])[k] = 0.f;
            c[0][0] = v0; c[0][1] = v1;
            mbar_wait(sb + SM_FULL + (IT_WUV + i) * 8);
#pragma unroll
            for (int kk = 0; kk < 8; kk++) {
                uint32_t r0, r1, r2, r3;
                ldsm4t(base + slot_off(IT_WUV + i) + kk * 2048, r0, r1, r2, r3);
                mma16816(c[2 * (kk & 1)],     a[kk].x, a[kk].y, a[kk].z, a[kk].w, r0, r1);
                mma16816(c[2 * (kk & 1) + 1], a[kk].x, a[kk].y, a[kk].z, a[kk].w, r2, r3);
            }
            v0 = (c[0][0] + c[1][2]) + (c[2][0] + c[3][2]);
            v1 = (c[0][1] + c[1][3]) + (c[2][1] + c[3][3]);
            if (i == 0) { v0 = __shfl_xor_sync(0xffffffffu, v0, 16); v1 = __shfl_xor_sync(0xffffffffu, v1, 16); }
        }
        st_rlx_if(dst, pack_bf16(v0, v1), lane >= 16);
    }

    {
        const bool isB = slice >= 32;
        const int r = j & 1;
        const uint32_t xl = isB ? t * 64 + (((g ^ (t & 2)) & 3) << 4) : (g & 3) * 256 + ((g & 1) * 4 + t) * 16;
        const uint32_t cs = isB ? 256 : 64;
        const uint32_t xo = r * 8192 + (w >> 1) * 1024 + (w & 1) * 2 * cs + xl, xz = (1 - r) * 12288 + w * 1024 + (g >> 2) * 2 * cs + xl;
        auto xoff = [&](int i) { return i < 6 ? (i >> 1) * 4096 + (xo ^ ((i & 1) * cs)) : xz ^ ((i & 1) * cs); };
        const char* src = (const char*)gs->x[slice >> 5][r * 12];
        uint32_t off[2], ofz[2];
#pragma unroll
        for (int u = 0; u < 2; u++) {
            const int tt = (lane & 7) >> 1;
            const int row = 8 * tt + 2 * ((2 * u + (lane >> 4) + tt) & 3) + (lane & 1);
            off[u] = sb + w * 2048 + row * 32 + ((((lane >> 3) ^ (row >> 2)) & 1) << 4);
            ofz[u] = __shfl_sync(0xffffffffu, sb + (w < 4 ? slot_off(IT_WO + 3) : slot_off(IT_W2)) + (w & 3) * 4096 + (lane & 8) * 256 +
                                              row * 32 + (((r ^ (row >> 2)) & 1) << 4), lane);
        }
        const uint32_t fin = __shfl_sync(0xffffffffu, sb + SM_FIN + (t & 1) * 768 + g * 48 + ((w ^ (t & 1)) << 2), lane);
        const uint32_t fi2 = __shfl_sync(0xffffffffu, sb + SM_FIN + 3072 + (t & 1) * 1280 + g * 80 + (((w * 2 + (t >> 1)) ^ (t * 2 & 2)) << 2), lane);
        uint32_t a[2][4][4];
        uint4 x[8];
        float c[4][4];
        auto load_w = [&](int i) {
            mbar_wait(sb + SM_FULL + (i < 3 ? IT_WO + i : w < 4 ? IT_WO + 3 : IT_W2) * 8);
#pragma unroll
            for (int q = 0; q < 4; q++)
                ldsm4t((i < 3 ? slot_off(IT_WO + i) + off[q & 1] : ofz[q & 1]) + (q >> 1) * 1024,
                       a[i & 1][q][0], a[i & 1][q][1], a[i & 1][q][2], a[i & 1][q][3]);
        };
        auto mma_w = [&](int i) {
#pragma unroll
            for (int q = 0; q < 4; q++) {
                if (i == 0 || i == 3) c[q][0] = c[q][1] = c[q][2] = c[q][3] = 0.f;
                mma16816(c[q], a[i & 1][q][0], a[i & 1][q][1], a[i & 1][q][2], a[i & 1][q][3],
                         (q & 1) ? x[2 * i + (q >> 1)].z : x[2 * i + (q >> 1)].x, (q & 1) ? x[2 * i + (q >> 1)].w : x[2 * i + (q >> 1)].y);
            }
        };
        load_w(0); load_w(1);
        mbar_wait(sb + SM_FULL + BAR_X * 8);
#pragma unroll
        for (int i = 0; i < 8; i++) x[i] = lds128_if(sb + slot_off(IT_X) + xoff(i), i >= 6 || lane < 16);
        int it = 0;
        while (true) {
            mma_w(0); mma_w(1);
            if (!refetch<6>(x, lane, [&](int i) { return src + xoff(i); })) break;
            if (++it > SPIN_LIMIT) __trap();
        }
        load_w(2);
        mma_w(2);
#pragma unroll
        for (int e = 0; e < 4; e++) stsf_if(fin + (e >> 1) * 1536 + (e & 1) * 384, (c[0][e] + c[1][e]) + (c[2][e] + c[3][e]), t < 2);
        asm volatile("bar.arrive 5, 320;" ::: "memory");
        load_w(3);
        mma_w(3);
#pragma unroll
        for (int e = 0; e < 2; e++) {
            const float lo = (c[0][e] + c[1][e]) + (c[2][e] + c[3][e]), hi = (c[0][e + 2] + c[1][e + 2]) + (c[2][e + 2] + c[3][e + 2]);
            stsf(fi2 + e * 640, t < 2 ? lo : hi);
        }
        asm volatile("bar.arrive 7, 288;" ::: "memory");
    }
}

typedef CUresult (*EncodeTiledFn)(CUtensorMap*, CUtensorMapDataType, cuuint32_t, void*, const cuuint64_t*,
                                  const cuuint64_t*, const cuuint32_t*, const cuuint32_t*, CUtensorMapInterleave,
                                  CUtensorMapSwizzle, CUtensorMapL2promotion, CUtensorMapFloatOOBfill);

void encode_map(EncodeTiledFn enc, CUtensorMap* tm, const void* p, cuuint64_t cols, cuuint64_t rows,
                cuuint32_t brows, cuuint32_t bblk) {
    cuuint64_t dims[3] = {64, rows, cols / 64};
    cuuint64_t strides[2] = {cols * 2, 128};
    cuuint32_t box[3] = {64, brows, bblk};
    cuuint32_t es[3] = {1, 1, 1};
    enc(tm, CU_TENSOR_MAP_DATA_TYPE_BFLOAT16, 3, const_cast<void*>(p), dims, strides, box, es,
        CU_TENSOR_MAP_INTERLEAVE_NONE, CU_TENSOR_MAP_SWIZZLE_128B, CU_TENSOR_MAP_L2_PROMOTION_L2_256B,
        CU_TENSOR_MAP_FLOAT_OOB_FILL_NONE);
}

void encode_slice_map(EncodeTiledFn enc, CUtensorMap* tm, const void* p, cuuint64_t cols, cuuint64_t rows, cuuint32_t bcols) {
    cuuint64_t dims[3] = {cols, 256, rows / 256};
    cuuint64_t strides[2] = {cols * 2, cols * 512};
    cuuint32_t box[3] = {bcols, 256, 32 / bcols};
    cuuint32_t es[3] = {1, 1, 1};
    enc(tm, CU_TENSOR_MAP_DATA_TYPE_BFLOAT16, 3, const_cast<void*>(p), dims, strides, box, es, CU_TENSOR_MAP_INTERLEAVE_NONE,
        bcols == 16 ? CU_TENSOR_MAP_SWIZZLE_32B : CU_TENSOR_MAP_SWIZZLE_64B, CU_TENSOR_MAP_L2_PROMOTION_L2_128B,
        CU_TENSOR_MAP_FLOAT_OOB_FILL_NONE);
}

}

extern "C" void kernel_launch(void* const* d_in, const int* in_sizes, int n_in, void* d_out, int out_size) {
    (void)in_sizes; (void)n_in; (void)out_size;
    static EncodeTiledFn enc = nullptr;
    static Scratch* gs = nullptr;
    if (!enc) {
        cudaGetSymbolAddress((void**)&gs, g_scratch);
        void* fn = nullptr;
        cudaDriverEntryPointQueryResult qr;
        cudaGetDriverEntryPoint("cuTensorMapEncodeTiled", &fn, cudaEnableDefault, &qr);
        enc = (EncodeTiledFn)fn;
        cudaFuncSetAttribute(fused_decode_kernel, cudaFuncAttributeMaxDynamicSharedMemorySize, SM_END);
    }
    Maps maps;
    encode_map(enc, &maps.wuk, d_in[8], 4096, 512, 64, 2);
    encode_slice_map(enc, &maps.wuv, d_in[9], 4096, 512, 32);
    encode_slice_map(enc, &maps.woB, d_in[10], 512, 4096, 16);
    encode_slice_map(enc, &maps.woA, d_in[4], 512, 4096, 16);
    encode_map(enc, &maps.ckv, d_in[6], 512, 16384, 16, 8);
    fused_decode_kernel<<<NCTA, NTHR, SM_END>>>((const __nv_bfloat16*)d_in[0], (const __nv_bfloat16*)d_in[5],
                                                (const __nv_bfloat16*)d_in[7], (const __nv_bfloat16*)d_in[3],
                                                (const __nv_bfloat16*)d_in[1] + 3072 * 128, (const __nv_bfloat16*)d_in[2] + 3072 * 128,
                                                (__nv_bfloat16*)d_out, gs, maps);
}
```

```cpp
#include <cuda_runtime.h>
#include <cuda_bf16.h>
#include <cuda.h>
#include <stdint.h>

namespace {

constexpr int NCTA   = 128;
constexpr int NSLOT  = 13;
constexpr int SLOT   = 16384;
constexpr int NITEM  = 56;
constexpr int NTHR   = 384;

constexpr int INFLIGHT = 4;
constexpr int PACE     = 644;
constexpr int LEAD     = 500;
constexpr int TAPER    = 280;
constexpr int XLEAD    = 500;
constexpr int OPGAP    = 200;
constexpr int NWIN     = 4;
__device__ constexpr int win_pos(int k)  { return k == 0 ? 10 : k == 1 ? 20 : k == 2 ? 31 : 38; }
__device__ constexpr int win_late(int k) { return k == 0 ? 1890 : k == 1 ? 1860 : k == 2 ? 1900 : 1800; }
constexpr int GAIN     = 11;

constexpr int IT_WQB = 0, IT_WQA = 2, IT_WUK = 4, IT_K0 = 6, IT_Q = 14, IT_C = 16, IT_K1 = 24, IT_V0 = 32,
              IT_OP = 40, IT_V1 = 42, IT_WUV = 50, IT_WO = 52;
constexpr int IT_X = 56;
constexpr int IT_W2 = 58;
constexpr int BAR_LAT = 56, BAR_FIN = 57, BAR_X = 59, BAR_PEER = 60;

constexpr int SM_FULL  = NSLOT * SLOT;
constexpr int SM_EMPTY = SM_FULL + 512;
constexpr int SM_IN0   = SM_EMPTY + 512;
constexpr int SM_IN1   = SM_IN0 + 1088;
constexpr int SM_SC    = SM_IN1 + 1088;
constexpr int SM_PA    = SM_SC + 4096;
constexpr int SM_PF    = SM_PA + 2048;
constexpr int SM_MX    = SM_PF + 8192;
constexpr int SM_ML    = SM_MX + 1024;
constexpr int SM_RCV   = SM_ML + 128;
constexpr int SM_PACE  = SM_RCV + 144;
constexpr int SM_END   = SM_PACE + 32;
constexpr int SM_LAT   = SM_PF + 4096;
constexpr int SM_FIN   = SM_SC;
constexpr int SM_SUM   = SM_IN0;
static_assert(SM_END <= 232448, "smem");

struct Maps { CUtensorMap wuk, wuv, woA, woB, ckv; };

struct Scratch {
    unsigned cnt[32];
    unsigned late[32];
    float    part[2][NCTA][512];
    uint32_t x[2][32][256];
    uint32_t lat[32][4][256];
    uint4    q[4][2048];
    uint4    op[NCTA][2048];
    float2   stat[32][128];
};
__device__ __align__(128) Scratch g_scratch;

constexpr int SPIN_LIMIT = 1 << 22;

__device__ __forceinline__ uint32_t smem_u32(const void* p) { return (uint32_t)__cvta_generic_to_shared(p); }
__device__ __forceinline__ void mbar_init(uint32_t bar, uint32_t cnt) {
    asm volatile("mbarrier.init.shared::cta.b64 [%0], %1;" ::"r"(bar), "r"(cnt) : "memory");
}
__device__ __forceinline__ void mbar_expect_tx(uint32_t bar, uint32_t bytes) {
    asm volatile("mbarrier.arrive.expect_tx.shared::cta.b64 _, [%0], %1;" ::"r"(bar), "r"(bytes) : "memory");
}
__device__ __forceinline__ void mbar_arrive(uint32_t bar) {
    asm volatile("mbarrier.arrive.shared::cta.b64 _, [%0];" ::"r"(bar) : "memory");
}
__device__ __forceinline__ void mbar_arrive8(uint32_t bar) {
    asm volatile("mbarrier.arrive.shared::cta.b64 _, [%0], 8;" ::"r"(bar) : "memory");
}
__device__ __forceinline__ void mbar_wait(uint32_t bar) {
    uint32_t done;
    int it = 0;
    do {
        asm volatile("{\n.reg .pred p;\nmbarrier.try_wait.parity.shared::cta.b64 p, [%1], 0;\nselp.u32 %0, 1, 0, p;\n}"
                     : "=r"(done) : "r"(bar) : "memory");
        if (++it > SPIN_LIMIT) __trap();
    } while (!done);
}
__device__ __forceinline__ uint32_t map_cta(uint32_t a, uint32_t rank) {
    uint32_t r; asm("mapa.shared::cluster.u32 %0, %1, %2;" : "=r"(r) : "r"(a), "r"(rank)); return r;
}
__device__ __forceinline__ void st_async32(uint32_t a, uint32_t v, uint32_t bar) {
    asm volatile("st.async.shared::cluster.mbarrier::complete_tx::bytes.b32 [%0], %1, [%2];" ::"r"(a), "r"(v), "r"(bar) : "memory");
}
__device__ __forceinline__ uint64_t evict_first() {
    uint64_t pol; asm volatile("createpolicy.fractional.L2::evict_first.b64 %0, 1.0;" : "=l"(pol)); return pol;
}
#define ELECT "{\n.reg .pred p;\nelect.sync _|p, 0xffffffff;\n@p "
__device__ __forceinline__ void bulk_load(uint32_t dst, const void* src, uint32_t bytes, uint32_t bar, uint64_t pol) {
    asm volatile(ELECT "cp.async.bulk.shared::cluster.global.mbarrier::complete_tx::bytes.L2::cache_hint [%0], [%1], %2, [%3], %4;\n}"
                 ::"r"(dst), "l"(src), "r"(bytes), "r"(bar), "l"(pol) : "memory");
}
__device__ __forceinline__ void bulk_load_nohint(uint32_t dst, const void* src, uint32_t bytes, uint32_t bar) {
    asm volatile("cp.async.bulk.shared::cluster.global.mbarrier::complete_tx::bytes [%0], [%1], %2, [%3];"
                 ::"r"(dst), "l"(src), "r"(bytes), "r"(bar) : "memory");
}
__device__ __forceinline__ void tma3d(uint32_t dst, const CUtensorMap* tm, int c0, int c1, int c2, uint32_t bar, uint64_t pol) {
    asm volatile(ELECT "cp.async.bulk.tensor.3d.shared::cluster.global.mbarrier::complete_tx::bytes.L2::cache_hint [%0], [%1, {%3, %4, %5}], [%2], %6;\n}"
                 ::"r"(dst), "l"(tm), "r"(bar), "r"(c0), "r"(c1), "r"(c2), "l"(pol) : "memory");
}
__device__ __forceinline__ void tma3d_pair(uint32_t dst, const CUtensorMap* tm, int c0, int c1, int c2, uint32_t bar, uint64_t pol) {
    asm volatile(ELECT "cp.async.bulk.tensor.3d.shared::cluster.global.mbarrier::complete_tx::bytes.multicast::cluster.L2::cache_hint [%0], [%1, {%3, %4, %5}], [%2], %7, %6;\n}"
                 ::"r"(dst), "l"(tm), "r"(bar), "r"(c0), "r"(c1), "r"(c2), "l"(pol), "h"((uint16_t)3) : "memory");
}
__device__ __forceinline__ void ldsm4(uint32_t a, uint32_t& r0, uint32_t& r1, uint32_t& r2, uint32_t& r3) {
    asm volatile("ldmatrix.sync.aligned.m8n8.x4.shared.b16 {%0,%1,%2,%3}, [%4];"
                 : "=r"(r0), "=r"(r1), "=r"(r2), "=r"(r3) : "r"(a) : "memory");
}
__device__ __forceinline__ void ldsm4t(uint32_t a, uint32_t& r0, uint32_t& r1, uint32_t& r2, uint32_t& r3) {
    asm volatile("ldmatrix.sync.aligned.m8n8.x4.trans.shared.b16 {%0,%1,%2,%3}, [%4];"
                 : "=r"(r0), "=r"(r1), "=r"(r2), "=r"(r3) : "r"(a) : "memory");
}
__device__ __forceinline__ void mma16816(float (&c)[4], uint32_t a0, uint32_t a1, uint32_t a2, uint32_t a3,
                                         uint32_t b0, uint32_t b1) {
    asm volatile("mma.sync.aligned.m16n8k16.row.col.f32.bf16.bf16.f32 {%0,%1,%2,%3}, {%4,%5,%6,%7}, {%8,%9}, {%0,%1,%2,%3};"
                 : "+f"(c[0]), "+f"(c[1]), "+f"(c[2]), "+f"(c[3])
                 : "r"(a0), "r"(a1), "r"(a2), "r"(a3), "r"(b0), "r"(b1));
}
__device__ __forceinline__ uint32_t lds32(uint32_t a) {
    uint32_t v; asm volatile("ld.shared.b32 %0, [%1];" : "=r"(v) : "r"(a) : "memory"); return v;
}
__device__ __forceinline__ float ldsf(uint32_t a) {
    float v; asm volatile("ld.shared.f32 %0, [%1];" : "=f"(v) : "r"(a) : "memory"); return v;
}
__device__ __forceinline__ float2 ldsf2(uint32_t a) {
    float2 v; asm volatile("ld.shared.v2.f32 {%0,%1}, [%2];" : "=f"(v.x), "=f"(v.y) : "r"(a) : "memory"); return v;
}
__device__ __forceinline__ float4 ldsf4(uint32_t a) {
    float4 v; asm volatile("ld.shared.v4.f32 {%0,%1,%2,%3}, [%4];" : "=f"(v.x), "=f"(v.y), "=f"(v.z), "=f"(v.w) : "r"(a) : "memory"); return v;
}
__device__ __forceinline__ uint4 lds128(uint32_t a) {
    uint4 v; asm volatile("ld.shared.v4.b32 {%0,%1,%2,%3}, [%4];" : "=r"(v.x), "=r"(v.y), "=r"(v.z), "=r"(v.w) : "r"(a) : "memory"); return v;
}
__device__ __forceinline__ uint4 lds128_if(uint32_t a, bool on) {
    uint4 v;
    asm volatile("{\n.reg .pred p;\nsetp.ne.u32 p, %5, 0;\n@p ld.shared.v4.b32 {%0,%1,%2,%3}, [%4];\n}"
                 : "=r"(v.x), "=r"(v.y), "=r"(v.z), "=r"(v.w) : "r"(a), "r"((uint32_t)on) : "memory");
    return v;
}
__device__ __forceinline__ void stsf_if(uint32_t a, float v, bool on) {
    asm volatile("{\n.reg .pred p;\nsetp.ne.u32 p, %2, 0;\n@p st.shared.f32 [%0], %1;\n}" ::"r"(a), "f"(v), "r"((uint32_t)on) : "memory");
}
__device__ __forceinline__ void sts16(uint32_t a, uint16_t v) { asm volatile("st.shared.b16 [%0], %1;" ::"r"(a), "h"(v) : "memory"); }
__device__ __forceinline__ void sts32(uint32_t a, uint32_t v) { asm volatile("st.shared.b32 [%0], %1;" ::"r"(a), "r"(v) : "memory"); }
__device__ __forceinline__ void stsf(uint32_t a, float v) { asm volatile("st.shared.f32 [%0], %1;" ::"r"(a), "f"(v) : "memory"); }
__device__ __forceinline__ void sts64(uint32_t a, uint32_t x, uint32_t y) {
    asm volatile("st.shared.v2.b32 [%0], {%1,%2};" ::"r"(a), "r"(x), "r"(y) : "memory");
}
__device__ __forceinline__ void sts128(uint32_t a, uint4 v) {
    asm volatile("st.shared.v4.b32 [%0], {%1,%2,%3,%4};" ::"r"(a), "r"(v.x), "r"(v.y), "r"(v.z), "r"(v.w) : "memory");
}
__device__ __forceinline__ uint32_t pack_bf16(float lo, float hi) {
    uint32_t r; asm("cvt.rn.bf16x2.f32 %0, %1, %2;" : "=r"(r) : "f"(hi), "f"(lo)); return r;
}
__device__ __forceinline__ float bf_lo(uint32_t v) { return __uint_as_float(v << 16); }
__device__ __forceinline__ float bf_hi(uint32_t v) { return __uint_as_float(v & 0xffff0000u); }
__device__ __forceinline__ float ex2(float x) { float y; asm("ex2.approx.ftz.f32 %0, %1;" : "=f"(y) : "f"(x)); return y; }
__device__ __forceinline__ uint32_t timer_ns() { uint32_t t; asm volatile("mov.u32 %0, %%globaltimer_lo;" : "=r"(t)); return t; }
__device__ __forceinline__ void bar_consumers() { asm volatile("bar.sync 1, 256;" ::: "memory"); }
__device__ __forceinline__ void bar_setup() { asm volatile("bar.sync 2, 384;" ::: "memory"); }

__device__ __forceinline__ uint32_t tagf(float v, uint32_t tag) { return (__float_as_uint(v) & 0xffffff00u) | tag; }
__device__ __forceinline__ uint2 ld_rlx2(const float* p) {
    uint2 v; asm volatile("ld.relaxed.gpu.global.v2.b32 {%0,%1}, [%2];" : "=r"(v.x), "=r"(v.y) : "l"(p) : "memory"); return v;
}
__device__ __forceinline__ float untag(uint32_t v) { return __uint_as_float(v & 0xffffff00u); }

__device__ __forceinline__ uint32_t slot_off(int item) { return (uint32_t)(item % NSLOT) * SLOT; }

template <bool TRANS, bool TMA = true>
__device__ __forceinline__ void tile_mma(uint32_t sb, int item, uint32_t in, int w, int lane, float (&acc)[2][2]) {
    const int g = lane >> 2, t = lane & 3;
    float c[4][4];
#pragma unroll
    for (int i = 0; i < 16; i++) (&c[0][0])[i] = 0.f;
    uint32_t a[16];
    const uint32_t ia = in + (g & 3) * 272 + t * 4;
#pragma unroll
    for (int i = 0; i < 16; i++) a[i] = lds32(ia + i * 16);
    const uint32_t s0 = sb + slot_off(item), s1 = sb + slot_off(item + 1);
    if (TRANS) {
        const int r = (lane & 7) + (lane & 8);
        const int ch = 2 * (w & 3) + (lane >> 4);
        const uint32_t off = (TMA ? (w >> 2) * 8192 + r * 128 : (w >> 2) * 128 + r * 256) + ((ch ^ (lane & 7)) << 4);
#pragma unroll
        for (int kk = 0; kk < 8; kk++) {
            if (TMA && (kk & 3) == 0) mbar_wait(sb + SM_FULL + (item + (kk >> 2)) * 8);
            uint32_t r0, r1, r2, r3;
            ldsm4t(((kk >> 2) ? s1 : s0) + off + (kk & 3) * (TMA ? 2048 : 4096), r0, r1, r2, r3);
            mma16816(c[2 * (kk & 1)],     a[2 * kk], 0u, a[2 * kk + 1], 0u, r0, r1);
            mma16816(c[2 * (kk & 1) + 1], a[2 * kk], 0u, a[2 * kk + 1], 0u, r2, r3);
        }
    } else {
        mbar_wait(sb + SM_FULL + (item + (w >> 2)) * 8);
        const int r = 16 * (w & 3) + (lane & 7) + ((lane >> 4) << 3);
        const uint32_t base = ((w >> 2) ? s1 : s0) + (r & 32) * 128 + r * 128 + ((((lane >> 3) & 1) ^ (lane & 7)) << 4);
#pragma unroll
        for (int kk = 0; kk < 8; kk++) {
            uint32_t r0, r1, r2, r3;
            ldsm4((base ^ ((kk & 3) << 5)) + (kk >> 2) * 4096, r0, r1, r2, r3);
            mma16816(c[2 * (kk & 1)],     a[2 * kk], 0u, a[2 * kk + 1], 0u, r0, r1);
            mma16816(c[2 * (kk & 1) + 1], a[2 * kk], 0u, a[2 * kk + 1], 0u, r2, r3);
        }
    }
    __syncwarp();
    if (lane == 0) {
        mbar_arrive(sb + SM_EMPTY + item * 8);
        mbar_arrive(sb + SM_EMPTY + (item + 1) * 8);
    }
    acc[0][0] = c[0][0] + c[2][0]; acc[0][1] = c[0][1] + c[2][1];
    acc[1][0] = c[1][0] + c[3][0]; acc[1][1] = c[1][1] + c[3][1];
}

__device__ __forceinline__ void publish(float* dst, int w, int lane, const float (&acc)[2][2], uint32_t tag) {
    if (lane < 16)
        asm volatile("st.relaxed.gpu.global.v4.b32 [%0], {%1,%2,%3,%4};" ::"l"(dst + w * 64 + lane * 4),
                     "r"(tagf(acc[0][0], tag)), "r"(tagf(acc[0][1], tag)), "r"(tagf(acc[1][0], tag)), "r"(tagf(acc[1][1], tag)) : "memory");
}

__device__ __forceinline__ void gather(const float* part, uint32_t in, int tid, uint32_t tag) {
    const float* p = part + tid * 2;
    uint2 v0, v1, v2, v3;
    int it = 0;
    while (true) {
        v0 = ld_rlx2(p); v1 = ld_rlx2(p + 512); v2 = ld_rlx2(p + 1024); v3 = ld_rlx2(p + 1536);
        uint32_t bad = ((v0.x ^ tag) | (v0.y ^ tag) | (v1.x ^ tag) | (v1.y ^ tag) |
                        (v2.x ^ tag) | (v2.y ^ tag) | (v3.x ^ tag) | (v3.y ^ tag)) & 0xffu;
        if (__all_sync(0xffffffffu, bad == 0)) break;
        if (++it > SPIN_LIMIT) __trap();
    }
    float x = (untag(v0.x) + untag(v1.x)) + (untag(v2.x) + untag(v3.x));
    float y = (untag(v0.y) + untag(v1.y)) + (untag(v2.y) + untag(v3.y));
    sts32(in + ((tid >> 3) & 3) * 272 + (tid >> 5) * 32 + (tid & 1) * 16 + (tid & 6) * 2, pack_bf16(x, y));
    bar_consumers();
}

constexpr uint32_t EMPTY = 0xffffffffu;
__device__ __forceinline__ void st_rlx(uint32_t* p, uint32_t v) {
    asm volatile("st.relaxed.gpu.global.b32 [%0], %1;" ::"l"(p), "r"(v) : "memory");
}
__device__ __forceinline__ void st_rlx_if(uint64_t p, uint32_t v, bool on) {
    asm volatile("{\n.reg .pred p;\nsetp.ne.u32 p, %2, 0;\n@p st.relaxed.gpu.global.b32 [%0], %1;\n}" ::"l"(p), "r"(v), "r"((uint32_t)on) : "memory");
}
__device__ __forceinline__ void st_rlx2(uint32_t* p, uint32_t v0, uint32_t v1) {
    asm volatile("st.relaxed.gpu.global.v2.b32 [%0], {%1,%2};" ::"l"(p), "r"(v0), "r"(v1) : "memory");
}
__device__ __forceinline__ void ld_rlx4_if(uint4& v, const void* p, bool need) {
    asm volatile("{\n.reg .pred p;\nsetp.ne.u32 p, %5, 0;\n@p ld.relaxed.gpu.global.v4.b32 {%0,%1,%2,%3}, [%4];\n}"
                 : "+r"(v.x), "+r"(v.y), "+r"(v.z), "+r"(v.w) : "l"(p), "r"((uint32_t)need) : "memory");
}

template <int HALF, class F>
__device__ __forceinline__ bool refetch(uint4 (&x)[8], int lane, F addr) {
    uint32_t m[8], m0 = 0, m1 = 0;
#pragma unroll
    for (int i = 0; i < 8; i++) {
        m[i] = max(max(x[i].x, x[i].y), max(x[i].z, x[i].w));
        if (i < HALF) m0 = max(m0, m[i]); else m1 = max(m1, m[i]);
    }
    if (!__any_sync(0xffffffffu, (m0 == EMPTY && lane < 16) || m1 == EMPTY)) return false;
#pragma unroll
    for (int i = 0; i < 8; i++) ld_rlx4_if(x[i], addr(i), m[i] == EMPTY && (i >= HALF || lane < 16));
    return true;
}

__device__ __forceinline__ unsigned read_counter(const unsigned* cnt) {
    unsigned v;
    asm volatile("ld.relaxed.gpu.global.u32 %0, [%1];" : "=r"(v) : "l"(cnt) : "memory");
    return v;
}
__device__ __forceinline__ unsigned epoch_of(unsigned cnt) {
    asm volatile("" : "+r"(cnt) :: "memory");
    return cnt / NCTA + 1;
}
__device__ __forceinline__ uint32_t epoch_tag(unsigned epoch) { return (epoch & 0x7fu) | 0x80u; }

__device__ __forceinline__ void signal_and_wait(unsigned* cnt, unsigned target, int lane) {
    if (lane == 0) asm volatile("red.release.gpu.global.add.u32 [%0], 1;" ::"l"(cnt) : "memory");
    int it = 0;
    while (true) {
        unsigned v;
        asm volatile("ld.acquire.gpu.global.u32 %0, [%1];" : "=r"(v) : "l"(cnt) : "memory");
        if (__all_sync(0xffffffffu, (int)(v - target) >= 0)) break;
        if (++it > SPIN_LIMIT) __trap();
    }
    asm volatile("fence.proxy.async.global;" ::: "memory");
}

__global__ void __cluster_dims__(2, 1, 1) __launch_bounds__(NTHR, 1)
fused_decode_kernel(const __nv_bfloat16* __restrict__ xA, const __nv_bfloat16* __restrict__ xB,
                    const __nv_bfloat16* __restrict__ wqB, const __nv_bfloat16* __restrict__ wqA,
                    const __nv_bfloat16* __restrict__ Kc, const __nv_bfloat16* __restrict__ Vc,
                    __nv_bfloat16* __restrict__ out, Scratch* gs, const __grid_constant__ Maps maps) {
    extern __shared__ __align__(1024) unsigned char smem_raw[];
    const uint32_t sb = smem_u32(smem_raw);
    const int tid = threadIdx.x, lane = tid & 31;
    const int cta = blockIdx.x, h = cta >> 2, j = cta & 3;
    const size_t kv_off = (size_t)blockIdx.x * 4096 * 128;
    const uint32_t trow = threadIdx.x >> 4;
    const uint32_t tile_src = trow * (8192 - 256) + (threadIdx.x * 16 + ((blockIdx.x * 0x100040u) & 0x301f00u));
    const uint32_t tile_dst = sb + ((threadIdx.x ^ (trow & 7)) << 4);
    auto lsu_tile = [&](const __nv_bfloat16* W, int item) {
#pragma unroll
        for (int q = 0; q < 8; q++)
            asm volatile("cp.async.cg.shared.global [%0], [%1], 16;" ::"r"(tile_dst + item * SLOT + q * 4096),
                         "l"(reinterpret_cast<const char*>(W + q * 16 * 4096) + tile_src) : "memory");
        asm volatile("cp.async.commit_group;" ::: "memory");
    };
    if (tid < 256) lsu_tile(wqB, IT_WQB);
    const uint32_t tz = timer_ns() - LEAD;
    const unsigned cnt1 = read_counter(&gs->cnt[1]);
    uint4 xv;
    if (tid < 128) {
        const __nv_bfloat16* x = (tid < 64 ? xB : xA) + ((tid >> 4) & 3) * 512 + j * 128 + (tid & 15) * 8;
        xv = __ldg(reinterpret_cast<const uint4*>(x));
    }
    const int w = __shfl_sync(0xffffffffu, tid >> 5, 0);
    const int pr = cta >> 1;
    const int slice = pr < 4 ? pr : pr < 36 ? 4 + ((pr - 4) & 7) * 4 + ((pr - 4) >> 3) : 36 + (pr - 36) % 7 * 4 + (pr - 36) / 7;

    if (w == 10) {
        if (lane == 0) sts64(sb + SM_PACE, tz, PACE * 16);
        bar_setup();
        if (lane == 0) {
            int slope = 0;
#pragma unroll
            for (int k = 0; k < NWIN; k++) {
                const int c = win_pos(k);
                uint32_t acc = 0;
#pragma unroll
                for (int p = c; p < c + 4; p++) {
                    mbar_wait(sb + SM_FULL + (p < IT_Q ? p : p < IT_OP - 2 ? p + 2 : p + 4) * 8);
                    acc += timer_ns() - tz - p * PACE - ((p * slope) >> 4);
                }
                if (k == 0) mbar_wait(sb + SM_FULL + IT_Q * 8);
                asm volatile("red.relaxed.gpu.global.add.u32 [%0], %1;" ::"l"(&gs->late[k]), "r"((1u << 24) + min(acc >> 2, 65535u)) : "memory");
                uint32_t v;
                int it = 0;
                do { v = read_counter(&gs->late[k]); } while ((v >> 24) != NCTA && ++it < 1000);
                const int late = (v & 0xffffffu) / NCTA;
                slope = max(-320, min(320, slope + (late - win_late(k)) * (GAIN * 2) / (2 * c + 3)));
                sts64(sb + SM_PACE, tz, PACE * 16 + slope);
            }
        }
        return;
    }
    if (w >= 8) {
        auto wait_due = [&](uint32_t p, uint32_t shift) {
            uint32_t a, b;
            do {
                asm volatile("ld.volatile.shared.v2.b32 {%0,%1}, [%2];" : "=r"(a), "=r"(b) : "r"(sb + SM_PACE) : "memory");
            } while (__all_sync(0xffffffffu, (int)(timer_ns() - (a + ((p * b) >> 4) + shift)) < 0));
        };
        if (w != 9) {
            bar_setup();
            const int half = w & 1;
            const uint64_t pol = evict_first();
            int slot = IT_WUK, tail = IT_WUK - INFLIGHT;
            uint32_t np = IT_WUK, shift = half ? PACE / 4 : -(PACE / 4);
#pragma unroll 1
            for (int i = IT_WUK; i < NITEM; i++) {
                const uint32_t dst = sb + slot * SLOT + half * (SLOT / 2), bar = sb + SM_FULL + i * 8;
                if (++slot == NSLOT) slot = 0;
                if ((i & ~1) == IT_Q || (i & ~1) == IT_OP) continue;
                const bool ckv = i >= IT_C && i < IT_K1, wo = i >= IT_WO;
                const bool tiled = ckv || i < IT_K0 || i >= IT_WUV;
                const CUtensorMap* tm = &maps.wuk + (i < IT_K0 ? 0 : ckv ? 4 : wo ? 2 + (slice >> 5) : 1);
                const int c0 = wo ? (slice & 31) * 16 : i >= IT_WUV ? cta * 32 : 0;
                const int c1 = i < IT_K0 ? j * 128 + (i & 1) * 64 + half * 32 : ckv ? cta * 128 + (i - IT_C) * 16 + half * 8 : wo ? 0 : half * 128;
                const int c2 = i < IT_K0 ? h * 2 : ckv ? 0 : wo ? (i - IT_WO) * 4 + (j & 1) * 2 + half : i & 1;
                const int c = i < IT_Q ? i - IT_K0 : i < IT_V0 ? i - IT_K1 + 8 : i < IT_OP ? i - IT_V0 : i - IT_V1 + 8;
                const __nv_bfloat16* src = (i < IT_V0 ? Kc : Vc) + kv_off + (size_t)(c * 2 + half) * (SLOT / 4);
                if (i >= NSLOT) mbar_wait(sb + SM_EMPTY + (i - NSLOT) * 8);
                if (tail >= IT_WUK) mbar_wait(sb + SM_FULL + tail * 8);
                ++tail;
                if (tail == IT_Q || tail == IT_OP) tail += 2;
                if (i == NITEM - 1) mbar_wait(sb + SM_FULL + BAR_PEER * 8);
                wait_due(np, shift);
                ++np;
                if (i == IT_WUV - 1) shift += TAPER;
                if (i == NITEM - 1) tma3d_pair(dst + (j & 1) * (IT_W2 - i) * SLOT, tm, c0, c1, c2, bar + (j & 1) * (IT_W2 - i) * 8, pol);
                else if (tiled) tma3d(dst, tm, c0, c1, c2, bar, pol);
                else bulk_load(dst, src, SLOT / 2, bar, pol);
            }
            if (half) return;
        } else {
            if (lane == 0) {
                mbar_init(sb + SM_FULL + IT_W2 * 8, 1);
                mbar_init(sb + SM_FULL + BAR_X * 8, 1);
                mbar_init(sb + SM_FULL + BAR_PEER * 8, 1);
                mbar_expect_tx(sb + SM_FULL + IT_W2 * 8, SLOT);
                mbar_expect_tx(sb + SM_FULL + BAR_X * 8, SLOT + 4096);
                mbar_expect_tx(sb + SM_FULL + BAR_PEER * 8, 8);
                asm volatile("fence.mbarrier_init.release.cluster;" ::: "memory");
            }
            if (lane < sizeof(Maps) / 128) asm volatile("prefetch.tensormap [%0];" ::"l"(&maps.wuk + lane) : "memory");
            bar_setup();
            asm volatile("bar.sync 3, 288;" ::: "memory");
            const unsigned epoch = epoch_of(cnt1);
            signal_and_wait(&gs->cnt[0], epoch * NCTA, lane);
            if (lane == 0) {
                const uint4* q = gs->q[cta >> 5];
                bulk_load_nohint(sb + slot_off(IT_Q), q, SLOT, sb + SM_FULL + IT_Q * 8);
                bulk_load_nohint(sb + slot_off(IT_Q + 1), q + 1024, SLOT, sb + SM_FULL + (IT_Q + 1) * 8);
            }
            asm volatile("bar.sync 3, 288;" ::: "memory");
            signal_and_wait(&gs->cnt[1], epoch * NCTA, lane);
            mbar_wait(sb + SM_EMPTY + (IT_OP - NSLOT) * 8);
            mbar_wait(sb + SM_EMPTY + (IT_OP + 1 - NSLOT) * 8);
            if (lane == 0) {
                const uint4* op = gs->op[cta];
                bulk_load_nohint(sb + SM_MX, gs->stat[h], 1024, sb + SM_FULL + IT_OP * 8);
                uint32_t t1 = timer_ns();
#pragma unroll 1
                for (int i = 0; i < 8; i++) {
                    while ((int)(timer_ns() - t1) < 0) {}
                    t1 += OPGAP;
                    bulk_load_nohint(sb + slot_off(IT_OP) + i * 4096, op + i * 256, 4096, sb + SM_FULL + (IT_OP + i / 4) * 8);
                }
            }
            mbar_wait(sb + SM_FULL + (IT_V1 + 4) * 8);
            if (lane == 0) bulk_load_nohint(sb + SM_LAT, gs->lat[h], 4096, sb + SM_FULL + BAR_LAT * 8);
            mbar_wait(sb + SM_EMPTY + (IT_X - NSLOT) * 8);
            mbar_wait(sb + SM_EMPTY + (IT_X + 1 - NSLOT) * 8);
            wait_due(NITEM - 5, TAPER - XLEAD);
            if (lane == 0)
                bulk_load_nohint(sb + slot_off(IT_X), gs->x[slice >> 5][(j & 1) * 12], SLOT + 4096, sb + SM_FULL + BAR_X * 8);
        }
        const uint32_t oo  = __shfl_sync(0xffffffffu, (lane >> 3) * 2048 + slice * 32 + (j & 1) * 16 + (lane & 7) * 2, lane);
        const uint32_t src = __shfl_sync(0xffffffffu, sb + SM_FIN + ((j ^ w ^ 1) & 1) * 1536 + lane * 48, lane);
        const uint32_t sr2 = __shfl_sync(0xffffffffu, sb + SM_FIN + 3072 + lane * 80, lane);
        const uint32_t to  = w == 8 ? map_cta(sb, (j & 1) ^ 1) : sb;
        const uint32_t rcv = __shfl_sync(0xffffffffu, to + SM_RCV + lane * 4, lane);
        const uint32_t fin = __shfl_sync(0xffffffffu, to + SM_FULL + BAR_FIN * 8, lane);
        mbar_wait(sb + SM_FULL + (NITEM - 3) * 8);
        asm volatile("bar.sync 5, 320;" ::: "memory");
        const float4 p0 = ldsf4(src), p1 = ldsf4(src + 16);
        float sum = ((p0.x + p0.y) + (p0.z + p0.w)) + ((p1.x + p1.y) + (p1.z + p1.w));
        if (w == 8) {
            st_async32(rcv, __float_as_uint(sum), fin);
        } else {
            __nv_bfloat16* dst = reinterpret_cast<__nv_bfloat16*>(reinterpret_cast<char*>(out) + oo);
            mbar_wait(sb + SM_FULL + BAR_FIN * 8);
            sum += ldsf(rcv);
            asm volatile("bar.sync 7, 288;" ::: "memory");
            const float4 q0 = ldsf4(sr2), q1 = ldsf4(sr2 + 16), q2 = ldsf4(sr2 + 32), q3 = ldsf4(sr2 + 48);
            *dst = __float2bfloat16((((q0.x + sum) + q0.y) + (q0.z + q0.w) + ((q1.x + q1.y) + (q1.z + q1.w))) +
                                    (((q2.x + q2.y) + (q2.z + q2.w)) + ((q3.x + q3.y) + (q3.z + q3.w))));
        }
        return;
    }

    const int g = lane >> 2, t = lane & 3;
    const uint32_t in0 = sb + SM_IN0, in1 = sb + SM_IN1;
    auto xpos = [](int hh) { return (hh & 4) * 4 + (((hh >> 3) + (hh >> 2 & 1)) & 3) * 4 + (hh & 3); };
    const int ba = cta >> 5, ha = cta & 31;
    uint32_t* const ctx_dst = &gs->x[1][xpos(h)][(j * 4 + (w & 3)) * 16 + ((g ^ (w & 2)) & 3) * 4 + ((t - w) & 3)];
    uint32_t* const o_dst = &gs->x[0][xpos(ha)][ba * 64 + ((tid & 60) ^ ((ba & 1) * 16)) + ((t - g) & 3)];
    uint32_t* const lat_dst = &gs->lat[h][g & 3][j * 64 + ((w >> 1) ^ (g & 1)) * 16 + t * 4 + ((w * 2 ^ t) & 2)];
    {
        if (lane == 0) {
            const uint32_t bars = sb + (w < 4 ? SM_EMPTY : SM_FULL + 2 * 8) + (w & 3) * 14 * 8;
            const uint32_t cnt = w < 4 ? 8 : 1;
#pragma unroll
            for (int i = 0; i < 14; i++) mbar_init(bars + i * 8, cnt);
            if (w >= 4) {
#pragma unroll
                for (int i = 0; i < 14; i++)
                    mbar_expect_tx(bars + i * 8, (i == (IT_OP - 2) % 14 && w == 4 + (IT_OP - 2) / 14) ? SLOT + 1024 :
                                                 (i >= 12 && w == 7) ? (i == 12 ? 4096 : 128) : SLOT);
            }
            asm volatile("fence.mbarrier_init.release.cluster;" ::: "memory");
        }
        lsu_tile(wqA, IT_WQA);
        bar_setup();
        if (lane < 16) st_rlx2(lat_dst, EMPTY, EMPTY);
        if (lane >= 16 && w < 4) st_rlx(ctx_dst, EMPTY);
        if (w >= 6) st_rlx(o_dst, EMPTY);
        if (cta == 0 && w == 5) st_rlx(&gs->late[lane], 0u);
        if (tid < 128) sts128((tid < 64 ? in0 : in1) + ((tid >> 4) & 3) * 272 + (tid & 15) * 16, xv);
        asm volatile("cp.async.wait_group 1;" ::: "memory");
    }
    bar_consumers();
    const uint32_t tag = epoch_tag(epoch_of(cnt1));

    float acc[2][2];
    tile_mma<true, false>(sb, IT_WQB, in0, w, lane, acc);
    publish(gs->part[0][cta], w, lane, acc, tag);
    asm volatile("cp.async.wait_group 0;" ::: "memory");
    bar_consumers();
    tile_mma<true, false>(sb, IT_WQA, in1, w, lane, acc);
    publish(gs->part[1][cta], w, lane, acc, tag);
    bar_consumers();

    const float SC = 0.08838834764831845f * 1.4426950408889634f;
    gather(gs->part[0][h * 4], in0, tid, tag);
    tile_mma<false>(sb, IT_WUK, in0, w, lane, acc);
    if (lane < 16) {
        uint32_t* q = reinterpret_cast<uint32_t*>(gs->q[g]) + (2 * j + (w >> 2)) * 1024 + h * 32 + t;
        const int ch = 2 * (w & 3);
        q[((ch) ^ (h & 7)) * 4]     = pack_bf16(acc[0][0] * SC, acc[0][1] * SC);
        q[((ch + 1) ^ (h & 7)) * 4] = pack_bf16(acc[1][0] * SC, acc[1][1] * SC);
    }
    __syncwarp();
    asm volatile("bar.arrive 3, 288;" ::: "memory");
    gather(gs->part[1][ha * 4], in1, tid, tag);

    uint32_t qf[16];
#pragma unroll
    for (int c = 0; c < 8; c++) {
        qf[2 * c]     = lds32(in1 + ba * 272 + ((c ^ g) << 4) + t * 4);
        qf[2 * c + 1] = lds32(in1 + ba * 272 + 128 + ((c ^ g) << 4) + t * 4);
    }
    const uint32_t sc_w = sb + SM_SC + w * 512;
    auto k_item = [&](int item, uint32_t sc) {
        mbar_wait(sb + SM_FULL + item * 8);
        const uint32_t base = sb + slot_off(item) + ((lane & 7) + (lane & 8)) * 256 + ((lane >> 4) << 7);
        float s[4][4];
#pragma unroll
        for (int T = 0; T < 4; T++) { s[T][0] = s[T][1] = s[T][2] = s[T][3] = 0.f; }
#pragma unroll
        for (int c = 0; c < 8; c++) {
            const uint32_t a = base + ((c ^ (lane & 7)) << 4);
#pragma unroll
            for (int T = 0; T < 4; T++) {
                uint32_t r0, r1, r2, r3;
                ldsm4(a + T * 4096, r0, r1, r2, r3);
                mma16816(s[T], r0, r1, r2, r3, qf[2 * c], qf[2 * c + 1]);
            }
        }
        __syncwarp();
        if (lane == 0) mbar_arrive8(sb + SM_EMPTY + item * 8);
        if (t == (g >> 1)) {
#pragma unroll
            for (int T = 0; T < 4; T++) {
                stsf(sc + (16 * T + g) * 4,     (g & 1) ? s[T][1] : s[T][0]);
                stsf(sc + (16 * T + g + 8) * 4, (g & 1) ? s[T][3] : s[T][2]);
            }
        }
    };
    k_item(IT_K0 + w, sc_w);

    {
        float s[2][2][4];
#pragma unroll
        for (int i = 0; i < 16; i++) (&s[0][0][0])[i] = 0.f;
        mbar_wait(sb + SM_FULL + IT_Q * 8);
        mbar_wait(sb + SM_FULL + (IT_Q + 1) * 8);
        mbar_wait(sb + SM_FULL + (IT_C + w) * 8);
        const uint32_t cb0 = sb + slot_off(IT_C + w) + (lane & 7) * 128 + (lane >> 4) * 8192;
        const uint32_t cx = (((lane >> 3) & 1) ^ (lane & 7)) << 4;
        const uint32_t qr = ((lane & 7) + (lane & 8)) * 128;
        const uint32_t qx = ((lane >> 4) ^ (lane & 7)) << 4;
#pragma unroll
        for (int cb = 0; cb < 8; cb++) {
            const uint32_t qb = sb + slot_off(IT_Q + (cb >> 2)) + (cb & 3) * 4096 + qr;
#pragma unroll
            for (int k4 = 0; k4 < 4; k4++) {
                uint32_t b0, b1, b2, b3, a0, a1, a2, a3;
                ldsm4(cb0 + cb * 1024 + (cx ^ (k4 << 5)), b0, b1, b2, b3);
                ldsm4(qb + (qx ^ (k4 << 5)), a0, a1, a2, a3);
                mma16816(s[0][0], a0, a1, a2, a3, b0, b1);
                mma16816(s[0][1], a0, a1, a2, a3, b2, b3);
                ldsm4(qb + 2048 + (qx ^ (k4 << 5)), a0, a1, a2, a3);
                mma16816(s[1][0], a0, a1, a2, a3, b0, b1);
                mma16816(s[1][1], a0, a1, a2, a3, b2, b3);
            }
        }
        __syncwarp();
        if (lane == 0) { mbar_arrive(sb + SM_EMPTY + IT_Q * 8); mbar_arrive(sb + SM_EMPTY + (IT_Q + 1) * 8); }
#pragma unroll
        for (int r = 0; r < 4; r++) {
            const int mt = r >> 1, hi = (r & 1) * 2;
            float m = fmaxf(fmaxf(s[mt][0][hi], s[mt][0][hi + 1]), fmaxf(s[mt][1][hi], s[mt][1][hi + 1]));
            m = fmaxf(m, __shfl_xor_sync(0xffffffffu, m, 1));
            m = fmaxf(m, __shfl_xor_sync(0xffffffffu, m, 2));
            if (t == 0) stsf(sb + SM_MX + (8 * r + g) * 32 + w * 4, m);
        }
        bar_consumers();
        uint32_t pf[2][4];
#pragma unroll
        for (int r = 0; r < 4; r++) {
            const int mt = r >> 1, hi = r & 1;
            const float4 m0 = ldsf4(sb + SM_MX + (8 * r + g) * 32), m1 = ldsf4(sb + SM_MX + (8 * r + g) * 32 + 16);
            const float m = fmaxf(fmaxf(fmaxf(m0.x, m0.y), fmaxf(m0.z, m0.w)), fmaxf(fmaxf(m1.x, m1.y), fmaxf(m1.z, m1.w)));
            const uint32_t p0 = pack_bf16(ex2(s[mt][0][2 * hi] - m), ex2(s[mt][0][2 * hi + 1] - m));
            const uint32_t p1 = pack_bf16(ex2(s[mt][1][2 * hi] - m), ex2(s[mt][1][2 * hi + 1] - m));
            pf[mt][hi] = p0; pf[mt][2 + hi] = p1;
            float l = (bf_lo(p0) + bf_hi(p0)) + (bf_lo(p1) + bf_hi(p1));
            l += __shfl_xor_sync(0xffffffffu, l, 1);
            l += __shfl_xor_sync(0xffffffffu, l, 2);
            if (t == 0) stsf(sb + SM_SUM + (8 * r + g) * 32 + w * 4, l);
        }
        sts128(sb + SM_PF + (w * 2 + 0) * 512 + lane * 16, make_uint4(pf[0][0], pf[0][1], pf[0][2], pf[0][3]));
        sts128(sb + SM_PF + (w * 2 + 1) * 512 + lane * 16, make_uint4(pf[1][0], pf[1][1], pf[1][2], pf[1][3]));
        bar_consumers();
        if (w == 0) {
            const float4 m0 = ldsf4(sb + SM_MX + lane * 32), m1 = ldsf4(sb + SM_MX + lane * 32 + 16);
            const float4 l0 = ldsf4(sb + SM_SUM + lane * 32), l1 = ldsf4(sb + SM_SUM + lane * 32 + 16);
            const float m = fmaxf(fmaxf(fmaxf(m0.x, m0.y), fmaxf(m0.z, m0.w)), fmaxf(fmaxf(m1.x, m1.y), fmaxf(m1.z, m1.w)));
            const float l = ((l0.x + l0.y) + (l0.z + l0.w)) + ((l1.x + l1.y) + (l1.z + l1.w));
            gs->stat[lane][cta] = make_float2(m, l);
        }
        float o[2][8][4];
#pragma unroll
        for (int i = 0; i < 64; i++) (&o[0][0][0])[i] = 0.f;
        const uint32_t vr = w * 1024 + (lane & 7) * 128 + (lane & 8) * 1024;
        const uint32_t vx = ((lane >> 4) ^ (lane & 7)) << 4;
#pragma unroll
        for (int ks = 0; ks < 8; ks++) {
            const uint4 p0 = lds128(sb + SM_PF + (ks * 2 + 0) * 512 + lane * 16);
            const uint4 p1 = lds128(sb + SM_PF + (ks * 2 + 1) * 512 + lane * 16);
            const uint32_t vb = sb + slot_off(IT_C + ks) + vr;
#pragma unroll
            for (int n2 = 0; n2 < 4; n2++) {
                uint32_t b0, b1, b2, b3;
                ldsm4t(vb + (vx ^ (n2 << 5)), b0, b1, b2, b3);
                mma16816(o[0][2 * n2],     p0.x, p0.y, p0.z, p0.w, b0, b1);
                mma16816(o[0][2 * n2 + 1], p0.x, p0.y, p0.z, p0.w, b2, b3);
                mma16816(o[1][2 * n2],     p1.x, p1.y, p1.z, p1.w, b0, b1);
                mma16816(o[1][2 * n2 + 1], p1.x, p1.y, p1.z, p1.w, b2, b3);
            }
            __syncwarp();
            if (lane == 0) mbar_arrive(sb + SM_EMPTY + (IT_C + ks) * 8);
        }
        mbar_wait(sb + SM_FULL + (IT_K1 + 2 + (w >> 1)) * 8);
#pragma unroll
        for (int r = 0; r < 4; r++) {
            const int mt = r >> 1, hi = (r & 1) * 2;
            uint4* dst = gs->op[(8 * r + g) * 4 + (w >> 1)] + (cta >> 6) * 1024 + (w & 1) * 512 + (cta & 63) * 8;
#pragma unroll
            for (int u = 0; u < 2; u++) {
                uint4 v;
                v.x = pack_bf16(o[mt][4 * u][hi],     o[mt][4 * u][hi + 1]);
                v.y = pack_bf16(o[mt][4 * u + 1][hi], o[mt][4 * u + 1][hi + 1]);
                v.z = pack_bf16(o[mt][4 * u + 2][hi], o[mt][4 * u + 2][hi + 1]);
                v.w = pack_bf16(o[mt][4 * u + 3][hi], o[mt][4 * u + 3][hi + 1]);
                dst[(t + 4 * u) ^ (cta & 7)] = v;
            }
        }
        asm volatile("bar.arrive 3, 288;" ::: "memory");
    }

    k_item(IT_K1 + w, sc_w + 256);
    __syncwarp();
    {
        const float4 s = ldsf4(sc_w + lane * 16);
        float m = fmaxf(fmaxf(s.x, s.y), fmaxf(s.z, s.w));
#pragma unroll
        for (int d = 1; d < 32; d <<= 1) m = fmaxf(m, __shfl_xor_sync(0xffffffffu, m, d));
        if (lane == 0) stsf(sb + SM_ML + w * 4, m);
        bar_consumers();
        const float4 m0 = ldsf4(sb + SM_ML), m1 = ldsf4(sb + SM_ML + 16);
        m = fmaxf(fmaxf(fmaxf(m0.x, m0.y), fmaxf(m0.z, m0.w)), fmaxf(fmaxf(m1.x, m1.y), fmaxf(m1.z, m1.w))) * SC;
        const uint32_t p0 = pack_bf16(ex2(fmaf(s.x, SC, -m)), ex2(fmaf(s.y, SC, -m)));
        const uint32_t p1 = pack_bf16(ex2(fmaf(s.z, SC, -m)), ex2(fmaf(s.w, SC, -m)));
        float l = (bf_lo(p0) + bf_hi(p0)) + (bf_lo(p1) + bf_hi(p1));
#pragma unroll
        for (int d = 1; d < 32; d <<= 1) l += __shfl_xor_sync(0xffffffffu, l, d);
        if (lane == 0) stsf(sb + SM_ML + 32 + w * 4, l);
        sts64(sb + SM_PA + w * 256 + lane * 8, p0, p1);
        __syncwarp();
    }

    float oa[4][4];
#pragma unroll
    for (int i = 0; i < 16; i++) (&oa[0][0])[i] = 0.f;
    auto v_item = [&](int item, uint32_t pa) {
        uint32_t p[8];
#pragma unroll
        for (int i = 0; i < 8; i++) p[i] = lds32(pa + i * 16 + t * 4);
        mbar_wait(sb + SM_FULL + item * 8);
        const uint32_t base = sb + slot_off(item) + ((lane & 7) + ((lane >> 4) << 3)) * 256 + ((lane & 8) << 4);
#pragma unroll
        for (int c = 0; c < 8; c++) {
            const uint32_t a = base + ((c ^ (lane & 7)) << 4);
            const uint32_t mask = ((c == (g ^ (2 * t))) ? 0x0000ffffu : 0u) | ((c == (g ^ (2 * t + 1))) ? 0xffff0000u : 0u);
#pragma unroll
            for (int T = 0; T < 4; T++) {
                uint32_t r0, r1, r2, r3;
                ldsm4t(a + T * 4096, r0, r1, r2, r3);
                mma16816(oa[T], r0, r1, r2, r3, p[2 * T] & mask, p[2 * T + 1] & mask);
            }
        }
        __syncwarp();
        if (lane == 0) mbar_arrive8(sb + SM_EMPTY + item * 8);
    };
    v_item(IT_V0 + w, sb + SM_PA + w * 256);

    mbar_wait(sb + SM_FULL + IT_OP * 8);
    if (w < 4) {
        const float2 st = ldsf2(sb + SM_MX + tid * 8);
        float m = st.x;
#pragma unroll
        for (int d = 1; d < 32; d <<= 1) m = fmaxf(m, __shfl_xor_sync(0xffffffffu, m, d));
        const uint32_t wb = pack_bf16(ex2(st.x - m), 0.f);
        float l = bf_lo(wb) * st.y;
#pragma unroll
        for (int d = 1; d < 32; d <<= 1) l += __shfl_xor_sync(0xffffffffu, l, d);
#pragma unroll
        for (int bb = 0; bb < 4; bb++) sts16(in0 + bb * 272 + tid * 2, bb == w ? (uint16_t)wb : (uint16_t)0);
        if (lane == 0) stsf(sb + SM_ML + 64 + w * 4, 1.f / l);
    }
    bar_consumers();
    tile_mma<true>(sb, IT_OP, in0, w, lane, acc);
    if (lane < 16) {
        const float inv = ldsf(sb + SM_ML + 64 + g * 4);
        const uint32_t v0 = pack_bf16(acc[0][0] * inv, acc[0][1] * inv), v1 = pack_bf16(acc[1][0] * inv, acc[1][1] * inv);
        st_rlx2(lat_dst, (t & 1) ? v1 : v0, (t & 1) ? v0 : v1);
    }

    {
        const float4 l0 = ldsf4(sb + SM_ML + 32), l1 = ldsf4(sb + SM_ML + 48);
        const float inv = 1.f / (((l0.x + l0.y) + (l0.z + l0.w)) + ((l1.x + l1.y) + (l1.z + l1.w)));
        v_item(IT_V1 + w, sb + SM_PA + w * 256 + 128);
        const uint32_t so = sb + SM_PF + w * 512 + (16 * t + g) * 4;
        stsf(so,       (oa[0][0] + oa[1][0]) + (oa[2][0] + oa[3][0]));
        stsf(so + 32,  (oa[0][1] + oa[1][1]) + (oa[2][1] + oa[3][1]));
        stsf(so + 256, (oa[0][2] + oa[1][2]) + (oa[2][2] + oa[3][2]));
        stsf(so + 288, (oa[0][3] + oa[1][3]) + (oa[2][3] + oa[3][3]));
        if (w < 6) {
            asm volatile("bar.arrive 1, 256;" ::: "memory");
        } else {
            bar_consumers();
            float x = 0.f, y = 0.f;
#pragma unroll
            for (int i = 0; i < 8; i++) {
                const float2 v = ldsf2(sb + SM_PF + i * 512 + (tid & 63) * 8);
                x += v.x; y += v.y;
            }
            st_rlx(o_dst, pack_bf16(x * inv, y * inv));
            if (lane == 0) {
                const uint32_t to = map_cta(sb, w & 1);
                st_async32(to + SM_RCV + 128 + (j & 1) * 4, 0u, to + SM_FULL + BAR_PEER * 8);
            }
        }
    }

    if (w < 4) {
        const uint32_t lo = (g & 3) * 1024 + (g >> 2) * 512 + (g & 1) * 64 + t * 16;
        const int wd = ((lane >> 2 & 2) + (lane >> 4)) ^ (lane >> 1 & 3);
        const uint32_t base = sb + ((lane & 6) * 4 + wd * 2 + (lane & 1)) * 64 + (((w ^ wd) & 3) << 4);
        const uint64_t dst = __shfl_sync(0xffffffffu, (unsigned long long)ctx_dst, lane);
        mbar_wait(sb + SM_FULL + BAR_LAT * 8);
        uint4 a[8];
#pragma unroll
        for (int i = 0; i < 8; i++) a[i] = lds128(sb + SM_LAT + (lo ^ (i * 64)));
        int it = 0;
        while (refetch<0>(a, lane, [&](int i) { return (const char*)gs->lat[h] + (lo ^ (i * 64)); }))
            if (++it > SPIN_LIMIT) __trap();
        float v0 = 0.f, v1 = 0.f;
#pragma unroll
        for (int i = 0; i < 2; i++) {
            float c[4][4];
#pragma unroll
            for (int k = 0; k < 16; k++) (&c[0][0])[k] = 0.f;
            c[0][0] = v0; c[0][1] = v1;
            mbar_wait(sb + SM_FULL + (IT_WUV + i) * 8);
#pragma unroll
            for (int kk = 0; kk < 8; kk++) {
                uint32_t r0, r1, r2, r3;
                ldsm4t(base + slot_off(IT_WUV + i) + kk * 2048, r0, r1, r2, r3);
                mma16816(c[2 * (kk & 1)],     a[kk].x, a[kk].y, a[kk].z, a[kk].w, r0, r1);
                mma16816(c[2 * (kk & 1) + 1], a[kk].x, a[kk].y, a[kk].z, a[kk].w, r2, r3);
            }
            v0 = (c[0][0] + c[1][2]) + (c[2][0] + c[3][2]);
            v1 = (c[0][1] + c[1][3]) + (c[2][1] + c[3][3]);
            if (i == 0) { v0 = __shfl_xor_sync(0xffffffffu, v0, 16); v1 = __shfl_xor_sync(0xffffffffu, v1, 16); }
        }
        st_rlx_if(dst, pack_bf16(v0, v1), lane >= 16);
    }

    {
        const bool isB = slice >= 32;
        const int r = j & 1;
        const uint32_t xl = isB ? t * 64 + (((g ^ (t & 2)) & 3) << 4) : (g & 3) * 256 + ((g & 1) * 4 + t) * 16;
        const uint32_t cs = isB ? 256 : 64;
        const uint32_t xo = r * 8192 + (w >> 1) * 1024 + (w & 1) * 2 * cs + xl, xz = (1 - r) * 12288 + w * 1024 + (g >> 2) * 2 * cs + xl;
        auto xoff = [&](int i) { return i < 6 ? (i >> 1) * 4096 + (xo ^ ((i & 1) * cs)) : xz ^ ((i & 1) * cs); };
        const char* src = (const char*)gs->x[slice >> 5][r * 12];
        uint32_t off[2], ofz[2];
#pragma unroll
        for (int u = 0; u < 2; u++) {
            const int tt = (lane & 7) >> 1;
            const int row = 8 * tt + 2 * ((2 * u + (lane >> 4) + tt) & 3) + (lane & 1);
            off[u] = sb + w * 2048 + row * 32 + ((((lane >> 3) ^ (row >> 2)) & 1) << 4);
            ofz[u] = __shfl_sync(0xffffffffu, sb + (w < 4 ? slot_off(IT_WO + 3) : slot_off(IT_W2)) + (w & 3) * 4096 + (lane & 8) * 256 +
                                              row * 32 + (((r ^ (row >> 2)) & 1) << 4), lane);
        }
        const uint32_t fin = __shfl_sync(0xffffffffu, sb + SM_FIN + (t & 1) * 768 + g * 48 + ((w ^ (t & 1)) << 2), lane);
        const uint32_t fi2 = __shfl_sync(0xffffffffu, sb + SM_FIN + 3072 + (t & 1) * 1280 + g * 80 + (((w * 2 + (t >> 1)) ^ (t * 2 & 2)) << 2), lane);
        uint32_t a[2][4][4];
        uint4 x[8];
        float c[4][4];
        auto load_w = [&](int i) {
            mbar_wait(sb + SM_FULL + (i < 3 ? IT_WO + i : w < 4 ? IT_WO + 3 : IT_W2) * 8);
#pragma unroll
            for (int q = 0; q < 4; q++)
                ldsm4t((i < 3 ? slot_off(IT_WO + i) + off[q & 1] : ofz[q & 1]) + (q >> 1) * 1024,
                       a[i & 1][q][0], a[i & 1][q][1], a[i & 1][q][2], a[i & 1][q][3]);
        };
        auto mma_w = [&](int i) {
#pragma unroll
            for (int q = 0; q < 4; q++) {
                if (i == 0 || i == 3) c[q][0] = c[q][1] = c[q][2] = c[q][3] = 0.f;
                mma16816(c[q], a[i & 1][q][0], a[i & 1][q][1], a[i & 1][q][2], a[i & 1][q][3],
                         (q & 1) ? x[2 * i + (q >> 1)].z : x[2 * i + (q >> 1)].x, (q & 1) ? x[2 * i + (q >> 1)].w : x[2 * i + (q >> 1)].y);
            }
        };
        load_w(0); load_w(1);
        mbar_wait(sb + SM_FULL + BAR_X * 8);
#pragma unroll
        for (int i = 0; i < 8; i++) x[i] = lds128_if(sb + slot_off(IT_X) + xoff(i), i >= 6 || lane < 16);
        int it = 0;
        while (true) {
            mma_w(0); mma_w(1);
            if (!refetch<6>(x, lane, [&](int i) { return src + xoff(i); })) break;
            if (++it > SPIN_LIMIT) __trap();
        }
        load_w(2);
        mma_w(2);
#pragma unroll
        for (int e = 0; e < 4; e++) stsf_if(fin + (e >> 1) * 1536 + (e & 1) * 384, (c[0][e] + c[1][e]) + (c[2][e] + c[3][e]), t < 2);
        asm volatile("bar.arrive 5, 320;" ::: "memory");
        load_w(3);
        mma_w(3);
#pragma unroll
        for (int e = 0; e < 2; e++) {
            const float lo = (c[0][e] + c[1][e]) + (c[2][e] + c[3][e]), hi = (c[0][e + 2] + c[1][e + 2]) + (c[2][e + 2] + c[3][e + 2]);
            stsf(fi2 + e * 640, t < 2 ? lo : hi);
        }
        asm volatile("bar.arrive 7, 288;" ::: "memory");
    }
}

typedef CUresult (*EncodeTiledFn)(CUtensorMap*, CUtensorMapDataType, cuuint32_t, void*, const cuuint64_t*,
                                  const cuuint64_t*, const cuuint32_t*, const cuuint32_t*, CUtensorMapInterleave,
                                  CUtensorMapSwizzle, CUtensorMapL2promotion, CUtensorMapFloatOOBfill);

void encode_map(EncodeTiledFn enc, CUtensorMap* tm, const void* p, cuuint64_t cols, cuuint64_t rows,
                cuuint32_t brows, cuuint32_t bblk) {
    cuuint64_t dims[3] = {64, rows, cols / 64};
    cuuint64_t strides[2] = {cols * 2, 128};
    cuuint32_t box[3] = {64, brows, bblk};
    cuuint32_t es[3] = {1, 1, 1};
    enc(tm, CU_TENSOR_MAP_DATA_TYPE_BFLOAT16, 3, const_cast<void*>(p), dims, strides, box, es,
        CU_TENSOR_MAP_INTERLEAVE_NONE, CU_TENSOR_MAP_SWIZZLE_128B, CU_TENSOR_MAP_L2_PROMOTION_L2_256B,
        CU_TENSOR_MAP_FLOAT_OOB_FILL_NONE);
}

void encode_slice_map(EncodeTiledFn enc, CUtensorMap* tm, const void* p, cuuint64_t cols, cuuint64_t rows, cuuint32_t bcols) {
    cuuint64_t dims[3] = {cols, 256, rows / 256};
    cuuint64_t strides[2] = {cols * 2, cols * 512};
    cuuint32_t box[3] = {bcols, 4096 / bcols, 1};
    cuuint32_t es[3] = {1, 1, 1};
    enc(tm, CU_TENSOR_MAP_DATA_TYPE_BFLOAT16, 3, const_cast<void*>(p), dims, strides, box, es, CU_TENSOR_MAP_INTERLEAVE_NONE,
        bcols == 16 ? CU_TENSOR_MAP_SWIZZLE_32B : CU_TENSOR_MAP_SWIZZLE_64B, CU_TENSOR_MAP_L2_PROMOTION_L2_128B,
        CU_TENSOR_MAP_FLOAT_OOB_FILL_NONE);
}

}

extern "C" void kernel_launch(void* const* d_in, const int* in_sizes, int n_in, void* d_out, int out_size) {
    (void)in_sizes; (void)n_in; (void)out_size;
    static EncodeTiledFn enc = nullptr;
    static Scratch* gs = nullptr;
    if (!enc) {
        cudaGetSymbolAddress((void**)&gs, g_scratch);
        void* fn = nullptr;
        cudaDriverEntryPointQueryResult qr;
        cudaGetDriverEntryPoint("cuTensorMapEncodeTiled", &fn, cudaEnableDefault, &qr);
        enc = (EncodeTiledFn)fn;
        cudaFuncSetAttribute(fused_decode_kernel, cudaFuncAttributeMaxDynamicSharedMemorySize, SM_END);
    }
    Maps maps;
    encode_map(enc, &maps.wuk, d_in[8], 4096, 512, 32, 2);
    encode_slice_map(enc, &maps.wuv, d_in[9], 4096, 512, 32);
    encode_slice_map(enc, &maps.woB, d_in[10], 512, 4096, 16);
    encode_slice_map(enc, &maps.woA, d_in[4], 512, 4096, 16);
    encode_map(enc, &maps.ckv, d_in[6], 512, 16384, 8, 8);
    fused_decode_kernel<<<NCTA, NTHR, SM_END>>>((const __nv_bfloat16*)d_in[0], (const __nv_bfloat16*)d_in[5],
                                                (const __nv_bfloat16*)d_in[7], (const __nv_bfloat16*)d_in[3],
                                                (const __nv_bfloat16*)d_in[1] + 3072 * 128, (const __nv_bfloat16*)d_in[2] + 3072 * 128,
                                                (__nv_bfloat16*)d_out, gs, maps);
}
```

```cpp
#include <cuda_runtime.h>
#include <cuda_bf16.h>
#include <cuda.h>
#include <stdint.h>

namespace {

constexpr int NCTA   = 128;
constexpr int NSLOT  = 13;
constexpr int SLOT   = 16384;
constexpr int NITEM  = 56;
constexpr int NTHR   = 384;

constexpr int INFLIGHT = 4;
constexpr int PACE     = 644;
constexpr int LEAD     = 550;
constexpr int TAPER    = 260;
constexpr int XLEAD    = 500;
constexpr int OPGAP    = 250;
constexpr int NWIN     = 4;
__device__ constexpr int win_pos(int k)  { return k == 0 ? 10 : k == 1 ? 20 : k == 2 ? 31 : 38; }
__device__ constexpr int win_late(int k) { return k == 0 ? 1860 : k == 1 ? 1880 : k == 2 ? 1870 : 1780; }
constexpr int GAIN     = 11;

constexpr int IT_WQB = 0, IT_WQA = 2, IT_WUK = 4, IT_K0 = 6, IT_Q = 14, IT_C = 16, IT_K1 = 24, IT_V0 = 32,
              IT_OP = 40, IT_V1 = 42, IT_WUV = 50, IT_WO = 52;
constexpr int IT_X = 56;
constexpr int IT_W2 = 58;
constexpr int BAR_LAT = 56, BAR_FIN = 57, BAR_X = 59, BAR_PEER = 60;

constexpr int SM_FULL  = NSLOT * SLOT;
constexpr int SM_EMPTY = SM_FULL + 512;
constexpr int SM_IN0   = SM_EMPTY + 512;
constexpr int SM_IN1   = SM_IN0 + 1088;
constexpr int SM_SC    = SM_IN1 + 1088;
constexpr int SM_PA    = SM_SC + 4096;
constexpr int SM_PF    = SM_PA + 2048;
constexpr int SM_MX    = SM_PF + 8192;
constexpr int SM_ML    = SM_MX + 1024;
constexpr int SM_RCV   = SM_ML + 128;
constexpr int SM_PACE  = SM_RCV + 144;
constexpr int SM_END   = SM_PACE + 32;
constexpr int SM_LAT   = SM_PF + 4096;
constexpr int SM_FIN   = SM_SC;
constexpr int SM_SUM   = SM_IN0;
static_assert(SM_END <= 232448, "smem");

struct Maps { CUtensorMap wuk, wuv, woA, woB, ckv; };

struct Scratch {
    unsigned cnt[32];
    unsigned late[32];
    float    part[2][NCTA][512];
    uint32_t x[2][32][256];
    uint32_t lat[32][4][256];
    uint4    q[4][2048];
    uint4    op[NCTA][2048];
    float2   stat[32][128];
};
__device__ __align__(128) Scratch g_scratch;

constexpr int SPIN_LIMIT = 1 << 22;

__device__ __forceinline__ uint32_t smem_u32(const void* p) { return (uint32_t)__cvta_generic_to_shared(p); }
__device__ __forceinline__ void mbar_init(uint32_t bar, uint32_t cnt) {
    asm volatile("mbarrier.init.shared::cta.b64 [%0], %1;" ::"r"(bar), "r"(cnt) : "memory");
}
__device__ __forceinline__ void mbar_expect_tx(uint32_t bar, uint32_t bytes) {
    asm volatile("mbarrier.arrive.expect_tx.shared::cta.b64 _, [%0], %1;" ::"r"(bar), "r"(bytes) : "memory");
}
__device__ __forceinline__ void mbar_arrive(uint32_t bar) {
    asm volatile("mbarrier.arrive.shared::cta.b64 _, [%0];" ::"r"(bar) : "memory");
}
__device__ __forceinline__ void mbar_arrive8(uint32_t bar) {
    asm volatile("mbarrier.arrive.shared::cta.b64 _, [%0], 8;" ::"r"(bar) : "memory");
}
__device__ __forceinline__ void mbar_wait(uint32_t bar) {
    uint32_t done;
    int it = 0;
    do {
        asm volatile("{\n.reg .pred p;\nmbarrier.try_wait.parity.shared::cta.b64 p, [%1], 0;\nselp.u32 %0, 1, 0, p;\n}"
                     : "=r"(done) : "r"(bar) : "memory");
        if (++it > SPIN_LIMIT) __trap();
    } while (!done);
}
__device__ __forceinline__ uint32_t map_cta(uint32_t a, uint32_t rank) {
    uint32_t r; asm("mapa.shared::cluster.u32 %0, %1, %2;" : "=r"(r) : "r"(a), "r"(rank)); return r;
}
__device__ __forceinline__ void st_async32(uint32_t a, uint32_t v, uint32_t bar) {
    asm volatile("st.async.shared::cluster.mbarrier::complete_tx::bytes.b32 [%0], %1, [%2];" ::"r"(a), "r"(v), "r"(bar) : "memory");
}
__device__ __forceinline__ uint64_t evict_first() {
    uint64_t pol; asm volatile("createpolicy.fractional.L2::evict_first.b64 %0, 1.0;" : "=l"(pol)); return pol;
}
#define ELECT "{\n.reg .pred p;\nelect.sync _|p, 0xffffffff;\n@p "
__device__ __forceinline__ void bulk_load(uint32_t dst, const void* src, uint32_t bytes, uint32_t bar, uint64_t pol) {
    asm volatile(ELECT "cp.async.bulk.shared::cluster.global.mbarrier::complete_tx::bytes.L2::cache_hint [%0], [%1], %2, [%3], %4;\n}"
                 ::"r"(dst), "l"(src), "r"(bytes), "r"(bar), "l"(pol) : "memory");
}
__device__ __forceinline__ void bulk_load_nohint(uint32_t dst, const void* src, uint32_t bytes, uint32_t bar) {
    asm volatile("cp.async.bulk.shared::cluster.global.mbarrier::complete_tx::bytes [%0], [%1], %2, [%3];"
                 ::"r"(dst), "l"(src), "r"(bytes), "r"(bar) : "memory");
}
__device__ __forceinline__ void tma3d(uint32_t dst, const CUtensorMap* tm, int c0, int c1, int c2, uint32_t bar, uint64_t pol) {
    asm volatile(ELECT "cp.async.bulk.tensor.3d.shared::cluster.global.mbarrier::complete_tx::bytes.L2::cache_hint [%0], [%1, {%3, %4, %5}], [%2], %6;\n}"
                 ::"r"(dst), "l"(tm), "r"(bar), "r"(c0), "r"(c1), "r"(c2), "l"(pol) : "memory");
}
__device__ __forceinline__ void tma3d_pair(uint32_t dst, const CUtensorMap* tm, int c0, int c1, int c2, uint32_t bar, uint64_t pol) {
    asm volatile(ELECT "cp.async.bulk.tensor.3d.shared::cluster.global.mbarrier::complete_tx::bytes.multicast::cluster.L2::cache_hint [%0], [%1, {%3, %4, %5}], [%2], %7, %6;\n}"
                 ::"r"(dst), "l"(tm), "r"(bar), "r"(c0), "r"(c1), "r"(c2), "l"(pol), "h"((uint16_t)3) : "memory");
}
__device__ __forceinline__ void ldsm4(uint32_t a, uint32_t& r0, uint32_t& r1, uint32_t& r2, uint32_t& r3) {
    asm volatile("ldmatrix.sync.aligned.m8n8.x4.shared.b16 {%0,%1,%2,%3}, [%4];"
                 : "=r"(r0), "=r"(r1), "=r"(r2), "=r"(r3) : "r"(a) : "memory");
}
__device__ __forceinline__ void ldsm4t(uint32_t a, uint32_t& r0, uint32_t& r1, uint32_t& r2, uint32_t& r3) {
    asm volatile("ldmatrix.sync.aligned.m8n8.x4.trans.shared.b16 {%0,%1,%2,%3}, [%4];"
                 : "=r"(r0), "=r"(r1), "=r"(r2), "=r"(r3) : "r"(a) : "memory");
}
__device__ __forceinline__ void mma16816(float (&c)[4], uint32_t a0, uint32_t a1, uint32_t a2, uint32_t a3,
                                         uint32_t b0, uint32_t b1) {
    asm volatile("mma.sync.aligned.m16n8k16.row.col.f32.bf16.bf16.f32 {%0,%1,%2,%3}, {%4,%5,%6,%7}, {%8,%9}, {%0,%1,%2,%3};"
                 : "+f"(c[0]), "+f"(c[1]), "+f"(c[2]), "+f"(c[3])
                 : "r"(a0), "r"(a1), "r"(a2), "r"(a3), "r"(b0), "r"(b1));
}
__device__ __forceinline__ uint32_t lds32(uint32_t a) {
    uint32_t v; asm volatile("ld.shared.b32 %0, [%1];" : "=r"(v) : "r"(a) : "memory"); return v;
}
__device__ __forceinline__ float ldsf(uint32_t a) {
    float v; asm volatile("ld.shared.f32 %0, [%1];" : "=f"(v) : "r"(a) : "memory"); return v;
}
__device__ __forceinline__ float2 ldsf2(uint32_t a) {
    float2 v; asm volatile("ld.shared.v2.f32 {%0,%1}, [%2];" : "=f"(v.x), "=f"(v.y) : "r"(a) : "memory"); return v;
}
__device__ __forceinline__ float4 ldsf4(uint32_t a) {
    float4 v; asm volatile("ld.shared.v4.f32 {%0,%1,%2,%3}, [%4];" : "=f"(v.x), "=f"(v.y), "=f"(v.z), "=f"(v.w) : "r"(a) : "memory"); return v;
}
__device__ __forceinline__ uint4 lds128(uint32_t a) {
    uint4 v; asm volatile("ld.shared.v4.b32 {%0,%1,%2,%3}, [%4];" : "=r"(v.x), "=r"(v.y), "=r"(v.z), "=r"(v.w) : "r"(a) : "memory"); return v;
}
__device__ __forceinline__ uint4 lds128_if(uint32_t a, bool on) {
    uint4 v;
    asm volatile("{\n.reg .pred p;\nsetp.ne.u32 p, %5, 0;\n@p ld.shared.v4.b32 {%0,%1,%2,%3}, [%4];\n}"
                 : "=r"(v.x), "=r"(v.y), "=r"(v.z), "=r"(v.w) : "r"(a), "r"((uint32_t)on) : "memory");
    return v;
}
__device__ __forceinline__ void stsf_if(uint32_t a, float v, bool on) {
    asm volatile("{\n.reg .pred p;\nsetp.ne.u32 p, %2, 0;\n@p st.shared.f32 [%0], %1;\n}" ::"r"(a), "f"(v), "r"((uint32_t)on) : "memory");
}
__device__ __forceinline__ void sts16(uint32_t a, uint16_t v) { asm volatile("st.shared.b16 [%0], %1;" ::"r"(a), "h"(v) : "memory"); }
__device__ __forceinline__ void sts32(uint32_t a, uint32_t v) { asm volatile("st.shared.b32 [%0], %1;" ::"r"(a), "r"(v) : "memory"); }
__device__ __forceinline__ void stsf(uint32_t a, float v) { asm volatile("st.shared.f32 [%0], %1;" ::"r"(a), "f"(v) : "memory"); }
__device__ __forceinline__ void sts64(uint32_t a, uint32_t x, uint32_t y) {
    asm volatile("st.shared.v2.b32 [%0], {%1,%2};" ::"r"(a), "r"(x), "r"(y) : "memory");
}
__device__ __forceinline__ void sts128(uint32_t a, uint4 v) {
    asm volatile("st.shared.v4.b32 [%0], {%1,%2,%3,%4};" ::"r"(a), "r"(v.x), "r"(v.y), "r"(v.z), "r"(v.w) : "memory");
}
__device__ __forceinline__ uint32_t pack_bf16(float lo, float hi) {
    uint32_t r; asm("cvt.rn.bf16x2.f32 %0, %1, %2;" : "=r"(r) : "f"(hi), "f"(lo)); return r;
}
__device__ __forceinline__ float bf_lo(uint32_t v) { return __uint_as_float(v << 16); }
__device__ __forceinline__ float bf_hi(uint32_t v) { return __uint_as_float(v & 0xffff0000u); }
__device__ __forceinline__ float ex2(float x) { float y; asm("ex2.approx.ftz.f32 %0, %1;" : "=f"(y) : "f"(x)); return y; }
__device__ __forceinline__ uint32_t timer_ns() { uint32_t t; asm volatile("mov.u32 %0, %%globaltimer_lo;" : "=r"(t)); return t; }
__device__ __forceinline__ void bar_consumers() { asm volatile("bar.sync 1, 256;" ::: "memory"); }

__device__ __forceinline__ uint32_t tagf(float v, uint32_t tag) { return (__float_as_uint(v) & 0xffffff00u) | tag; }
__device__ __forceinline__ uint2 ld_rlx2(const float* p) {
    uint2 v; asm volatile("ld.relaxed.gpu.global.v2.b32 {%0,%1}, [%2];" : "=r"(v.x), "=r"(v.y) : "l"(p) : "memory"); return v;
}
__device__ __forceinline__ float untag(uint32_t v) { return __uint_as_float(v & 0xffffff00u); }

__device__ __forceinline__ uint32_t slot_off(int item) { return (uint32_t)(item % NSLOT) * SLOT; }

template <bool TRANS, bool TMA = true>
__device__ __forceinline__ void tile_mma(uint32_t sb, int item, uint32_t in, int w, int lane, float (&acc)[2][2]) {
    const int g = lane >> 2, t = lane & 3;
    float c[4][4];
#pragma unroll
    for (int i = 0; i < 16; i++) (&c[0][0])[i] = 0.f;
    uint32_t a[16];
    const uint32_t ia = in + (g & 3) * 272 + t * 4;
#pragma unroll
    for (int i = 0; i < 16; i++) a[i] = lds32(ia + i * 16);
    const uint32_t s0 = sb + slot_off(item), s1 = sb + slot_off(item + 1);
    if (TRANS) {
        const int r = (lane & 7) + (lane & 8);
        const int ch = 2 * (w & 3) + (lane >> 4);
        const uint32_t off = (TMA ? (w >> 2) * 8192 + r * 128 : (w >> 2) * 128 + r * 256) + ((ch ^ (lane & 7)) << 4);
#pragma unroll
        for (int kk = 0; kk < 8; kk++) {
            if (TMA && (kk & 3) == 0) mbar_wait(sb + SM_FULL + (item + (kk >> 2)) * 8);
            uint32_t r0, r1, r2, r3;
            ldsm4t(((kk >> 2) ? s1 : s0) + off + (kk & 3) * (TMA ? 2048 : 4096), r0, r1, r2, r3);
            mma16816(c[2 * (kk & 1)],     a[2 * kk], 0u, a[2 * kk + 1], 0u, r0, r1);
            mma16816(c[2 * (kk & 1) + 1], a[2 * kk], 0u, a[2 * kk + 1], 0u, r2, r3);
        }
    } else {
        mbar_wait(sb + SM_FULL + (item + (w >> 2)) * 8);
        const int r = 16 * (w & 3) + (lane & 7) + ((lane >> 4) << 3);
        const uint32_t base = ((w >> 2) ? s1 : s0) + (r & 32) * 128 + r * 128 + ((((lane >> 3) & 1) ^ (lane & 7)) << 4);
#pragma unroll
        for (int kk = 0; kk < 8; kk++) {
            uint32_t r0, r1, r2, r3;
            ldsm4((base ^ ((kk & 3) << 5)) + (kk >> 2) * 4096, r0, r1, r2, r3);
            mma16816(c[2 * (kk & 1)],     a[2 * kk], 0u, a[2 * kk + 1], 0u, r0, r1);
            mma16816(c[2 * (kk & 1) + 1], a[2 * kk], 0u, a[2 * kk + 1], 0u, r2, r3);
        }
    }
    __syncwarp();
    if (lane == 0) {
        mbar_arrive(sb + SM_EMPTY + item * 8);
        mbar_arrive(sb + SM_EMPTY + (item + 1) * 8);
    }
    acc[0][0] = c[0][0] + c[2][0]; acc[0][1] = c[0][1] + c[2][1];
    acc[1][0] = c[1][0] + c[3][0]; acc[1][1] = c[1][1] + c[3][1];
}

__device__ __forceinline__ void publish(float* dst, int w, int lane, const float (&acc)[2][2], uint32_t tag) {
    if (lane < 16)
        asm volatile("st.relaxed.gpu.global.v4.b32 [%0], {%1,%2,%3,%4};" ::"l"(dst + w * 64 + lane * 4),
                     "r"(tagf(acc[0][0], tag)), "r"(tagf(acc[0][1], tag)), "r"(tagf(acc[1][0], tag)), "r"(tagf(acc[1][1], tag)) : "memory");
}

__device__ __forceinline__ void gather(const float* part, uint32_t in, int tid, uint32_t tag) {
    const float* p = part + tid * 2;
    uint2 v0, v1, v2, v3;
    int it = 0;
    while (true) {
        v0 = ld_rlx2(p); v1 = ld_rlx2(p + 512); v2 = ld_rlx2(p + 1024); v3 = ld_rlx2(p + 1536);
        uint32_t bad = ((v0.x ^ tag) | (v0.y ^ tag) | (v1.x ^ tag) | (v1.y ^ tag) |
                        (v2.x ^ tag) | (v2.y ^ tag) | (v3.x ^ tag) | (v3.y ^ tag)) & 0xffu;
        if (__all_sync(0xffffffffu, bad == 0)) break;
        if (++it > SPIN_LIMIT) __trap();
    }
    float x = (untag(v0.x) + untag(v1.x)) + (untag(v2.x) + untag(v3.x));
    float y = (untag(v0.y) + untag(v1.y)) + (untag(v2.y) + untag(v3.y));
    sts32(in + ((tid >> 3) & 3) * 272 + (tid >> 5) * 32 + (tid & 1) * 16 + (tid & 6) * 2, pack_bf16(x, y));
    bar_consumers();
}

constexpr uint32_t EMPTY = 0xffffffffu;
__device__ __forceinline__ void st_rlx(uint32_t* p, uint32_t v) {
    asm volatile("st.relaxed.gpu.global.b32 [%0], %1;" ::"l"(p), "r"(v) : "memory");
}
__device__ __forceinline__ void st_rlx_if(uint64_t p, uint32_t v, bool on) {
    asm volatile("{\n.reg .pred p;\nsetp.ne.u32 p, %2, 0;\n@p st.relaxed.gpu.global.b32 [%0], %1;\n}" ::"l"(p), "r"(v), "r"((uint32_t)on) : "memory");
}
__device__ __forceinline__ void st_rlx2(uint32_t* p, uint32_t v0, uint32_t v1) {
    asm volatile("st.relaxed.gpu.global.v2.b32 [%0], {%1,%2};" ::"l"(p), "r"(v0), "r"(v1) : "memory");
}
__device__ __forceinline__ void ld_rlx4_if(uint4& v, const void* p, bool need) {
    asm volatile("{\n.reg .pred p;\nsetp.ne.u32 p, %5, 0;\n@p ld.relaxed.gpu.global.v4.b32 {%0,%1,%2,%3}, [%4];\n}"
                 : "+r"(v.x), "+r"(v.y), "+r"(v.z), "+r"(v.w) : "l"(p), "r"((uint32_t)need) : "memory");
}

template <int HALF, class F>
__device__ __forceinline__ bool refetch(uint4 (&x)[8], int lane, F addr) {
    uint32_t m[8], m0 = 0, m1 = 0;
#pragma unroll
    for (int i = 0; i < 8; i++) {
        m[i] = max(max(x[i].x, x[i].y), max(x[i].z, x[i].w));
        if (i < HALF) m0 = max(m0, m[i]); else m1 = max(m1, m[i]);
    }
    if (!__any_sync(0xffffffffu, (m0 == EMPTY && lane < 16) || m1 == EMPTY)) return false;
#pragma unroll
    for (int i = 0; i < 8; i++) ld_rlx4_if(x[i], addr(i), m[i] == EMPTY && (i >= HALF || lane < 16));
    return true;
}

__device__ __forceinline__ unsigned read_counter(const unsigned* cnt) {
    unsigned v;
    asm volatile("ld.relaxed.gpu.global.u32 %0, [%1];" : "=r"(v) : "l"(cnt) : "memory");
    return v;
}
__device__ __forceinline__ unsigned epoch_of(unsigned cnt) {
    asm volatile("" : "+r"(cnt) :: "memory");
    return cnt / NCTA + 1;
}
__device__ __forceinline__ uint32_t epoch_tag(unsigned epoch) { return (epoch & 0x7fu) | 0x80u; }

__device__ __forceinline__ void signal_and_wait(unsigned* cnt, unsigned target, int lane) {
    if (lane == 0) asm volatile("red.release.gpu.global.add.u32 [%0], 1;" ::"l"(cnt) : "memory");
    int it = 0;
    while (true) {
        unsigned v;
        asm volatile("ld.acquire.gpu.global.u32 %0, [%1];" : "=r"(v) : "l"(cnt) : "memory");
        if (__all_sync(0xffffffffu, (int)(v - target) >= 0)) break;
        if (++it > SPIN_LIMIT) __trap();
    }
    asm volatile("fence.proxy.async.global;" ::: "memory");
}

__global__ void __cluster_dims__(2, 1, 1) __launch_bounds__(NTHR, 1)
fused_decode_kernel(const __nv_bfloat16* __restrict__ xA, const __nv_bfloat16* __restrict__ xB,
                    const __nv_bfloat16* __restrict__ wqB, const __nv_bfloat16* __restrict__ wqA,
                    const __nv_bfloat16* __restrict__ Kc, const __nv_bfloat16* __restrict__ Vc,
                    __nv_bfloat16* __restrict__ out, Scratch* gs, const __grid_constant__ Maps maps) {
    extern __shared__ __align__(1024) unsigned char smem_raw[];
    const uint32_t sb = smem_u32(smem_raw);
    const int tid = threadIdx.x, lane = tid & 31;
    const int cta = blockIdx.x, h = cta >> 2, j = cta & 3;
    const size_t kv_off = (size_t)blockIdx.x * 4096 * 128;
    const uint32_t trow = threadIdx.x >> 4;
    const uint32_t tile_src = trow * (8192 - 256) + (threadIdx.x * 16 + ((blockIdx.x * 0x100040u) & 0x301f00u));
    const uint32_t tile_dst = sb + ((threadIdx.x ^ (trow & 7)) << 4);
    auto lsu_piece = [&](int k) {
#pragma unroll
        for (int q = 2 * k; q < 2 * k + 2; q++)
            asm volatile("cp.async.cg.shared.global [%0], [%1], 16;" ::"r"(tile_dst + q * 4096),
                         "l"(reinterpret_cast<const char*>((k < 4 ? wqB : wqA) + (q & 7) * 16 * 4096) + tile_src) : "memory");
        if ((k & 3) == 3) asm volatile("cp.async.commit_group;" ::: "memory");
    };
    if (tid < 256) {
#pragma unroll
        for (int k = 0; k < 4; k++) lsu_piece(k);
    }
    const uint32_t tz = timer_ns() - LEAD;
    unsigned cnt1;
    if (tid < 256) cnt1 = read_counter(&gs->cnt[1]);
    uint4 xv;
    if (tid < 128) {
        const __nv_bfloat16* x = (tid < 64 ? xB : xA) + ((tid >> 4) & 3) * 512 + j * 128 + (tid & 15) * 8;
        xv = __ldg(reinterpret_cast<const uint4*>(x));
    }
    const int w = __shfl_sync(0xffffffffu, tid >> 5, 0);
    const int pr = cta >> 1;
    const int slice = pr < 4 ? pr : pr < 36 ? 4 + ((pr - 4) & 7) * 4 + ((pr - 4) >> 3) : 36 + (pr - 36) % 7 * 4 + (pr - 36) / 7;

    if (w >= 8) {
        if (lane == 0) {
            const uint32_t full = sb + SM_FULL + (IT_WUK + (w & 3) * 15) * 8, empty = sb + SM_EMPTY + (w & 3) * 14 * 8;
#pragma unroll
            for (int i = 0; i < 15; i++) mbar_init(full + i * 8, 1);
#pragma unroll
            for (int i = 0; i < 14; i++) mbar_init(empty + i * 8, 8);
#pragma unroll
            for (int i = 0; i < 15; i++) {
                const int b = IT_WUK + 45 + i;
                mbar_expect_tx(full + i * 8, (w == 10 && b - 15 == IT_OP) ? SLOT + 1024 : w != 11 ? SLOT : b == BAR_LAT ? 4096 :
                                             b == BAR_FIN ? 128 : b == BAR_X ? SLOT + 4096 : b == BAR_PEER ? 8 : SLOT);
            }
            asm volatile("fence.mbarrier_init.release.cluster;" ::: "memory");
            if (w == 10) sts64(sb + SM_PACE, tz, PACE * 16);
        }
        asm volatile("bar.sync 2, 128;" ::: "memory");
        asm volatile("bar.arrive 4, 384;" ::: "memory");
    }
    if (w == 10) {
        if (lane == 0) {
            int slope = 0;
#pragma unroll
            for (int k = 0; k < NWIN; k++) {
                const int c = win_pos(k);
                uint32_t acc = 0;
#pragma unroll
                for (int p = c; p < c + 4; p++) {
                    mbar_wait(sb + SM_FULL + (p < IT_Q ? p : p < IT_OP - 2 ? p + 2 : p + 4) * 8);
                    acc += timer_ns() - tz - p * PACE - ((p * slope) >> 4);
                }
                if (k == 0) mbar_wait(sb + SM_FULL + IT_Q * 8);
                asm volatile("red.relaxed.gpu.global.add.u32 [%0], %1;" ::"l"(&gs->late[k]), "r"((1u << 24) + min(acc >> 2, 65535u)) : "memory");
                uint32_t v;
                int it = 0;
                do { v = read_counter(&gs->late[k]); } while ((v >> 24) != NCTA && ++it < 1000);
                const int late = (v & 0xffffffu) / NCTA;
                slope = max(-320, min(320, slope + (late - win_late(k)) * (GAIN * 2) / (2 * c + 3)));
                sts64(sb + SM_PACE, tz, PACE * 16 + slope);
            }
        }
        return;
    }
    if (w >= 8) {
        auto wait_due = [&](uint32_t p, uint32_t shift) {
            uint32_t a, b;
            do {
                asm volatile("ld.volatile.shared.v2.b32 {%0,%1}, [%2];" : "=r"(a), "=r"(b) : "r"(sb + SM_PACE) : "memory");
            } while (__all_sync(0xffffffffu, (int)(timer_ns() - (a + ((p * b) >> 4) + shift)) < 0));
        };
        if (w != 9) {
            const int half = w & 1;
            const uint64_t pol = evict_first();
            int slot = IT_WUK, tail = IT_WUK - INFLIGHT;
            uint32_t np = IT_WUK, shift = half ? PACE / 4 : -(PACE / 4);
#pragma unroll 1
            for (int i = IT_WUK; i < NITEM; i++) {
                const uint32_t dst = sb + slot * SLOT + half * (SLOT / 2), bar = sb + SM_FULL + i * 8;
                if (++slot == NSLOT) slot = 0;
                if ((i & ~1) == IT_Q || (i & ~1) == IT_OP) continue;
                const bool ckv = i >= IT_C && i < IT_K1, wo = i >= IT_WO;
                const bool tiled = ckv || i < IT_K0 || i >= IT_WUV;
                const CUtensorMap* tm = &maps.wuk + (i < IT_K0 ? 0 : ckv ? 4 : wo ? 2 + (slice >> 5) : 1);
                const int c0 = wo ? (slice & 31) * 16 : i >= IT_WUV ? cta * 32 : 0;
                const int c1 = i < IT_K0 ? j * 128 + (i & 1) * 64 + half * 32 : ckv ? cta * 128 + (i - IT_C) * 16 + half * 8 : wo ? 0 : half * 128;
                const int c2 = i < IT_K0 ? h * 2 : ckv ? 0 : wo ? (i - IT_WO) * 4 + (j & 1) * 2 + half : i & 1;
                const int c = i < IT_Q ? i - IT_K0 : i < IT_V0 ? i - IT_K1 + 8 : i < IT_OP ? i - IT_V0 : i - IT_V1 + 8;
                const __nv_bfloat16* src = (i < IT_V0 ? Kc : Vc) + kv_off + (size_t)(c * 2 + half) * (SLOT / 4);
                if (i >= NSLOT) mbar_wait(sb + SM_EMPTY + (i - NSLOT) * 8);
                if (tail >= IT_WUK) mbar_wait(sb + SM_FULL + tail * 8);
                ++tail;
                if (tail == IT_Q || tail == IT_OP) tail += 2;
                if (i == NITEM - 1) mbar_wait(sb + SM_FULL + BAR_PEER * 8);
                wait_due(np, shift);
                ++np;
                if (i == IT_WUV - 1) shift += TAPER;
                if (i == NITEM - 1) tma3d_pair(dst + (j & 1) * (IT_W2 - i) * SLOT, tm, c0, c1, c2, bar + (j & 1) * (IT_W2 - i) * 8, pol);
                else if (tiled) tma3d(dst, tm, c0, c1, c2, bar, pol);
                else bulk_load(dst, src, SLOT / 2, bar, pol);
            }
            if (half) return;
        } else {
            if (lane < sizeof(Maps) / 128) asm volatile("prefetch.tensormap [%0];" ::"l"(&maps.wuk + lane) : "memory");
            cnt1 = read_counter(&gs->cnt[1]);
            asm volatile("bar.sync 3, 288;" ::: "memory");
            const unsigned epoch = epoch_of(cnt1);
            signal_and_wait(&gs->cnt[0], epoch * NCTA, lane);
            if (lane == 0) {
                const uint4* q = gs->q[cta >> 5];
                bulk_load_nohint(sb + slot_off(IT_Q), q, SLOT, sb + SM_FULL + IT_Q * 8);
                bulk_load_nohint(sb + slot_off(IT_Q + 1), q + 1024, SLOT, sb + SM_FULL + (IT_Q + 1) * 8);
            }
            asm volatile("bar.sync 3, 288;" ::: "memory");
            signal_and_wait(&gs->cnt[1], epoch * NCTA, lane);
            mbar_wait(sb + SM_EMPTY + (IT_OP - NSLOT) * 8);
            mbar_wait(sb + SM_EMPTY + (IT_OP + 1 - NSLOT) * 8);
            if (lane == 0) {
                const uint4* op = gs->op[cta];
                bulk_load_nohint(sb + SM_MX, gs->stat[h], 1024, sb + SM_FULL + IT_OP * 8);
                uint32_t t1 = timer_ns();
#pragma unroll 1
                for (int i = 0; i < 8; i++) {
                    while ((int)(timer_ns() - t1) < 0) {}
                    t1 += OPGAP;
                    bulk_load_nohint(sb + slot_off(IT_OP) + i * 4096, op + i * 256, 4096, sb + SM_FULL + (IT_OP + i / 4) * 8);
                }
            }
            mbar_wait(sb + SM_FULL + (IT_V1 + 4) * 8);
            if (lane == 0) bulk_load_nohint(sb + SM_LAT, gs->lat[h], 4096, sb + SM_FULL + BAR_LAT * 8);
            mbar_wait(sb + SM_EMPTY + (IT_X - NSLOT) * 8);
            mbar_wait(sb + SM_EMPTY + (IT_X + 1 - NSLOT) * 8);
            mbar_wait(sb + SM_FULL + (IT_WUV + 1) * 8);
            mbar_wait(sb + SM_FULL + BAR_PEER * 8);
            wait_due(NITEM - 5, (uint32_t)(TAPER - XLEAD));
            if (lane == 0)
                bulk_load_nohint(sb + slot_off(IT_X), gs->x[slice >> 5][(j & 1) * 12], SLOT + 4096, sb + SM_FULL + BAR_X * 8);
        }
        const uint32_t oo  = __shfl_sync(0xffffffffu, (lane >> 3) * 2048 + slice * 32 + (j & 1) * 16 + (lane & 7) * 2, lane);
        const uint32_t src = __shfl_sync(0xffffffffu, sb + SM_FIN + ((j ^ w ^ 1) & 1) * 1536 + lane * 48, lane);
        const uint32_t sr2 = __shfl_sync(0xffffffffu, sb + SM_FIN + 3072 + lane * 80, lane);
        const uint32_t to  = w == 8 ? map_cta(sb, (j & 1) ^ 1) : sb;
        const uint32_t rcv = __shfl_sync(0xffffffffu, to + SM_RCV + lane * 4, lane);
        const uint32_t fin = __shfl_sync(0xffffffffu, to + SM_FULL + BAR_FIN * 8, lane);
        mbar_wait(sb + SM_FULL + (NITEM - 3) * 8);
        asm volatile("bar.sync 5, 320;" ::: "memory");
        const float4 p0 = ldsf4(src), p1 = ldsf4(src + 16);
        float sum = ((p0.x + p0.y) + (p0.z + p0.w)) + ((p1.x + p1.y) + (p1.z + p1.w));
        if (w == 8) {
            st_async32(rcv, __float_as_uint(sum), fin);
        } else {
            __nv_bfloat16* dst = reinterpret_cast<__nv_bfloat16*>(reinterpret_cast<char*>(out) + oo);
            mbar_wait(sb + SM_FULL + BAR_FIN * 8);
            sum += ldsf(rcv);
            asm volatile("bar.sync 7, 288;" ::: "memory");
            const float4 q0 = ldsf4(sr2), q1 = ldsf4(sr2 + 16), q2 = ldsf4(sr2 + 32), q3 = ldsf4(sr2 + 48);
            *dst = __float2bfloat16((((q0.x + sum) + q0.y) + (q0.z + q0.w) + ((q1.x + q1.y) + (q1.z + q1.w))) +
                                    (((q2.x + q2.y) + (q2.z + q2.w)) + ((q3.x + q3.y) + (q3.z + q3.w))));
        }
        return;
    }

    const int g = lane >> 2, t = lane & 3;
    const uint32_t in0 = sb + SM_IN0, in1 = sb + SM_IN1;
    auto xpos = [](int hh) { return (hh & 4) * 4 + (((hh >> 3) + (hh >> 2 & 1)) & 3) * 4 + (hh & 3); };
    const int ba = cta >> 5, ha = cta & 31;
    uint32_t* const ctx_dst = &gs->x[1][xpos(h)][(j * 4 + (w & 3)) * 16 + ((g ^ (w & 2)) & 3) * 4 + ((t - w) & 3)];
    uint32_t* const o_dst = &gs->x[0][xpos(ha)][ba * 64 + ((tid & 60) ^ ((ba & 1) * 16)) + ((t - g) & 3)];
    uint32_t* const lat_dst = &gs->lat[h][g & 3][j * 64 + ((w >> 1) ^ (g & 1)) * 16 + t * 4 + ((w * 2 ^ t) & 2)];
    {
#pragma unroll
        for (int k = 4; k < 8; k++) {
            while (__all_sync(0xffffffffu, (int)(timer_ns() - (tz + (2 * k - 1) * (PACE / 4))) < 0)) {}
            lsu_piece(k);
        }
        if (lane < 16) st_rlx2(lat_dst, EMPTY, EMPTY);
        if (lane >= 16 && w < 4) st_rlx(ctx_dst, EMPTY);
        if (w >= 6) st_rlx(o_dst, EMPTY);
        if (cta == 0 && w == 5) st_rlx(&gs->late[lane], 0u);
        if (tid < 128) sts128((tid < 64 ? in0 : in1) + ((tid >> 4) & 3) * 272 + (tid & 15) * 16, xv);
        asm volatile("cp.async.wait_group 1;" ::: "memory");
    }
    asm volatile("bar.sync 4, 384;" ::: "memory");
    const uint32_t tag = epoch_tag(epoch_of(cnt1));

    float acc[2][2];
    tile_mma<true, false>(sb, IT_WQB, in0, w, lane, acc);
    publish(gs->part[0][cta], w, lane, acc, tag);
    asm volatile("cp.async.wait_group 0;" ::: "memory");
    bar_consumers();
    tile_mma<true, false>(sb, IT_WQA, in1, w, lane, acc);
    publish(gs->part[1][cta], w, lane, acc, tag);
    bar_consumers();

    const float SC = 0.08838834764831845f * 1.4426950408889634f;
    gather(gs->part[0][h * 4], in0, tid, tag);
    tile_mma<false>(sb, IT_WUK, in0, w, lane, acc);
    if (lane < 16) {
        uint32_t* q = reinterpret_cast<uint32_t*>(gs->q[g]) + (2 * j + (w >> 2)) * 1024 + h * 32 + t;
        const int ch = 2 * (w & 3);
        q[((ch) ^ (h & 7)) * 4]     = pack_bf16(acc[0][0] * SC, acc[0][1] * SC);
        q[((ch + 1) ^ (h & 7)) * 4] = pack_bf16(acc[1][0] * SC, acc[1][1] * SC);
    }
    __syncwarp();
    asm volatile("bar.arrive 3, 288;" ::: "memory");
    gather(gs->part[1][ha * 4], in1, tid, tag);

    uint32_t qf[16];
#pragma unroll
    for (int c = 0; c < 8; c++) {
        qf[2 * c]     = lds32(in1 + ba * 272 + ((c ^ g) << 4) + t * 4);
        qf[2 * c + 1] = lds32(in1 + ba * 272 + 128 + ((c ^ g) << 4) + t * 4);
    }
    const uint32_t sc_w = sb + SM_SC + w * 512;
    auto k_item = [&](int item, uint32_t sc) {
        mbar_wait(sb + SM_FULL + item * 8);
        const uint32_t base = sb + slot_off(item) + ((lane & 7) + (lane & 8)) * 256 + ((lane >> 4) << 7);
        float s[4][4];
#pragma unroll
        for (int T = 0; T < 4; T++) { s[T][0] = s[T][1] = s[T][2] = s[T][3] = 0.f; }
#pragma unroll
        for (int c = 0; c < 8; c++) {
            const uint32_t a = base + ((c ^ (lane & 7)) << 4);
#pragma unroll
            for (int T = 0; T < 4; T++) {
                uint32_t r0, r1, r2, r3;
                ldsm4(a + T * 4096, r0, r1, r2, r3);
                mma16816(s[T], r0, r1, r2, r3, qf[2 * c], qf[2 * c + 1]);
            }
        }
        __syncwarp();
        if (lane == 0) mbar_arrive8(sb + SM_EMPTY + item * 8);
        if (t == (g >> 1)) {
#pragma unroll
            for (int T = 0; T < 4; T++) {
                stsf(sc + (16 * T + g) * 4,     (g & 1) ? s[T][1] : s[T][0]);
                stsf(sc + (16 * T + g + 8) * 4, (g & 1) ? s[T][3] : s[T][2]);
            }
        }
    };
    k_item(IT_K0 + w, sc_w);

    {
        float s[2][2][4];
#pragma unroll
        for (int i = 0; i < 16; i++) (&s[0][0][0])[i] = 0.f;
        mbar_wait(sb + SM_FULL + IT_Q * 8);
        mbar_wait(sb + SM_FULL + (IT_Q + 1) * 8);
        mbar_wait(sb + SM_FULL + (IT_C + w) * 8);
        const uint32_t cb0 = sb + slot_off(IT_C + w) + (lane & 7) * 128 + (lane >> 4) * 8192;
        const uint32_t cx = (((lane >> 3) & 1) ^ (lane & 7)) << 4;
        const uint32_t qr = ((lane & 7) + (lane & 8)) * 128;
        const uint32_t qx = ((lane >> 4) ^ (lane & 7)) << 4;
#pragma unroll
        for (int cb = 0; cb < 8; cb++) {
            const uint32_t qb = sb + slot_off(IT_Q + (cb >> 2)) + (cb & 3) * 4096 + qr;
#pragma unroll
            for (int k4 = 0; k4 < 4; k4++) {
                uint32_t b0, b1, b2, b3, a0, a1, a2, a3;
                ldsm4(cb0 + cb * 1024 + (cx ^ (k4 << 5)), b0, b1, b2, b3);
                ldsm4(qb + (qx ^ (k4 << 5)), a0, a1, a2, a3);
                mma16816(s[0][0], a0, a1, a2, a3, b0, b1);
                mma16816(s[0][1], a0, a1, a2, a3, b2, b3);
                ldsm4(qb + 2048 + (qx ^ (k4 << 5)), a0, a1, a2, a3);
                mma16816(s[1][0], a0, a1, a2, a3, b0, b1);
                mma16816(s[1][1], a0, a1, a2, a3, b2, b3);
            }
        }
        __syncwarp();
        if (lane == 0) { mbar_arrive(sb + SM_EMPTY + IT_Q * 8); mbar_arrive(sb + SM_EMPTY + (IT_Q + 1) * 8); }
#pragma unroll
        for (int r = 0; r < 4; r++) {
            const int mt = r >> 1, hi = (r & 1) * 2;
            float m = fmaxf(fmaxf(s[mt][0][hi], s[mt][0][hi + 1]), fmaxf(s[mt][1][hi], s[mt][1][hi + 1]));
            m = fmaxf(m, __shfl_xor_sync(0xffffffffu, m, 1));
            m = fmaxf(m, __shfl_xor_sync(0xffffffffu, m, 2));
            if (t == 0) stsf(sb + SM_MX + (8 * r + g) * 32 + w * 4, m);
        }
        bar_consumers();
        uint32_t pf[2][4];
#pragma unroll
        for (int r = 0; r < 4; r++) {
            const int mt = r >> 1, hi = r & 1;
            const float4 m0 = ldsf4(sb + SM_MX + (8 * r + g) * 32), m1 = ldsf4(sb + SM_MX + (8 * r + g) * 32 + 16);
            const float m = fmaxf(fmaxf(fmaxf(m0.x, m0.y), fmaxf(m0.z, m0.w)), fmaxf(fmaxf(m1.x, m1.y), fmaxf(m1.z, m1.w)));
            const uint32_t p0 = pack_bf16(ex2(s[mt][0][2 * hi] - m), ex2(s[mt][0][2 * hi + 1] - m));
            const uint32_t p1 = pack_bf16(ex2(s[mt][1][2 * hi] - m), ex2(s[mt][1][2 * hi + 1] - m));
            pf[mt][hi] = p0; pf[mt][2 + hi] = p1;
            float l = (bf_lo(p0) + bf_hi(p0)) + (bf_lo(p1) + bf_hi(p1));
            l += __shfl_xor_sync(0xffffffffu, l, 1);
            l += __shfl_xor_sync(0xffffffffu, l, 2);
            if (t == 0) stsf(sb + SM_SUM + (8 * r + g) * 32 + w * 4, l);
        }
        sts128(sb + SM_PF + (w * 2 + 0) * 512 + lane * 16, make_uint4(pf[0][0], pf[0][1], pf[0][2], pf[0][3]));
        sts128(sb + SM_PF + (w * 2 + 1) * 512 + lane * 16, make_uint4(pf[1][0], pf[1][1], pf[1][2], pf[1][3]));
        bar_consumers();
        if (w == 0) {
            const float4 m0 = ldsf4(sb + SM_MX + lane * 32), m1 = ldsf4(sb + SM_MX + lane * 32 + 16);
            const float4 l0 = ldsf4(sb + SM_SUM + lane * 32), l1 = ldsf4(sb + SM_SUM + lane * 32 + 16);
            const float m = fmaxf(fmaxf(fmaxf(m0.x, m0.y), fmaxf(m0.z, m0.w)), fmaxf(fmaxf(m1.x, m1.y), fmaxf(m1.z, m1.w)));
            const float l = ((l0.x + l0.y) + (l0.z + l0.w)) + ((l1.x + l1.y) + (l1.z + l1.w));
            gs->stat[lane][cta] = make_float2(m, l);
        }
        float o[2][8][4];
#pragma unroll
        for (int i = 0; i < 64; i++) (&o[0][0][0])[i] = 0.f;
        const uint32_t vr = w * 1024 + (lane & 7) * 128 + (lane & 8) * 1024;
        const uint32_t vx = ((lane >> 4) ^ (lane & 7)) << 4;
#pragma unroll
        for (int ks = 0; ks < 8; ks++) {
            const uint4 p0 = lds128(sb + SM_PF + (ks * 2 + 0) * 512 + lane * 16);
            const uint4 p1 = lds128(sb + SM_PF + (ks * 2 + 1) * 512 + lane * 16);
            const uint32_t vb = sb + slot_off(IT_C + ks) + vr;
#pragma unroll
            for (int n2 = 0; n2 < 4; n2++) {
                uint32_t b0, b1, b2, b3;
                ldsm4t(vb + (vx ^ (n2 << 5)), b0, b1, b2, b3);
                mma16816(o[0][2 * n2],     p0.x, p0.y, p0.z, p0.w, b0, b1);
                mma16816(o[0][2 * n2 + 1], p0.x, p0.y, p0.z, p0.w, b2, b3);
                mma16816(o[1][2 * n2],     p1.x, p1.y, p1.z, p1.w, b0, b1);
                mma16816(o[1][2 * n2 + 1], p1.x, p1.y, p1.z, p1.w, b2, b3);
            }
            __syncwarp();
            if (lane == 0) mbar_arrive(sb + SM_EMPTY + (IT_C + ks) * 8);
        }
        mbar_wait(sb + SM_FULL + (IT_K1 + 2 + (w >> 1)) * 8);
#pragma unroll
        for (int r = 0; r < 4; r++) {
            const int mt = r >> 1, hi = (r & 1) * 2;
            uint4* dst = gs->op[(8 * r + g) * 4 + (w >> 1)] + (cta >> 6) * 1024 + (w & 1) * 512 + (cta & 63) * 8;
#pragma unroll
            for (int u = 0; u < 2; u++) {
                uint4 v;
                v.x = pack_bf16(o[mt][4 * u][hi],     o[mt][4 * u][hi + 1]);
                v.y = pack_bf16(o[mt][4 * u + 1][hi], o[mt][4 * u + 1][hi + 1]);
                v.z = pack_bf16(o[mt][4 * u + 2][hi], o[mt][4 * u + 2][hi + 1]);
                v.w = pack_bf16(o[mt][4 * u + 3][hi], o[mt][4 * u + 3][hi + 1]);
                dst[(t + 4 * u) ^ (cta & 7)] = v;
            }
        }
        asm volatile("bar.arrive 3, 288;" ::: "memory");
    }

    k_item(IT_K1 + w, sc_w + 256);
    __syncwarp();
    {
        const float4 s = ldsf4(sc_w + lane * 16);
        float m = fmaxf(fmaxf(s.x, s.y), fmaxf(s.z, s.w));
#pragma unroll
        for (int d = 1; d < 32; d <<= 1) m = fmaxf(m, __shfl_xor_sync(0xffffffffu, m, d));
        if (lane == 0) stsf(sb + SM_ML + w * 4, m);
        bar_consumers();
        const float4 m0 = ldsf4(sb + SM_ML), m1 = ldsf4(sb + SM_ML + 16);
        m = fmaxf(fmaxf(fmaxf(m0.x, m0.y), fmaxf(m0.z, m0.w)), fmaxf(fmaxf(m1.x, m1.y), fmaxf(m1.z, m1.w))) * SC;
        const uint32_t p0 = pack_bf16(ex2(fmaf(s.x, SC, -m)), ex2(fmaf(s.y, SC, -m)));
        const uint32_t p1 = pack_bf16(ex2(fmaf(s.z, SC, -m)), ex2(fmaf(s.w, SC, -m)));
        float l = (bf_lo(p0) + bf_hi(p0)) + (bf_lo(p1) + bf_hi(p1));
#pragma unroll
        for (int d = 1; d < 32; d <<= 1) l += __shfl_xor_sync(0xffffffffu, l, d);
        if (lane == 0) stsf(sb + SM_ML + 32 + w * 4, l);
        sts64(sb + SM_PA + w * 256 + lane * 8, p0, p1);
        __syncwarp();
    }

    float oa[4][4];
#pragma unroll
    for (int i = 0; i < 16; i++) (&oa[0][0])[i] = 0.f;
    auto v_item = [&](int item, uint32_t pa) {
        uint32_t p[8];
#pragma unroll
        for (int i = 0; i < 8; i++) p[i] = lds32(pa + i * 16 + t * 4);
        mbar_wait(sb + SM_FULL + item * 8);
        const uint32_t base = sb + slot_off(item) + ((lane & 7) + ((lane >> 4) << 3)) * 256 + ((lane & 8) << 4);
#pragma unroll
        for (int c = 0; c < 8; c++) {
            const uint32_t a = base + ((c ^ (lane & 7)) << 4);
            const uint32_t mask = ((c == (g ^ (2 * t))) ? 0x0000ffffu : 0u) | ((c == (g ^ (2 * t + 1))) ? 0xffff0000u : 0u);
#pragma unroll
            for (int T = 0; T < 4; T++) {
                uint32_t r0, r1, r2, r3;
                ldsm4t(a + T * 4096, r0, r1, r2, r3);
                mma16816(oa[T], r0, r1, r2, r3, p[2 * T] & mask, p[2 * T + 1] & mask);
            }
        }
        __syncwarp();
        if (lane == 0) mbar_arrive8(sb + SM_EMPTY + item * 8);
    };
    v_item(IT_V0 + w, sb + SM_PA + w * 256);

    mbar_wait(sb + SM_FULL + IT_OP * 8);
    if (w < 4) {
        const float2 st = ldsf2(sb + SM_MX + tid * 8);
        float m = st.x;
#pragma unroll
        for (int d = 1; d < 32; d <<= 1) m = fmaxf(m, __shfl_xor_sync(0xffffffffu, m, d));
        const uint32_t wb = pack_bf16(ex2(st.x - m), 0.f);
        float l = bf_lo(wb) * st.y;
#pragma unroll
        for (int d = 1; d < 32; d <<= 1) l += __shfl_xor_sync(0xffffffffu, l, d);
#pragma unroll
        for (int bb = 0; bb < 4; bb++) sts16(in0 + bb * 272 + tid * 2, bb == w ? (uint16_t)wb : (uint16_t)0);
        if (lane == 0) stsf(sb + SM_ML + 64 + w * 4, 1.f / l);
    }
    bar_consumers();
    tile_mma<true>(sb, IT_OP, in0, w, lane, acc);
    if (lane < 16) {
        const float inv = ldsf(sb + SM_ML + 64 + g * 4);
        const uint32_t v0 = pack_bf16(acc[0][0] * inv, acc[0][1] * inv), v1 = pack_bf16(acc[1][0] * inv, acc[1][1] * inv);
        st_rlx2(lat_dst, (t & 1) ? v1 : v0, (t & 1) ? v0 : v1);
    }

    {
        const float4 l0 = ldsf4(sb + SM_ML + 32), l1 = ldsf4(sb + SM_ML + 48);
        const float inv = 1.f / (((l0.x + l0.y) + (l0.z + l0.w)) + ((l1.x + l1.y) + (l1.z + l1.w)));
        v_item(IT_V1 + w, sb + SM_PA + w * 256 + 128);
        const uint32_t so = sb + SM_PF + w * 512 + (16 * t + g) * 4;
        stsf(so,       (oa[0][0] + oa[1][0]) + (oa[2][0] + oa[3][0]));
        stsf(so + 32,  (oa[0][1] + oa[1][1]) + (oa[2][1] + oa[3][1]));
        stsf(so + 256, (oa[0][2] + oa[1][2]) + (oa[2][2] + oa[3][2]));
        stsf(so + 288, (oa[0][3] + oa[1][3]) + (oa[2][3] + oa[3][3]));
        if (w < 6) {
            asm volatile("bar.arrive 1, 256;" ::: "memory");
        } else {
            bar_consumers();
            float x = 0.f, y = 0.f;
#pragma unroll
            for (int i = 0; i < 8; i++) {
                const float2 v = ldsf2(sb + SM_PF + i * 512 + (tid & 63) * 8);
                x += v.x; y += v.y;
            }
            st_rlx(o_dst, pack_bf16(x * inv, y * inv));
            if (lane == 0) {
                const uint32_t to = map_cta(sb, w & 1);
                st_async32(to + SM_RCV + 128 + (j & 1) * 4, 0u, to + SM_FULL + BAR_PEER * 8);
            }
        }
    }

    if (w < 4) {
        const uint32_t lo = (g & 3) * 1024 + (g >> 2) * 512 + (g & 1) * 64 + t * 16;
        const int wd = ((lane >> 2 & 2) + (lane >> 4)) ^ (lane >> 1 & 3);
        const uint32_t base = sb + ((lane & 6) * 4 + wd * 2 + (lane & 1)) * 64 + (((w ^ wd) & 3) << 4);
        const uint64_t dst = __shfl_sync(0xffffffffu, (unsigned long long)ctx_dst, lane);
        mbar_wait(sb + SM_FULL + BAR_LAT * 8);
        uint4 a[8];
#pragma unroll
        for (int i = 0; i < 8; i++) a[i] = lds128(sb + SM_LAT + (lo ^ (i * 64)));
        int it = 0;
        while (refetch<0>(a, lane, [&](int i) { return (const char*)gs->lat[h] + (lo ^ (i * 64)); }))
            if (++it > SPIN_LIMIT) __trap();
        float v0 = 0.f, v1 = 0.f;
#pragma unroll
        for (int i = 0; i < 2; i++) {
            float c[4][4];
#pragma unroll
            for (int k = 0; k < 16; k++) (&c[0][0])[k] = 0.f;
            c[0][0] = v0; c[0][1] = v1;
            mbar_wait(sb + SM_FULL + (IT_WUV + i) * 8);
#pragma unroll
            for (int kk = 0; kk < 8; kk++) {
                uint32_t r0, r1, r2, r3;
                ldsm4t(base + slot_off(IT_WUV + i) + kk * 2048, r0, r1, r2, r3);
                mma16816(c[2 * (kk & 1)],     a[kk].x, a[kk].y, a[kk].z, a[kk].w, r0, r1);
                mma16816(c[2 * (kk & 1) + 1], a[kk].x, a[kk].y, a[kk].z, a[kk].w, r2, r3);
            }
            v0 = (c[0][0] + c[1][2]) + (c[2][0] + c[3][2]);
            v1 = (c[0][1] + c[1][3]) + (c[2][1] + c[3][3]);
            if (i == 0) { v0 = __shfl_xor_sync(0xffffffffu, v0, 16); v1 = __shfl_xor_sync(0xffffffffu, v1, 16); }
        }
        st_rlx_if(dst, pack_bf16(v0, v1), lane >= 16);
    }

    {
        const bool isB = slice >= 32;
        const int r = j & 1;
        const uint32_t xl = isB ? t * 64 + (((g ^ (t & 2)) & 3) << 4) : (g & 3) * 256 + ((g & 1) * 4 + t) * 16;
        const uint32_t cs = isB ? 256 : 64;
        const uint32_t xo = r * 8192 + (w >> 1) * 1024 + (w & 1) * 2 * cs + xl, xz = (1 - r) * 12288 + w * 1024 + (g >> 2) * 2 * cs + xl;
        auto xoff = [&](int i) { return i < 6 ? (i >> 1) * 4096 + (xo ^ ((i & 1) * cs)) : xz ^ ((i & 1) * cs); };
        const char* src = (const char*)gs->x[slice >> 5][r * 12];
        uint32_t off[2], ofz[2];
#pragma unroll
        for (int u = 0; u < 2; u++) {
            const int tt = (lane & 7) >> 1;
            const int row = 8 * tt + 2 * ((2 * u + (lane >> 4) + tt) & 3) + (lane & 1);
            off[u] = sb + w * 2048 + row * 32 + ((((lane >> 3) ^ (row >> 2)) & 1) << 4);
            ofz[u] = __shfl_sync(0xffffffffu, sb + (w < 4 ? slot_off(IT_WO + 3) : slot_off(IT_W2)) + (w & 3) * 4096 + (lane & 8) * 256 +
                                              row * 32 + (((r ^ (row >> 2)) & 1) << 4), lane);
        }
        const uint32_t fin = __shfl_sync(0xffffffffu, sb + SM_FIN + (t & 1) * 768 + g * 48 + ((w ^ (t & 1)) << 2), lane);
        const uint32_t fi2 = __shfl_sync(0xffffffffu, sb + SM_FIN + 3072 + (t & 1) * 1280 + g * 80 + (((w * 2 + (t >> 1)) ^ (t * 2 & 2)) << 2), lane);
        uint32_t a[2][4][4];
        uint4 x[8];
        float c[4][4];
        auto load_w = [&](int i) {
            mbar_wait(sb + SM_FULL + (i < 3 ? IT_WO + i : w < 4 ? IT_WO + 3 : IT_W2) * 8);
#pragma unroll
            for (int q = 0; q < 4; q++)
                ldsm4t((i < 3 ? slot_off(IT_WO + i) + off[q & 1] : ofz[q & 1]) + (q >> 1) * 1024,
                       a[i & 1][q][0], a[i & 1][q][1], a[i & 1][q][2], a[i & 1][q][3]);
        };
        auto mma_w = [&](int i) {
#pragma unroll
            for (int q = 0; q < 4; q++) {
                if (i == 0 || i == 3) c[q][0] = c[q][1] = c[q][2] = c[q][3] = 0.f;
                mma16816(c[q], a[i & 1][q][0], a[i & 1][q][1], a[i & 1][q][2], a[i & 1][q][3],
                         (q & 1) ? x[2 * i + (q >> 1)].z : x[2 * i + (q >> 1)].x, (q & 1) ? x[2 * i + (q >> 1)].w : x[2 * i + (q >> 1)].y);
            }
        };
        load_w(0); load_w(1);
        mbar_wait(sb + SM_FULL + BAR_X * 8);
#pragma unroll
        for (int i = 0; i < 8; i++) x[i] = lds128_if(sb + slot_off(IT_X) + xoff(i), i >= 6 || lane < 16);
        int it = 0;
        while (true) {
            mma_w(0); mma_w(1);
            if (!refetch<6>(x, lane, [&](int i) { return src + xoff(i); })) break;
            if (++it > SPIN_LIMIT) __trap();
        }
        load_w(2);
        mma_w(2);
#pragma unroll
        for (int e = 0; e < 4; e++) stsf_if(fin + (e >> 1) * 1536 + (e & 1) * 384, (c[0][e] + c[1][e]) + (c[2][e] + c[3][e]), t < 2);
        asm volatile("bar.arrive 5, 320;" ::: "memory");
        load_w(3);
        mma_w(3);
#pragma unroll
        for (int e = 0; e < 2; e++) {
            const float lo = (c[0][e] + c[1][e]) + (c[2][e] + c[3][e]), hi = (c[0][e + 2] + c[1][e + 2]) + (c[2][e + 2] + c[3][e + 2]);
            stsf(fi2 + e * 640, t < 2 ? lo : hi);
        }
        asm volatile("bar.arrive 7, 288;" ::: "memory");
    }
}

typedef CUresult (*EncodeTiledFn)(CUtensorMap*, CUtensorMapDataType, cuuint32_t, void*, const cuuint64_t*,
                                  const cuuint64_t*, const cuuint32_t*, const cuuint32_t*, CUtensorMapInterleave,
                                  CUtensorMapSwizzle, CUtensorMapL2promotion, CUtensorMapFloatOOBfill);

void encode_map(EncodeTiledFn enc, CUtensorMap* tm, const void* p, cuuint64_t cols, cuuint64_t rows,
                cuuint32_t brows, cuuint32_t bblk) {
    cuuint64_t dims[3] = {64, rows, cols / 64};
    cuuint64_t strides[2] = {cols * 2, 128};
    cuuint32_t box[3] = {64, brows, bblk};
    cuuint32_t es[3] = {1, 1, 1};
    enc(tm, CU_TENSOR_MAP_DATA_TYPE_BFLOAT16, 3, const_cast<void*>(p), dims, strides, box, es,
        CU_TENSOR_MAP_INTERLEAVE_NONE, CU_TENSOR_MAP_SWIZZLE_128B, CU_TENSOR_MAP_L2_PROMOTION_L2_256B,
        CU_TENSOR_MAP_FLOAT_OOB_FILL_NONE);
}

void encode_slice_map(EncodeTiledFn enc, CUtensorMap* tm, const void* p, cuuint64_t cols, cuuint64_t rows, cuuint32_t bcols) {
    cuuint64_t dims[3] = {cols, 256, rows / 256};
    cuuint64_t strides[2] = {cols * 2, cols * 512};
    cuuint32_t box[3] = {bcols, 4096 / bcols, 1};
    cuuint32_t es[3] = {1, 1, 1};
    enc(tm, CU_TENSOR_MAP_DATA_TYPE_BFLOAT16, 3, const_cast<void*>(p), dims, strides, box, es, CU_TENSOR_MAP_INTERLEAVE_NONE,
        bcols == 16 ? CU_TENSOR_MAP_SWIZZLE_32B : CU_TENSOR_MAP_SWIZZLE_64B, CU_TENSOR_MAP_L2_PROMOTION_L2_128B,
        CU_TENSOR_MAP_FLOAT_OOB_FILL_NONE);
}

}

extern "C" void kernel_launch(void* const* d_in, const int* in_sizes, int n_in, void* d_out, int out_size) {
    (void)in_sizes; (void)n_in; (void)out_size;
    static EncodeTiledFn enc = nullptr;
    static Scratch* gs = nullptr;
    if (!enc) {
        cudaGetSymbolAddress((void**)&gs, g_scratch);
        void* fn = nullptr;
        cudaDriverEntryPointQueryResult qr;
        cudaGetDriverEntryPoint("cuTensorMapEncodeTiled", &fn, cudaEnableDefault, &qr);
        enc = (EncodeTiledFn)fn;
        cudaFuncSetAttribute(fused_decode_kernel, cudaFuncAttributeMaxDynamicSharedMemorySize, SM_END);
    }
    Maps maps;
    encode_map(enc, &maps.wuk, d_in[8], 4096, 512, 32, 2);
    encode_slice_map(enc, &maps.wuv, d_in[9], 4096, 512, 32);
    encode_slice_map(enc, &maps.woB, d_in[10], 512, 4096, 16);
    encode_slice_map(enc, &maps.woA, d_in[4], 512, 4096, 16);
    encode_map(enc, &maps.ckv, d_in[6], 512, 16384, 8, 8);
    fused_decode_kernel<<<NCTA, NTHR, SM_END>>>((const __nv_bfloat16*)d_in[0], (const __nv_bfloat16*)d_in[5],
                                                (const __nv_bfloat16*)d_in[7], (const __nv_bfloat16*)d_in[3],
                                                (const __nv_bfloat16*)d_in[1] + 3072 * 128, (const __nv_bfloat16*)d_in[2] + 3072 * 128,
                                                (__nv_bfloat16*)d_out, gs, maps);
}
```

```cpp
#include <cuda_runtime.h>
#include <cuda_bf16.h>
#include <cuda.h>
#include <stdint.h>

namespace {

constexpr int NCTA   = 128;
constexpr int NSLOT  = 13;
constexpr int SLOT   = 16384;
constexpr int NITEM  = 56;
constexpr int NTHR   = 384;

constexpr int INFLIGHT = 4;
constexpr int PACE     = 644;
constexpr int LEAD     = 550;
constexpr int TAPER    = 260;
constexpr int XLEAD    = 500;
constexpr int OPGAP    = 250;
constexpr int NWIN     = 4;
__device__ constexpr int win_pos(int k)  { return k == 0 ? 10 : k == 1 ? 20 : k == 2 ? 31 : 38; }
__device__ constexpr int win_late(int k) { return k == 0 ? 1860 : k == 1 ? 1880 : k == 2 ? 1870 : 1780; }
constexpr int GAIN     = 11;

constexpr int IT_WQB = 0, IT_WQA = 2, IT_WUK = 4, IT_K0 = 6, IT_Q = 14, IT_C = 16, IT_K1 = 24, IT_V0 = 32,
              IT_OP = 40, IT_V1 = 42, IT_WUV = 50, IT_WO = 52;
constexpr int IT_X = 56;
constexpr int IT_W2 = 58;
constexpr int BAR_LAT = 56, BAR_FIN = 57, BAR_X = 59, BAR_PEER = 60, BAR_END = 61;

constexpr int SM_FULL  = NSLOT * SLOT;
constexpr int SM_EMPTY = SM_FULL + 512;
constexpr int SM_IN0   = SM_EMPTY + 512;
constexpr int SM_IN1   = SM_IN0 + 1088;
constexpr int SM_SC    = SM_IN1 + 1088;
constexpr int SM_PA    = SM_SC + 4096;
constexpr int SM_PF    = SM_PA + 2048;
constexpr int SM_MX    = SM_PF + 8192;
constexpr int SM_ML    = SM_MX + 1024;
constexpr int SM_RCV   = SM_ML + 128;
constexpr int SM_PACE  = SM_RCV + 144;
constexpr int SM_END   = SM_PACE + 32;
constexpr int SM_LAT   = SM_PF + 4096;
constexpr int SM_FIN   = SM_SC;
constexpr int SM_SUM   = SM_IN0;
static_assert(SM_END <= 232448, "smem");

struct Maps { CUtensorMap wuk, wuv, woA, woB, ckv; };

struct Scratch {
    unsigned cnt[32];
    unsigned late[32];
    float    part[2][NCTA][512];
    uint32_t x[2][32][256];
    uint32_t lat[32][4][256];
    uint4    q[4][2048];
    uint4    op[NCTA][2048];
    float2   stat[32][128];
};
__device__ __align__(128) Scratch g_scratch;

constexpr int SPIN_LIMIT = 1 << 22;

__device__ __forceinline__ uint32_t smem_u32(const void* p) { return (uint32_t)__cvta_generic_to_shared(p); }
__device__ __forceinline__ void mbar_init(uint32_t bar, uint32_t cnt) {
    asm volatile("mbarrier.init.shared::cta.b64 [%0], %1;" ::"r"(bar), "r"(cnt) : "memory");
}
__device__ __forceinline__ void mbar_expect_tx(uint32_t bar, uint32_t bytes) {
    asm volatile("mbarrier.arrive.expect_tx.shared::cta.b64 _, [%0], %1;" ::"r"(bar), "r"(bytes) : "memory");
}
__device__ __forceinline__ void mbar_arrive(uint32_t bar) {
    asm volatile("mbarrier.arrive.shared::cta.b64 _, [%0];" ::"r"(bar) : "memory");
}
__device__ __forceinline__ void mbar_arrive8(uint32_t bar) {
    asm volatile("mbarrier.arrive.shared::cta.b64 _, [%0], 8;" ::"r"(bar) : "memory");
}
__device__ __forceinline__ void mbar_wait(uint32_t bar) {
    uint32_t done;
    int it = 0;
    do {
        asm volatile("{\n.reg .pred p;\nmbarrier.try_wait.parity.shared::cta.b64 p, [%1], 0;\nselp.u32 %0, 1, 0, p;\n}"
                     : "=r"(done) : "r"(bar) : "memory");
        if (++it > SPIN_LIMIT) __trap();
    } while (!done);
}
__device__ __forceinline__ uint32_t map_cta(uint32_t a, uint32_t rank) {
    uint32_t r; asm("mapa.shared::cluster.u32 %0, %1, %2;" : "=r"(r) : "r"(a), "r"(rank)); return r;
}
__device__ __forceinline__ void st_async32(uint32_t a, uint32_t v, uint32_t bar) {
    asm volatile("st.async.shared::cluster.mbarrier::complete_tx::bytes.b32 [%0], %1, [%2];" ::"r"(a), "r"(v), "r"(bar) : "memory");
}
__device__ __forceinline__ uint64_t evict_first() {
    uint64_t pol; asm volatile("createpolicy.fractional.L2::evict_first.b64 %0, 1.0;" : "=l"(pol)); return pol;
}
#define ELECT "{\n.reg .pred p;\nelect.sync _|p, 0xffffffff;\n@p "
__device__ __forceinline__ void bulk_load(uint32_t dst, const void* src, uint32_t bytes, uint32_t bar, uint64_t pol) {
    asm volatile(ELECT "cp.async.bulk.shared::cluster.global.mbarrier::complete_tx::bytes.L2::cache_hint [%0], [%1], %2, [%3], %4;\n}"
                 ::"r"(dst), "l"(src), "r"(bytes), "r"(bar), "l"(pol) : "memory");
}
__device__ __forceinline__ void bulk_load_nohint(uint32_t dst, const void* src, uint32_t bytes, uint32_t bar) {
    asm volatile("cp.async.bulk.shared::cluster.global.mbarrier::complete_tx::bytes [%0], [%1], %2, [%3];"
                 ::"r"(dst), "l"(src), "r"(bytes), "r"(bar) : "memory");
}
__device__ __forceinline__ void tma3d(uint32_t dst, const CUtensorMap* tm, int c0, int c1, int c2, uint32_t bar, uint64_t pol) {
    asm volatile(ELECT "cp.async.bulk.tensor.3d.shared::cluster.global.mbarrier::complete_tx::bytes.L2::cache_hint [%0], [%1, {%3, %4, %5}], [%2], %6;\n}"
                 ::"r"(dst), "l"(tm), "r"(bar), "r"(c0), "r"(c1), "r"(c2), "l"(pol) : "memory");
}
__device__ __forceinline__ void tma3d_pair(uint32_t dst, const CUtensorMap* tm, int c0, int c1, int c2, uint32_t bar, uint64_t pol) {
    asm volatile(ELECT "cp.async.bulk.tensor.3d.shared::cluster.global.mbarrier::complete_tx::bytes.multicast::cluster.L2::cache_hint [%0], [%1, {%3, %4, %5}], [%2], %7, %6;\n}"
                 ::"r"(dst), "l"(tm), "r"(bar), "r"(c0), "r"(c1), "r"(c2), "l"(pol), "h"((uint16_t)3) : "memory");
}
__device__ __forceinline__ void ldsm4(uint32_t a, uint32_t& r0, uint32_t& r1, uint32_t& r2, uint32_t& r3) {
    asm volatile("ldmatrix.sync.aligned.m8n8.x4.shared.b16 {%0,%1,%2,%3}, [%4];"
                 : "=r"(r0), "=r"(r1), "=r"(r2), "=r"(r3) : "r"(a) : "memory");
}
__device__ __forceinline__ void ldsm4t(uint32_t a, uint32_t& r0, uint32_t& r1, uint32_t& r2, uint32_t& r3) {
    asm volatile("ldmatrix.sync.aligned.m8n8.x4.trans.shared.b16 {%0,%1,%2,%3}, [%4];"
                 : "=r"(r0), "=r"(r1), "=r"(r2), "=r"(r3) : "r"(a) : "memory");
}
__device__ __forceinline__ void mma16816(float (&c)[4], uint32_t a0, uint32_t a1, uint32_t a2, uint32_t a3,
                                         uint32_t b0, uint32_t b1) {
    asm volatile("mma.sync.aligned.m16n8k16.row.col.f32.bf16.bf16.f32 {%0,%1,%2,%3}, {%4,%5,%6,%7}, {%8,%9}, {%0,%1,%2,%3};"
                 : "+f"(c[0]), "+f"(c[1]), "+f"(c[2]), "+f"(c[3])
                 : "r"(a0), "r"(a1), "r"(a2), "r"(a3), "r"(b0), "r"(b1));
}
__device__ __forceinline__ uint32_t lds32(uint32_t a) {
    uint32_t v; asm volatile("ld.shared.b32 %0, [%1];" : "=r"(v) : "r"(a) : "memory"); return v;
}
__device__ __forceinline__ float ldsf(uint32_t a) {
    float v; asm volatile("ld.shared.f32 %0, [%1];" : "=f"(v) : "r"(a) : "memory"); return v;
}
__device__ __forceinline__ float2 ldsf2(uint32_t a) {
    float2 v; asm volatile("ld.shared.v2.f32 {%0,%1}, [%2];" : "=f"(v.x), "=f"(v.y) : "r"(a) : "memory"); return v;
}
__device__ __forceinline__ float4 ldsf4(uint32_t a) {
    float4 v; asm volatile("ld.shared.v4.f32 {%0,%1,%2,%3}, [%4];" : "=f"(v.x), "=f"(v.y), "=f"(v.z), "=f"(v.w) : "r"(a) : "memory"); return v;
}
__device__ __forceinline__ uint4 lds128(uint32_t a) {
    uint4 v; asm volatile("ld.shared.v4.b32 {%0,%1,%2,%3}, [%4];" : "=r"(v.x), "=r"(v.y), "=r"(v.z), "=r"(v.w) : "r"(a) : "memory"); return v;
}
__device__ __forceinline__ uint4 lds128_if(uint32_t a, bool on) {
    uint4 v;
    asm volatile("{\n.reg .pred p;\nsetp.ne.u32 p, %5, 0;\n@p ld.shared.v4.b32 {%0,%1,%2,%3}, [%4];\n}"
                 : "=r"(v.x), "=r"(v.y), "=r"(v.z), "=r"(v.w) : "r"(a), "r"((uint32_t)on) : "memory");
    return v;
}
__device__ __forceinline__ void stsf_if(uint32_t a, float v, bool on) {
    asm volatile("{\n.reg .pred p;\nsetp.ne.u32 p, %2, 0;\n@p st.shared.f32 [%0], %1;\n}" ::"r"(a), "f"(v), "r"((uint32_t)on) : "memory");
}
__device__ __forceinline__ void sts16(uint32_t a, uint16_t v) { asm volatile("st.shared.b16 [%0], %1;" ::"r"(a), "h"(v) : "memory"); }
__device__ __forceinline__ void sts32(uint32_t a, uint32_t v) { asm volatile("st.shared.b32 [%0], %1;" ::"r"(a), "r"(v) : "memory"); }
__device__ __forceinline__ void stsf(uint32_t a, float v) { asm volatile("st.shared.f32 [%0], %1;" ::"r"(a), "f"(v) : "memory"); }
__device__ __forceinline__ void sts64(uint32_t a, uint32_t x, uint32_t y) {
    asm volatile("st.shared.v2.b32 [%0], {%1,%2};" ::"r"(a), "r"(x), "r"(y) : "memory");
}
__device__ __forceinline__ void sts128(uint32_t a, uint4 v) {
    asm volatile("st.shared.v4.b32 [%0], {%1,%2,%3,%4};" ::"r"(a), "r"(v.x), "r"(v.y), "r"(v.z), "r"(v.w) : "memory");
}
__device__ __forceinline__ uint32_t pack_bf16(float lo, float hi) {
    uint32_t r; asm("cvt.rn.bf16x2.f32 %0, %1, %2;" : "=r"(r) : "f"(hi), "f"(lo)); return r;
}
__device__ __forceinline__ float bf_lo(uint32_t v) { return __uint_as_float(v << 16); }
__device__ __forceinline__ float bf_hi(uint32_t v) { return __uint_as_float(v & 0xffff0000u); }
__device__ __forceinline__ float ex2(float x) { float y; asm("ex2.approx.ftz.f32 %0, %1;" : "=f"(y) : "f"(x)); return y; }
__device__ __forceinline__ uint32_t timer_ns() { uint32_t t; asm volatile("mov.u32 %0, %%globaltimer_lo;" : "=r"(t)); return t; }
__device__ __forceinline__ void bar_consumers() { asm volatile("bar.sync 1, 256;" ::: "memory"); }

__device__ __forceinline__ uint32_t tagf(float v, uint32_t tag) { return (__float_as_uint(v) & 0xffffff00u) | tag; }
__device__ __forceinline__ uint2 ld_rlx2(const float* p) {
    uint2 v; asm volatile("ld.relaxed.gpu.global.v2.b32 {%0,%1}, [%2];" : "=r"(v.x), "=r"(v.y) : "l"(p) : "memory"); return v;
}
__device__ __forceinline__ float untag(uint32_t v) { return __uint_as_float(v & 0xffffff00u); }

__device__ __forceinline__ uint32_t slot_off(int item) { return (uint32_t)(item % NSLOT) * SLOT; }

template <bool TRANS, bool TMA = true>
__device__ __forceinline__ void tile_mma(uint32_t sb, int item, uint32_t in, int w, int lane, float (&acc)[2][2]) {
    const int g = lane >> 2, t = lane & 3;
    float c[4][4];
#pragma unroll
    for (int i = 0; i < 16; i++) (&c[0][0])[i] = 0.f;
    uint32_t a[16];
    const uint32_t ia = in + (g & 3) * 272 + t * 4;
#pragma unroll
    for (int i = 0; i < 16; i++) a[i] = lds32(ia + i * 16);
    const uint32_t s0 = sb + slot_off(item), s1 = sb + slot_off(item + 1);
    if (TRANS) {
        const int r = (lane & 7) + (lane & 8);
        const int ch = 2 * (w & 3) + (lane >> 4);
        const uint32_t off = (TMA ? (w >> 2) * 8192 + r * 128 : (w >> 2) * 128 + r * 256) + ((ch ^ (lane & 7)) << 4);
#pragma unroll
        for (int kk = 0; kk < 8; kk++) {
            if (TMA && (kk & 3) == 0) mbar_wait(sb + SM_FULL + (item + (kk >> 2)) * 8);
            uint32_t r0, r1, r2, r3;
            ldsm4t(((kk >> 2) ? s1 : s0) + off + (kk & 3) * (TMA ? 2048 : 4096), r0, r1, r2, r3);
            mma16816(c[2 * (kk & 1)],     a[2 * kk], 0u, a[2 * kk + 1], 0u, r0, r1);
            mma16816(c[2 * (kk & 1) + 1], a[2 * kk], 0u, a[2 * kk + 1], 0u, r2, r3);
        }
    } else {
        mbar_wait(sb + SM_FULL + (item + (w >> 2)) * 8);
        const int r = 16 * (w & 3) + (lane & 7) + ((lane >> 4) << 3);
        const uint32_t base = ((w >> 2) ? s1 : s0) + (r & 32) * 128 + r * 128 + ((((lane >> 3) & 1) ^ (lane & 7)) << 4);
#pragma unroll
        for (int kk = 0; kk < 8; kk++) {
            uint32_t r0, r1, r2, r3;
            ldsm4((base ^ ((kk & 3) << 5)) + (kk >> 2) * 4096, r0, r1, r2, r3);
            mma16816(c[2 * (kk & 1)],     a[2 * kk], 0u, a[2 * kk + 1], 0u, r0, r1);
            mma16816(c[2 * (kk & 1) + 1], a[2 * kk], 0u, a[2 * kk + 1], 0u, r2, r3);
        }
    }
    __syncwarp();
    if (lane == 0) {
        mbar_arrive(sb + SM_EMPTY + item * 8);
        mbar_arrive(sb + SM_EMPTY + (item + 1) * 8);
    }
    acc[0][0] = c[0][0] + c[2][0]; acc[0][1] = c[0][1] + c[2][1];
    acc[1][0] = c[1][0] + c[3][0]; acc[1][1] = c[1][1] + c[3][1];
}

__device__ __forceinline__ void publish(float* dst, int w, int lane, const float (&acc)[2][2], uint32_t tag) {
    if (lane < 16)
        asm volatile("st.relaxed.gpu.global.v4.b32 [%0], {%1,%2,%3,%4};" ::"l"(dst + w * 64 + lane * 4),
                     "r"(tagf(acc[0][0], tag)), "r"(tagf(acc[0][1], tag)), "r"(tagf(acc[1][0], tag)), "r"(tagf(acc[1][1], tag)) : "memory");
}

__device__ __forceinline__ void gather(const float* part, uint32_t in, int tid, uint32_t tag) {
    const float* p = part + tid * 2;
    uint2 v0, v1, v2, v3;
    int it = 0;
    while (true) {
        v0 = ld_rlx2(p); v1 = ld_rlx2(p + 512); v2 = ld_rlx2(p + 1024); v3 = ld_rlx2(p + 1536);
        uint32_t bad = ((v0.x ^ tag) | (v0.y ^ tag) | (v1.x ^ tag) | (v1.y ^ tag) |
                        (v2.x ^ tag) | (v2.y ^ tag) | (v3.x ^ tag) | (v3.y ^ tag)) & 0xffu;
        if (__all_sync(0xffffffffu, bad == 0)) break;
        if (++it > SPIN_LIMIT) __trap();
    }
    float x = (untag(v0.x) + untag(v1.x)) + (untag(v2.x) + untag(v3.x));
    float y = (untag(v0.y) + untag(v1.y)) + (untag(v2.y) + untag(v3.y));
    sts32(in + ((tid >> 3) & 3) * 272 + (tid >> 5) * 32 + (tid & 1) * 16 + (tid & 6) * 2, pack_bf16(x, y));
    bar_consumers();
}

constexpr uint32_t EMPTY = 0xffffffffu;
__device__ __forceinline__ void st_rlx(uint32_t* p, uint32_t v) {
    asm volatile("st.relaxed.gpu.global.b32 [%0], %1;" ::"l"(p), "r"(v) : "memory");
}
__device__ __forceinline__ void st_rlx_if(uint64_t p, uint32_t v, bool on) {
    asm volatile("{\n.reg .pred p;\nsetp.ne.u32 p, %2, 0;\n@p st.relaxed.gpu.global.b32 [%0], %1;\n}" ::"l"(p), "r"(v), "r"((uint32_t)on) : "memory");
}
__device__ __forceinline__ void st_rlx2(uint32_t* p, uint32_t v0, uint32_t v1) {
    asm volatile("st.relaxed.gpu.global.v2.b32 [%0], {%1,%2};" ::"l"(p), "r"(v0), "r"(v1) : "memory");
}
__device__ __forceinline__ void ld_rlx4_if(uint4& v, const void* p, bool need) {
    asm volatile("{\n.reg .pred p;\nsetp.ne.u32 p, %5, 0;\n@p ld.relaxed.gpu.global.v4.b32 {%0,%1,%2,%3}, [%4];\n}"
                 : "+r"(v.x), "+r"(v.y), "+r"(v.z), "+r"(v.w) : "l"(p), "r"((uint32_t)need) : "memory");
}

template <int HALF, class F>
__device__ __forceinline__ bool refetch(uint4 (&x)[8], int lane, F addr) {
    uint32_t m[8], m0 = 0, m1 = 0;
#pragma unroll
    for (int i = 0; i < 8; i++) {
        m[i] = max(max(x[i].x, x[i].y), max(x[i].z, x[i].w));
        if (i < HALF) m0 = max(m0, m[i]); else m1 = max(m1, m[i]);
    }
    if (!__any_sync(0xffffffffu, (m0 == EMPTY && lane < 16) || m1 == EMPTY)) return false;
#pragma unroll
    for (int i = 0; i < 8; i++) ld_rlx4_if(x[i], addr(i), m[i] == EMPTY && (i >= HALF || lane < 16));
    return true;
}

__device__ __forceinline__ unsigned read_counter(const unsigned* cnt) {
    unsigned v;
    asm volatile("ld.relaxed.gpu.global.u32 %0, [%1];" : "=r"(v) : "l"(cnt) : "memory");
    return v;
}
__device__ __forceinline__ unsigned epoch_of(unsigned cnt) {
    asm volatile("" : "+r"(cnt) :: "memory");
    return cnt / NCTA + 1;
}
__device__ __forceinline__ uint32_t epoch_tag(unsigned epoch) { return (epoch & 0x7fu) | 0x80u; }

__device__ __forceinline__ void signal_and_wait(unsigned* cnt, unsigned target, int lane) {
    if (lane == 0) asm volatile("red.release.gpu.global.add.u32 [%0], 1;" ::"l"(cnt) : "memory");
    int it = 0;
    while (true) {
        unsigned v;
        asm volatile("ld.acquire.gpu.global.u32 %0, [%1];" : "=r"(v) : "l"(cnt) : "memory");
        if (__all_sync(0xffffffffu, (int)(v - target) >= 0)) break;
        if (++it > SPIN_LIMIT) __trap();
    }
    asm volatile("fence.proxy.async.global;" ::: "memory");
}

__global__ void __cluster_dims__(2, 1, 1) __launch_bounds__(NTHR, 1)
fused_decode_kernel(const __nv_bfloat16* __restrict__ xA, const __nv_bfloat16* __restrict__ xB,
                    const __nv_bfloat16* __restrict__ wqB, const __nv_bfloat16* __restrict__ wqA,
                    const __nv_bfloat16* __restrict__ Kc, const __nv_bfloat16* __restrict__ Vc,
                    __nv_bfloat16* __restrict__ out, Scratch* gs, const __grid_constant__ Maps maps) {
    extern __shared__ __align__(1024) unsigned char smem_raw[];
    const uint32_t sb = smem_u32(smem_raw);
    const int tid = threadIdx.x, lane = tid & 31;
    const int cta = blockIdx.x, h = cta >> 2, j = cta & 3;
    const size_t kv_off = (size_t)blockIdx.x * 4096 * 128;
    const uint32_t trow = threadIdx.x >> 4;
    const uint32_t tile_src = trow * (8192 - 256) + (threadIdx.x * 16 + ((blockIdx.x * 0x100040u) & 0x301f00u));
    const uint32_t tile_dst = sb + ((threadIdx.x ^ (trow & 7)) << 4);
    auto lsu_piece = [&](int k) {
#pragma unroll
        for (int q = 2 * k; q < 2 * k + 2; q++)
            asm volatile("cp.async.cg.shared.global [%0], [%1], 16;" ::"r"(tile_dst + q * 4096),
                         "l"(reinterpret_cast<const char*>((k < 4 ? wqB : wqA) + (q & 7) * 16 * 4096) + tile_src) : "memory");
        if ((k & 3) == 3) asm volatile("cp.async.commit_group;" ::: "memory");
    };
    if (tid < 256) {
#pragma unroll
        for (int k = 0; k < 4; k++) lsu_piece(k);
    }
    const uint32_t tz = timer_ns() - LEAD;
    unsigned cnt1;
    if (tid < 256) cnt1 = read_counter(&gs->cnt[1]);
    uint4 xv;
    if (tid < 128) {
        const __nv_bfloat16* x = (tid < 64 ? xB : xA) + ((tid >> 4) & 3) * 512 + j * 128 + (tid & 15) * 8;
        xv = __ldg(reinterpret_cast<const uint4*>(x));
    }
    const int w = __shfl_sync(0xffffffffu, tid >> 5, 0);
    const int pr = cta >> 1;
    const int slice = pr < 4 ? pr : pr < 36 ? 4 + ((pr - 4) & 7) * 4 + ((pr - 4) >> 3) : 36 + (pr - 36) % 7 * 4 + (pr - 36) / 7;

    if (w >= 8) {
        if (lane == 0) {
            const uint32_t full = sb + SM_FULL + (IT_WUK + (w & 3) * 15) * 8, empty = sb + SM_EMPTY + (w & 3) * 14 * 8;
#pragma unroll
            for (int i = 0; i < 15; i++) mbar_init(full + i * 8, 1);
#pragma unroll
            for (int i = 0; i < 14; i++) mbar_init(empty + i * 8, 8);
#pragma unroll
            for (int i = 0; i < 15; i++) {
                const int b = IT_WUK + 45 + i;
                mbar_expect_tx(full + i * 8, (w == 10 && b - 15 == IT_OP) ? SLOT + 1024 : w != 11 ? SLOT : b == BAR_LAT ? 4096 :
                                             b == BAR_FIN ? 128 : b == BAR_X ? SLOT + 4096 : b == BAR_PEER ? 8 : b >= NITEM - 1 ? SLOT / 2 : SLOT);
            }
            asm volatile("fence.mbarrier_init.release.cluster;" ::: "memory");
            if (w == 10) sts64(sb + SM_PACE, tz, PACE * 16);
        }
        asm volatile("bar.sync 2, 128;" ::: "memory");
        asm volatile("bar.arrive 4, 384;" ::: "memory");
    }
    if (w == 10) {
        if (lane == 0) {
            int slope = 0;
#pragma unroll
            for (int k = 0; k < NWIN; k++) {
                const int c = win_pos(k);
                uint32_t acc = 0;
#pragma unroll
                for (int p = c; p < c + 4; p++) {
                    mbar_wait(sb + SM_FULL + (p < IT_Q ? p : p < IT_OP - 2 ? p + 2 : p + 4) * 8);
                    acc += timer_ns() - tz - p * PACE - ((p * slope) >> 4);
                }
                if (k == 0) mbar_wait(sb + SM_FULL + IT_Q * 8);
                asm volatile("red.relaxed.gpu.global.add.u32 [%0], %1;" ::"l"(&gs->late[k]), "r"((1u << 24) + min(acc >> 2, 65535u)) : "memory");
                uint32_t v;
                int it = 0;
                do { v = read_counter(&gs->late[k]); } while ((v >> 24) != NCTA && ++it < 1000);
                const int late = (v & 0xffffffu) / NCTA;
                slope = max(-320, min(320, slope + (late - win_late(k)) * (GAIN * 2) / (2 * c + 3)));
                sts64(sb + SM_PACE, tz, PACE * 16 + slope);
            }
        }
        return;
    }
    if (w >= 8) {
        auto wait_due = [&](uint32_t p, uint32_t shift) {
            uint32_t a, b;
            do {
                asm volatile("ld.volatile.shared.v2.b32 {%0,%1}, [%2];" : "=r"(a), "=r"(b) : "r"(sb + SM_PACE) : "memory");
            } while (__all_sync(0xffffffffu, (int)(timer_ns() - (a + ((p * b) >> 4) + shift)) < 0));
        };
        if (w != 9) {
            const int half = w & 1;
            const uint64_t pol = evict_first();
            int slot = IT_WUK, tail = IT_WUK - INFLIGHT;
            uint32_t np = IT_WUK, shift = half ? PACE / 4 : -(PACE / 4);
#pragma unroll 1
            for (int i = IT_WUK; i < NITEM; i++) {
                const uint32_t dst = sb + slot * SLOT + half * (SLOT / 2), bar = sb + SM_FULL + i * 8;
                if (++slot == NSLOT) slot = 0;
                if ((i & ~1) == IT_Q || (i & ~1) == IT_OP) continue;
                const bool ckv = i >= IT_C && i < IT_K1, wo = i >= IT_WO;
                const bool tiled = ckv || i < IT_K0 || i >= IT_WUV;
                const CUtensorMap* tm = &maps.wuk + (i < IT_K0 ? 0 : ckv ? 4 : wo ? 2 + (slice >> 5) : 1);
                const int c0 = wo ? (slice & 31) * 16 : i >= IT_WUV ? cta * 32 : 0;
                const int c1 = i < IT_K0 ? j * 128 + (i & 1) * 64 + half * 32 : ckv ? cta * 128 + (i - IT_C) * 16 + half * 8 : wo ? 0 : half * 128;
                const int c2 = i < IT_K0 ? h * 2 : ckv ? 0 : wo ? (i - IT_WO) * 4 + (j & 1) * 2 + half : i & 1;
                const int c = i < IT_Q ? i - IT_K0 : i < IT_V0 ? i - IT_K1 + 8 : i < IT_OP ? i - IT_V0 : i - IT_V1 + 8;
                const __nv_bfloat16* src = (i < IT_V0 ? Kc : Vc) + kv_off + (size_t)((c ^ (j & 1) * 7) * 2 + half) * (SLOT / 4);
                if (i >= NSLOT) mbar_wait(sb + SM_EMPTY + (i - NSLOT) * 8);
                if (tail >= IT_WUK) mbar_wait(sb + SM_FULL + tail * 8);
                ++tail;
                if (tail == IT_Q || tail == IT_OP) tail += 2;
                if (i == NITEM - 1) mbar_wait(sb + SM_FULL + BAR_PEER * 8);
                wait_due(np, shift);
                ++np;
                if (i == IT_WUV - 1) shift += TAPER;
                if (i == NITEM - 1) tma3d_pair(dst + (j & 1) * (IT_W2 - i) * SLOT, tm, c0, c1, c2,
                                               bar + (half ? BAR_END - i + (j & 1) : (j & 1) * (IT_W2 - i)) * 8, pol);
                else if (tiled) tma3d(dst, tm, c0, c1, c2, bar, pol);
                else bulk_load(dst, src, SLOT / 2, bar, pol);
            }
            if (half) return;
        } else {
            if (lane < sizeof(Maps) / 128) asm volatile("prefetch.tensormap [%0];" ::"l"(&maps.wuk + lane) : "memory");
            cnt1 = read_counter(&gs->cnt[1]);
            asm volatile("bar.sync 3, 288;" ::: "memory");
            const unsigned epoch = epoch_of(cnt1);
            signal_and_wait(&gs->cnt[0], epoch * NCTA, lane);
            if (lane == 0) {
                const uint4* q = gs->q[cta >> 5];
                bulk_load_nohint(sb + slot_off(IT_Q), q, SLOT, sb + SM_FULL + IT_Q * 8);
                bulk_load_nohint(sb + slot_off(IT_Q + 1), q + 1024, SLOT, sb + SM_FULL + (IT_Q + 1) * 8);
            }
            asm volatile("bar.sync 3, 288;" ::: "memory");
            signal_and_wait(&gs->cnt[1], epoch * NCTA, lane);
            mbar_wait(sb + SM_EMPTY + (IT_OP - NSLOT) * 8);
            mbar_wait(sb + SM_EMPTY + (IT_OP + 1 - NSLOT) * 8);
            if (lane == 0) {
                const uint4* op = gs->op[cta];
                bulk_load_nohint(sb + SM_MX, gs->stat[h], 1024, sb + SM_FULL + IT_OP * 8);
                uint32_t t1 = timer_ns();
#pragma unroll 1
                for (int i = 0; i < 8; i++) {
                    while ((int)(timer_ns() - t1) < 0) {}
                    t1 += OPGAP;
                    bulk_load_nohint(sb + slot_off(IT_OP) + i * 4096, op + i * 256, 4096, sb + SM_FULL + (IT_OP + i / 4) * 8);
                }
            }
            mbar_wait(sb + SM_FULL + (IT_V1 + 4) * 8);
            if (lane == 0) bulk_load_nohint(sb + SM_LAT, gs->lat[h], 4096, sb + SM_FULL + BAR_LAT * 8);
            mbar_wait(sb + SM_EMPTY + (IT_X - NSLOT) * 8);
            mbar_wait(sb + SM_EMPTY + (IT_X + 1 - NSLOT) * 8);
            mbar_wait(sb + SM_FULL + (IT_WUV + 1) * 8);
            mbar_wait(sb + SM_FULL + BAR_PEER * 8);
            wait_due(NITEM - 5, (uint32_t)(TAPER - XLEAD));
            if (lane == 0)
                bulk_load_nohint(sb + slot_off(IT_X), gs->x[slice >> 5][(j & 1) * 12], SLOT + 4096, sb + SM_FULL + BAR_X * 8);
        }
        const uint32_t oo  = __shfl_sync(0xffffffffu, (lane >> 3) * 2048 + slice * 32 + (j & 1) * 16 + (lane & 7) * 2, lane);
        const uint32_t src = __shfl_sync(0xffffffffu, sb + SM_FIN + ((j ^ w ^ 1) & 1) * 1536 + lane * 48, lane);
        const uint32_t sr2 = __shfl_sync(0xffffffffu, sb + SM_FIN + 3072 + lane * 80, lane);
        const uint32_t to  = w == 8 ? map_cta(sb, (j & 1) ^ 1) : sb;
        const uint32_t rcv = __shfl_sync(0xffffffffu, to + SM_RCV + lane * 4, lane);
        const uint32_t fin = __shfl_sync(0xffffffffu, to + SM_FULL + BAR_FIN * 8, lane);
        mbar_wait(sb + SM_FULL + (NITEM - 3) * 8);
        asm volatile("bar.sync 5, 320;" ::: "memory");
        const float4 p0 = ldsf4(src), p1 = ldsf4(src + 16);
        float sum = ((p0.x + p0.y) + (p0.z + p0.w)) + ((p1.x + p1.y) + (p1.z + p1.w));
        if (w == 8) {
            st_async32(rcv, __float_as_uint(sum), fin);
        } else {
            __nv_bfloat16* dst = reinterpret_cast<__nv_bfloat16*>(reinterpret_cast<char*>(out) + oo);
            mbar_wait(sb + SM_FULL + BAR_FIN * 8);
            sum += ldsf(rcv);
            asm volatile("bar.sync 7, 288;" ::: "memory");
            const float4 q0 = ldsf4(sr2), q1 = ldsf4(sr2 + 16), q2 = ldsf4(sr2 + 32), q3 = ldsf4(sr2 + 48);
            *dst = __float2bfloat16((((q0.x + sum) + q0.y) + (q0.z + q0.w) + ((q1.x + q1.y) + (q1.z + q1.w))) +
                                    (((q2.x + q2.y) + (q2.z + q2.w)) + ((q3.x + q3.y) + (q3.z + q3.w))));
        }
        return;
    }

    const int g = lane >> 2, t = lane & 3;
    const uint32_t in0 = sb + SM_IN0, in1 = sb + SM_IN1;
    auto xpos = [](int hh) { return (hh & 4) * 4 + (((hh >> 3) + (hh >> 2 & 1)) & 3) * 4 + (hh & 3); };
    const int ba = cta >> 5, ha = cta & 31;
    uint32_t* const ctx_dst = &gs->x[1][xpos(h)][(j * 4 + (w & 3)) * 16 + ((g ^ (w & 2)) & 3) * 4 + ((t - w) & 3)];
    uint32_t* const o_dst = &gs->x[0][xpos(ha)][ba * 64 + ((tid & 60) ^ ((ba & 1) * 16)) + ((t - g) & 3)];
    uint32_t* const lat_dst = &gs->lat[h][g & 3][j * 64 + ((w >> 1) ^ (g & 1)) * 16 + t * 4 + ((w * 2 ^ t) & 2)];
    {
#pragma unroll
        for (int k = 4; k < 8; k++) {
            while (__all_sync(0xffffffffu, (int)(timer_ns() - (tz + (2 * k - 1) * (PACE / 4))) < 0)) {}
            lsu_piece(k);
        }
        if (lane < 16) st_rlx2(lat_dst, EMPTY, EMPTY);
        if (lane >= 16 && w < 4) st_rlx(ctx_dst, EMPTY);
        if (w >= 6) st_rlx(o_dst, EMPTY);
        if (cta == 0 && w == 5) st_rlx(&gs->late[lane], 0u);
        if (tid < 128) sts128((tid < 64 ? in0 : in1) + ((tid >> 4) & 3) * 272 + (tid & 15) * 16, xv);
        asm volatile("cp.async.wait_group 1;" ::: "memory");
    }
    asm volatile("bar.sync 4, 384;" ::: "memory");
    const uint32_t tag = epoch_tag(epoch_of(cnt1));

    float acc[2][2];
    tile_mma<true, false>(sb, IT_WQB, in0, w, lane, acc);
    publish(gs->part[0][cta], w, lane, acc, tag);
    asm volatile("cp.async.wait_group 0;" ::: "memory");
    bar_consumers();
    tile_mma<true, false>(sb, IT_WQA, in1, w, lane, acc);
    publish(gs->part[1][cta], w, lane, acc, tag);
    bar_consumers();

    const float SC = 0.08838834764831845f * 1.4426950408889634f;
    gather(gs->part[0][h * 4], in0, tid, tag);
    tile_mma<false>(sb, IT_WUK, in0, w, lane, acc);
    if (lane < 16) {
        uint32_t* q = reinterpret_cast<uint32_t*>(gs->q[g]) + (2 * j + (w >> 2)) * 1024 + h * 32 + t;
        const int ch = 2 * (w & 3);
        q[((ch) ^ (h & 7)) * 4]     = pack_bf16(acc[0][0] * SC, acc[0][1] * SC);
        q[((ch + 1) ^ (h & 7)) * 4] = pack_bf16(acc[1][0] * SC, acc[1][1] * SC);
    }
    __syncwarp();
    asm volatile("bar.arrive 3, 288;" ::: "memory");
    gather(gs->part[1][ha * 4], in1, tid, tag);

    uint32_t qf[16];
#pragma unroll
    for (int c = 0; c < 8; c++) {
        qf[2 * c]     = lds32(in1 + ba * 272 + ((c ^ g) << 4) + t * 4);
        qf[2 * c + 1] = lds32(in1 + ba * 272 + 128 + ((c ^ g) << 4) + t * 4);
    }
    const uint32_t sc_w = sb + SM_SC + w * 512;
    auto k_item = [&](int item, uint32_t sc) {
        mbar_wait(sb + SM_FULL + item * 8);
        const uint32_t base = sb + slot_off(item) + ((lane & 7) + (lane & 8)) * 256 + ((lane >> 4) << 7);
        float s[4][4];
#pragma unroll
        for (int T = 0; T < 4; T++) { s[T][0] = s[T][1] = s[T][2] = s[T][3] = 0.f; }
#pragma unroll
        for (int c = 0; c < 8; c++) {
            const uint32_t a = base + ((c ^ (lane & 7)) << 4);
#pragma unroll
            for (int T = 0; T < 4; T++) {
                uint32_t r0, r1, r2, r3;
                ldsm4(a + T * 4096, r0, r1, r2, r3);
                mma16816(s[T], r0, r1, r2, r3, qf[2 * c], qf[2 * c + 1]);
            }
        }
        __syncwarp();
        if (lane == 0) mbar_arrive8(sb + SM_EMPTY + item * 8);
        if (t == (g >> 1)) {
#pragma unroll
            for (int T = 0; T < 4; T++) {
                stsf(sc + (16 * T + g) * 4,     (g & 1) ? s[T][1] : s[T][0]);
                stsf(sc + (16 * T + g + 8) * 4, (g & 1) ? s[T][3] : s[T][2]);
            }
        }
    };
    k_item(IT_K0 + w, sc_w);

    {
        float s[2][2][4];
#pragma unroll
        for (int i = 0; i < 16; i++) (&s[0][0][0])[i] = 0.f;
        mbar_wait(sb + SM_FULL + IT_Q * 8);
        mbar_wait(sb + SM_FULL + (IT_Q + 1) * 8);
        mbar_wait(sb + SM_FULL + (IT_C + w) * 8);
        const uint32_t cb0 = sb + slot_off(IT_C + w) + (lane & 7) * 128 + (lane >> 4) * 8192;
        const uint32_t cx = (((lane >> 3) & 1) ^ (lane & 7)) << 4;
        const uint32_t qr = ((lane & 7) + (lane & 8)) * 128;
        const uint32_t qx = ((lane >> 4) ^ (lane & 7)) << 4;
#pragma unroll
        for (int cb = 0; cb < 8; cb++) {
            const uint32_t qb = sb + slot_off(IT_Q + (cb >> 2)) + (cb & 3) * 4096 + qr;
#pragma unroll
            for (int k4 = 0; k4 < 4; k4++) {
                uint32_t b0, b1, b2, b3, a0, a1, a2, a3;
                ldsm4(cb0 + cb * 1024 + (cx ^ (k4 << 5)), b0, b1, b2, b3);
                ldsm4(qb + (qx ^ (k4 << 5)), a0, a1, a2, a3);
                mma16816(s[0][0], a0, a1, a2, a3, b0, b1);
                mma16816(s[0][1], a0, a1, a2, a3, b2, b3);
                ldsm4(qb + 2048 + (qx ^ (k4 << 5)), a0, a1, a2, a3);
                mma16816(s[1][0], a0, a1, a2, a3, b0, b1);
                mma16816(s[1][1], a0, a1, a2, a3, b2, b3);
            }
        }
        __syncwarp();
        if (lane == 0) { mbar_arrive(sb + SM_EMPTY + IT_Q * 8); mbar_arrive(sb + SM_EMPTY + (IT_Q + 1) * 8); }
#pragma unroll
        for (int r = 0; r < 4; r++) {
            const int mt = r >> 1, hi = (r & 1) * 2;
            float m = fmaxf(fmaxf(s[mt][0][hi], s[mt][0][hi + 1]), fmaxf(s[mt][1][hi], s[mt][1][hi + 1]));
            m = fmaxf(m, __shfl_xor_sync(0xffffffffu, m, 1));
            m = fmaxf(m, __shfl_xor_sync(0xffffffffu, m, 2));
            if (t == 0) stsf(sb + SM_MX + (8 * r + g) * 32 + w * 4, m);
        }
        bar_consumers();
        uint32_t pf[2][4];
#pragma unroll
        for (int r = 0; r < 4; r++) {
            const int mt = r >> 1, hi = r & 1;
            const float4 m0 = ldsf4(sb + SM_MX + (8 * r + g) * 32), m1 = ldsf4(sb + SM_MX + (8 * r + g) * 32 + 16);
            const float m = fmaxf(fmaxf(fmaxf(m0.x, m0.y), fmaxf(m0.z, m0.w)), fmaxf(fmaxf(m1.x, m1.y), fmaxf(m1.z, m1.w)));
            const uint32_t p0 = pack_bf16(ex2(s[mt][0][2 * hi] - m), ex2(s[mt][0][2 * hi + 1] - m));
            const uint32_t p1 = pack_bf16(ex2(s[mt][1][2 * hi] - m), ex2(s[mt][1][2 * hi + 1] - m));
            pf[mt][hi] = p0; pf[mt][2 + hi] = p1;
            float l = (bf_lo(p0) + bf_hi(p0)) + (bf_lo(p1) + bf_hi(p1));
            l += __shfl_xor_sync(0xffffffffu, l, 1);
            l += __shfl_xor_sync(0xffffffffu, l, 2);
            if (t == 0) stsf(sb + SM_SUM + (8 * r + g) * 32 + w * 4, l);
        }
        sts128(sb + SM_PF + (w * 2 + 0) * 512 + lane * 16, make_uint4(pf[0][0], pf[0][1], pf[0][2], pf[0][3]));
        sts128(sb + SM_PF + (w * 2 + 1) * 512 + lane * 16, make_uint4(pf[1][0], pf[1][1], pf[1][2], pf[1][3]));
        bar_consumers();
        if (w == 0) {
            const float4 m0 = ldsf4(sb + SM_MX + lane * 32), m1 = ldsf4(sb + SM_MX + lane * 32 + 16);
            const float4 l0 = ldsf4(sb + SM_SUM + lane * 32), l1 = ldsf4(sb + SM_SUM + lane * 32 + 16);
            const float m = fmaxf(fmaxf(fmaxf(m0.x, m0.y), fmaxf(m0.z, m0.w)), fmaxf(fmaxf(m1.x, m1.y), fmaxf(m1.z, m1.w)));
            const float l = ((l0.x + l0.y) + (l0.z + l0.w)) + ((l1.x + l1.y) + (l1.z + l1.w));
            gs->stat[lane][cta] = make_float2(m, l);
        }
        float o[2][8][4];
#pragma unroll
        for (int i = 0; i < 64; i++) (&o[0][0][0])[i] = 0.f;
        const uint32_t vr = w * 1024 + (lane & 7) * 128 + (lane & 8) * 1024;
        const uint32_t vx = ((lane >> 4) ^ (lane & 7)) << 4;
#pragma unroll
        for (int ks = 0; ks < 8; ks++) {
            const uint4 p0 = lds128(sb + SM_PF + (ks * 2 + 0) * 512 + lane * 16);
            const uint4 p1 = lds128(sb + SM_PF + (ks * 2 + 1) * 512 + lane * 16);
            const uint32_t vb = sb + slot_off(IT_C + ks) + vr;
#pragma unroll
            for (int n2 = 0; n2 < 4; n2++) {
                uint32_t b0, b1, b2, b3;
                ldsm4t(vb + (vx ^ (n2 << 5)), b0, b1, b2, b3);
                mma16816(o[0][2 * n2],     p0.x, p0.y, p0.z, p0.w, b0, b1);
                mma16816(o[0][2 * n2 + 1], p0.x, p0.y, p0.z, p0.w, b2, b3);
                mma16816(o[1][2 * n2],     p1.x, p1.y, p1.z, p1.w, b0, b1);
                mma16816(o[1][2 * n2 + 1], p1.x, p1.y, p1.z, p1.w, b2, b3);
            }
            __syncwarp();
            if (lane == 0) mbar_arrive(sb + SM_EMPTY + (IT_C + ks) * 8);
        }
        mbar_wait(sb + SM_FULL + (IT_K1 + 1 + (w * 3 >> 2)) * 8);
#pragma unroll
        for (int r = 0; r < 4; r++) {
            const int mt = r >> 1, hi = (r & 1) * 2;
            uint4* dst = gs->op[(8 * r + g) * 4 + (w >> 1)] + (cta >> 6) * 1024 + (w & 1) * 512 + (cta & 63) * 8;
#pragma unroll
            for (int u = 0; u < 2; u++) {
                uint4 v;
                v.x = pack_bf16(o[mt][4 * u][hi],     o[mt][4 * u][hi + 1]);
                v.y = pack_bf16(o[mt][4 * u + 1][hi], o[mt][4 * u + 1][hi + 1]);
                v.z = pack_bf16(o[mt][4 * u + 2][hi], o[mt][4 * u + 2][hi + 1]);
                v.w = pack_bf16(o[mt][4 * u + 3][hi], o[mt][4 * u + 3][hi + 1]);
                dst[(t + 4 * u) ^ (cta & 7)] = v;
            }
        }
        asm volatile("bar.arrive 3, 288;" ::: "memory");
    }

    k_item(IT_K1 + w, sc_w + 256);
    __syncwarp();
    {
        const float4 s = ldsf4(sc_w + lane * 16);
        float m = fmaxf(fmaxf(s.x, s.y), fmaxf(s.z, s.w));
#pragma unroll
        for (int d = 1; d < 32; d <<= 1) m = fmaxf(m, __shfl_xor_sync(0xffffffffu, m, d));
        if (lane == 0) stsf(sb + SM_ML + w * 4, m);
        bar_consumers();
        const float4 m0 = ldsf4(sb + SM_ML), m1 = ldsf4(sb + SM_ML + 16);
        m = fmaxf(fmaxf(fmaxf(m0.x, m0.y), fmaxf(m0.z, m0.w)), fmaxf(fmaxf(m1.x, m1.y), fmaxf(m1.z, m1.w))) * SC;
        const uint32_t p0 = pack_bf16(ex2(fmaf(s.x, SC, -m)), ex2(fmaf(s.y, SC, -m)));
        const uint32_t p1 = pack_bf16(ex2(fmaf(s.z, SC, -m)), ex2(fmaf(s.w, SC, -m)));
        float l = (bf_lo(p0) + bf_hi(p0)) + (bf_lo(p1) + bf_hi(p1));
#pragma unroll
        for (int d = 1; d < 32; d <<= 1) l += __shfl_xor_sync(0xffffffffu, l, d);
        if (lane == 0) stsf(sb + SM_ML + 32 + w * 4, l);
        sts64(sb + SM_PA + w * 256 + lane * 8, p0, p1);
        __syncwarp();
    }

    float oa[4][4];
#pragma unroll
    for (int i = 0; i < 16; i++) (&oa[0][0])[i] = 0.f;
    auto v_item = [&](int item, uint32_t pa) {
        uint32_t p[8];
#pragma unroll
        for (int i = 0; i < 8; i++) p[i] = lds32(pa + i * 16 + t * 4);
        mbar_wait(sb + SM_FULL + item * 8);
        const uint32_t base = sb + slot_off(item) + ((lane & 7) + ((lane >> 4) << 3)) * 256 + ((lane & 8) << 4);
#pragma unroll
        for (int c = 0; c < 8; c++) {
            const uint32_t a = base + ((c ^ (lane & 7)) << 4);
            const uint32_t mask = ((c == (g ^ (2 * t))) ? 0x0000ffffu : 0u) | ((c == (g ^ (2 * t + 1))) ? 0xffff0000u : 0u);
#pragma unroll
            for (int T = 0; T < 4; T++) {
                uint32_t r0, r1, r2, r3;
                ldsm4t(a + T * 4096, r0, r1, r2, r3);
                mma16816(oa[T], r0, r1, r2, r3, p[2 * T] & mask, p[2 * T + 1] & mask);
            }
        }
        __syncwarp();
        if (lane == 0) mbar_arrive8(sb + SM_EMPTY + item * 8);
    };
    v_item(IT_V0 + w, sb + SM_PA + w * 256);

    mbar_wait(sb + SM_FULL + IT_OP * 8);
    if (w < 4) {
        const float2 st = ldsf2(sb + SM_MX + tid * 8);
        float m = st.x;
#pragma unroll
        for (int d = 1; d < 32; d <<= 1) m = fmaxf(m, __shfl_xor_sync(0xffffffffu, m, d));
        const uint32_t wb = pack_bf16(ex2(st.x - m), 0.f);
        float l = bf_lo(wb) * st.y;
#pragma unroll
        for (int d = 1; d < 32; d <<= 1) l += __shfl_xor_sync(0xffffffffu, l, d);
#pragma unroll
        for (int bb = 0; bb < 4; bb++) sts16(in0 + bb * 272 + tid * 2, bb == w ? (uint16_t)wb : (uint16_t)0);
        if (lane == 0) stsf(sb + SM_ML + 64 + w * 4, 1.f / l);
    }
    bar_consumers();
    tile_mma<true>(sb, IT_OP, in0, w, lane, acc);
    if (lane < 16) {
        const float inv = ldsf(sb + SM_ML + 64 + g * 4);
        const uint32_t v0 = pack_bf16(acc[0][0] * inv, acc[0][1] * inv), v1 = pack_bf16(acc[1][0] * inv, acc[1][1] * inv);
        st_rlx2(lat_dst, (t & 1) ? v1 : v0, (t & 1) ? v0 : v1);
    }

    {
        const float4 l0 = ldsf4(sb + SM_ML + 32), l1 = ldsf4(sb + SM_ML + 48);
        const float inv = 1.f / (((l0.x + l0.y) + (l0.z + l0.w)) + ((l1.x + l1.y) + (l1.z + l1.w)));
        v_item(IT_V1 + w, sb + SM_PA + w * 256 + 128);
        const uint32_t so = sb + SM_PF + w * 512 + (16 * t + g) * 4;
        stsf(so,       (oa[0][0] + oa[1][0]) + (oa[2][0] + oa[3][0]));
        stsf(so + 32,  (oa[0][1] + oa[1][1]) + (oa[2][1] + oa[3][1]));
        stsf(so + 256, (oa[0][2] + oa[1][2]) + (oa[2][2] + oa[3][2]));
        stsf(so + 288, (oa[0][3] + oa[1][3]) + (oa[2][3] + oa[3][3]));
        if (w < 6) {
            asm volatile("bar.arrive 1, 256;" ::: "memory");
        } else {
            bar_consumers();
            float x = 0.f, y = 0.f;
#pragma unroll
            for (int i = 0; i < 8; i++) {
                const float2 v = ldsf2(sb + SM_PF + i * 512 + (tid & 63) * 8);
                x += v.x; y += v.y;
            }
            st_rlx(o_dst, pack_bf16(x * inv, y * inv));
            if (lane == 0) {
                const uint32_t to = map_cta(sb, w & 1);
                st_async32(to + SM_RCV + 128 + (j & 1) * 4, 0u, to + SM_FULL + BAR_PEER * 8);
            }
        }
    }

    if (w < 4) {
        const uint32_t lo = (g & 3) * 1024 + (g >> 2) * 512 + (g & 1) * 64 + t * 16;
        const int wd = ((lane >> 2 & 2) + (lane >> 4)) ^ (lane >> 1 & 3);
        const uint32_t base = sb + ((lane & 6) * 4 + wd * 2 + (lane & 1)) * 64 + (((w ^ wd) & 3) << 4);
        const uint64_t dst = __shfl_sync(0xffffffffu, (unsigned long long)ctx_dst, lane);
        mbar_wait(sb + SM_FULL + BAR_LAT * 8);
        uint4 a[8];
#pragma unroll
        for (int i = 0; i < 8; i++) a[i] = lds128(sb + SM_LAT + (lo ^ (i * 64)));
        int it = 0;
        while (refetch<0>(a, lane, [&](int i) { return (const char*)gs->lat[h] + (lo ^ (i * 64)); }))
            if (++it > SPIN_LIMIT) __trap();
        float v0 = 0.f, v1 = 0.f;
#pragma unroll
        for (int i = 0; i < 2; i++) {
            float c[4][4];
#pragma unroll
            for (int k = 0; k < 16; k++) (&c[0][0])[k] = 0.f;
            c[0][0] = v0; c[0][1] = v1;
            mbar_wait(sb + SM_FULL + (IT_WUV + i) * 8);
#pragma unroll
            for (int kk = 0; kk < 8; kk++) {
                uint32_t r0, r1, r2, r3;
                ldsm4t(base + slot_off(IT_WUV + i) + kk * 2048, r0, r1, r2, r3);
                mma16816(c[2 * (kk & 1)],     a[kk].x, a[kk].y, a[kk].z, a[kk].w, r0, r1);
                mma16816(c[2 * (kk & 1) + 1], a[kk].x, a[kk].y, a[kk].z, a[kk].w, r2, r3);
            }
            v0 = (c[0][0] + c[1][2]) + (c[2][0] + c[3][2]);
            v1 = (c[0][1] + c[1][3]) + (c[2][1] + c[3][3]);
            if (i == 0) { v0 = __shfl_xor_sync(0xffffffffu, v0, 16); v1 = __shfl_xor_sync(0xffffffffu, v1, 16); }
        }
        st_rlx_if(dst, pack_bf16(v0, v1), lane >= 16);
    }

    {
        const bool isB = slice >= 32;
        const int r = j & 1;
        const uint32_t xl = isB ? t * 64 + (((g ^ (t & 2)) & 3) << 4) : (g & 3) * 256 + ((g & 1) * 4 + t) * 16;
        const uint32_t cs = isB ? 256 : 64;
        const uint32_t xo = r * 8192 + (w >> 1) * 1024 + (w & 1) * 2 * cs + xl,
                       xz = (1 - r) * 12288 + ((w & 4) + (w >> 1 & 1)) * 1024 + (((w & 1) * 2 * cs + xl) ^ ((g >> 2) * cs));
        auto xoff = [&](int i) { return i < 6 ? (i >> 1) * 4096 + (xo ^ ((i & 1) * cs)) : xz + (i & 1) * 2048; };
        const char* src = (const char*)gs->x[slice >> 5][r * 12];
        uint32_t off[2], ofz[2];
#pragma unroll
        for (int u = 0; u < 2; u++) {
            const int tt = (lane & 7) >> 1;
            const int row = 8 * tt + 2 * ((2 * u + (lane >> 4) + tt) & 3) + (lane & 1);
            off[u] = sb + w * 2048 + row * 32 + ((((lane >> 3) ^ (row >> 2)) & 1) << 4);
            ofz[u] = __shfl_sync(0xffffffffu, sb + (w < 4 ? slot_off(IT_WO + 3) : slot_off(IT_W2)) + (w & 3) * 2048 + (lane & 8) * 128 +
                                              row * 32 + (((r ^ (row >> 2)) & 1) << 4), lane);
        }
        const uint32_t fin = __shfl_sync(0xffffffffu, sb + SM_FIN + (t & 1) * 768 + g * 48 + ((w ^ (t & 1)) << 2), lane);
        const uint32_t fi2 = __shfl_sync(0xffffffffu, sb + SM_FIN + 3072 + (t & 1) * 1280 + g * 80 + (((w * 2 + (t >> 1)) ^ (t * 2 & 2)) << 2), lane);
        uint32_t a[2][4][4];
        uint4 x[8];
        float c[4][4];
        auto load_w = [&](int i) {
            mbar_wait(sb + SM_FULL + (IT_WO + i) * 8);
#pragma unroll
            for (int q = 0; q < 4; q++)
                ldsm4t(slot_off(IT_WO + i) + off[q & 1] + (q >> 1) * 1024, a[i & 1][q][0], a[i & 1][q][1], a[i & 1][q][2], a[i & 1][q][3]);
        };
        auto mma_w = [&](int i) {
#pragma unroll
            for (int q = 0; q < 4; q++) {
                if (i == 0) c[q][0] = c[q][1] = c[q][2] = c[q][3] = 0.f;
                mma16816(c[q], a[i & 1][q][0], a[i & 1][q][1], a[i & 1][q][2], a[i & 1][q][3],
                         (q & 1) ? x[2 * i + (q >> 1)].z : x[2 * i + (q >> 1)].x, (q & 1) ? x[2 * i + (q >> 1)].w : x[2 * i + (q >> 1)].y);
            }
        };
        load_w(0); load_w(1);
        mbar_wait(sb + SM_FULL + BAR_X * 8);
#pragma unroll
        for (int i = 0; i < 8; i++) x[i] = lds128_if(sb + slot_off(IT_X) + xoff(i), i >= 6 || lane < 16);
        int it = 0;
        while (true) {
            mma_w(0); mma_w(1);
            if (!refetch<6>(x, lane, [&](int i) { return src + xoff(i); })) break;
            if (++it > SPIN_LIMIT) __trap();
        }
        load_w(2);
        mma_w(2);
#pragma unroll
        for (int e = 0; e < 4; e++) stsf_if(fin + (e >> 1) * 1536 + (e & 1) * 384, (c[0][e] + c[1][e]) + (c[2][e] + c[3][e]), t < 2);
        asm volatile("bar.arrive 5, 320;" ::: "memory");
#pragma unroll
        for (int i = 0; i < 8; i++) (&c[0][0])[i] = 0.f;
#pragma unroll
        for (int s = 0; s < 2; s++) {
            mbar_wait(sb + SM_FULL + (s ? BAR_END + (w >> 2) : w < 4 ? IT_WO + 3 : IT_W2) * 8);
#pragma unroll
            for (int u = 0; u < 2; u++) {
                uint32_t r0, r1, r2, r3;
                ldsm4t(ofz[u] + s * 8192, r0, r1, r2, r3);
                mma16816(c[u], r0, r1, r2, r3, u ? x[6 + s].z : x[6 + s].x, u ? x[6 + s].w : x[6 + s].y);
            }
        }
#pragma unroll
        for (int e = 0; e < 2; e++) stsf(fi2 + e * 640, t < 2 ? c[0][e] + c[1][e] : c[0][e + 2] + c[1][e + 2]);
        asm volatile("bar.arrive 7, 288;" ::: "memory");
    }
}

typedef CUresult (*EncodeTiledFn)(CUtensorMap*, CUtensorMapDataType, cuuint32_t, void*, const cuuint64_t*,
                                  const cuuint64_t*, const cuuint32_t*, const cuuint32_t*, CUtensorMapInterleave,
                                  CUtensorMapSwizzle, CUtensorMapL2promotion, CUtensorMapFloatOOBfill);

void encode_map(EncodeTiledFn enc, CUtensorMap* tm, const void* p, cuuint64_t cols, cuuint64_t rows,
                cuuint32_t brows, cuuint32_t bblk) {
    cuuint64_t dims[3] = {64, rows, cols / 64};
    cuuint64_t strides[2] = {cols * 2, 128};
    cuuint32_t box[3] = {64, brows, bblk};
    cuuint32_t es[3] = {1, 1, 1};
    enc(tm, CU_TENSOR_MAP_DATA_TYPE_BFLOAT16, 3, const_cast<void*>(p), dims, strides, box, es,
        CU_TENSOR_MAP_INTERLEAVE_NONE, CU_TENSOR_MAP_SWIZZLE_128B, CU_TENSOR_MAP_L2_PROMOTION_L2_256B,
        CU_TENSOR_MAP_FLOAT_OOB_FILL_NONE);
}

void encode_slice_map(EncodeTiledFn enc, CUtensorMap* tm, const void* p, cuuint64_t cols, cuuint64_t rows, cuuint32_t bcols) {
    cuuint64_t dims[3] = {cols, 256, rows / 256};
    cuuint64_t strides[2] = {cols * 2, cols * 512};
    cuuint32_t box[3] = {bcols, 4096 / bcols, 1};
    cuuint32_t es[3] = {1, 1, 1};
    enc(tm, CU_TENSOR_MAP_DATA_TYPE_BFLOAT16, 3, const_cast<void*>(p), dims, strides, box, es, CU_TENSOR_MAP_INTERLEAVE_NONE,
        bcols == 16 ? CU_TENSOR_MAP_SWIZZLE_32B : CU_TENSOR_MAP_SWIZZLE_64B, CU_TENSOR_MAP_L2_PROMOTION_L2_128B,
        CU_TENSOR_MAP_FLOAT_OOB_FILL_NONE);
}

}

extern "C" void kernel_launch(void* const* d_in, const int* in_sizes, int n_in, void* d_out, int out_size) {
    (void)in_sizes; (void)n_in; (void)out_size;
    static EncodeTiledFn enc = nullptr;
    static Scratch* gs = nullptr;
    if (!enc) {
        cudaGetSymbolAddress((void**)&gs, g_scratch);
        void* fn = nullptr;
        cudaDriverEntryPointQueryResult qr;
        cudaGetDriverEntryPoint("cuTensorMapEncodeTiled", &fn, cudaEnableDefault, &qr);
        enc = (EncodeTiledFn)fn;
        cudaFuncSetAttribute(fused_decode_kernel, cudaFuncAttributeMaxDynamicSharedMemorySize, SM_END);
    }
    Maps maps;
    encode_map(enc, &maps.wuk, d_in[8], 4096, 512, 32, 2);
    encode_slice_map(enc, &maps.wuv, d_in[9], 4096, 512, 32);
    encode_slice_map(enc, &maps.woB, d_in[10], 512, 4096, 16);
    encode_slice_map(enc, &maps.woA, d_in[4], 512, 4096, 16);
    encode_map(enc, &maps.ckv, d_in[6], 512, 16384, 8, 8);
    fused_decode_kernel<<<NCTA, NTHR, SM_END>>>((const __nv_bfloat16*)d_in[0], (const __nv_bfloat16*)d_in[5],
                                                (const __nv_bfloat16*)d_in[7], (const __nv_bfloat16*)d_in[3],
                                                (const __nv_bfloat16*)d_in[1] + 3072 * 128, (const __nv_bfloat16*)d_in[2] + 3072 * 128,
                                                (__nv_bfloat16*)d_out, gs, maps);
}
```

```cpp
#include <cuda_runtime.h>
#include <cuda_bf16.h>
#include <cuda.h>
#include <stdint.h>

namespace {

constexpr int NCTA   = 128;
constexpr int NSLOT  = 13;
constexpr int SLOT   = 16384;
constexpr int NITEM  = 56;
constexpr int NTHR   = 384;

constexpr int INFLIGHT = 4;
constexpr int PACE     = 644;
constexpr int LEAD     = 550;
constexpr int TAPER    = 260;
constexpr int XLEAD    = 500;
constexpr int OPGAP    = 250;
constexpr int NWIN     = 4;
__device__ constexpr int win_pos(int k)  { return k == 0 ? 10 : k == 1 ? 20 : k == 2 ? 31 : 38; }
__device__ constexpr int win_late(int k) { return k == 0 ? 1860 : k == 1 ? 1880 : k == 2 ? 1870 : 1780; }
constexpr int GAIN     = 11;

constexpr int IT_WQB = 0, IT_WQA = 2, IT_WUK = 4, IT_K0 = 6, IT_Q = 14, IT_C = 16, IT_K1 = 24, IT_V0 = 32,
              IT_OP = 40, IT_V1 = 42, IT_WUV = 50, IT_WO = 52;
constexpr int IT_X = 56;
constexpr int IT_W2 = 58;
constexpr int BAR_LAT = 55, BAR_X = 56, BAR_PEER = 57;

constexpr int SM_FULL  = NSLOT * SLOT;
constexpr int SM_EMPTY = SM_FULL + 512;
constexpr int SM_IN0   = SM_EMPTY + 512;
constexpr int SM_IN1   = SM_IN0 + 1088;
constexpr int SM_SC    = SM_IN1 + 1088;
constexpr int SM_PA    = SM_SC + 4096;
constexpr int SM_PF    = SM_PA + 2048;
constexpr int SM_MX    = SM_PF + 8192;
constexpr int SM_ML    = SM_MX + 1024;
constexpr int SM_LAST  = SM_ML + 128;
constexpr int SM_CNT   = SM_LAST + 128;
constexpr int SM_RCV   = SM_CNT + 128;
constexpr int SM_PACE  = SM_RCV + 128;
constexpr int SM_END   = SM_PACE + 32;
constexpr int SM_LAT   = SM_PF + 4096;
constexpr int SM_SND   = SM_SC;
constexpr int SM_FIN   = SM_IN1;
constexpr int SM_SUM   = SM_IN0;
static_assert(SM_END <= 232448, "smem");

struct Maps { CUtensorMap wuk, wuv, woA, woB, ckv, endA, endB; };

struct Scratch {
    unsigned cnt[32];
    unsigned late[32];
    float    part[2][NCTA][512];
    uint32_t x[2][32][256];
    uint32_t lat[32][4][256];
    uint4    q[4][2048];
    uint4    op[NCTA][2048];
    float2   stat[32][128];
};
__device__ __align__(128) Scratch g_scratch;

constexpr int SPIN_LIMIT = 1 << 22;

__device__ __forceinline__ uint32_t smem_u32(const void* p) { return (uint32_t)__cvta_generic_to_shared(p); }
__device__ __forceinline__ void mbar_init(uint32_t bar, uint32_t cnt) {
    asm volatile("mbarrier.init.shared::cta.b64 [%0], %1;" ::"r"(bar), "r"(cnt) : "memory");
}
__device__ __forceinline__ void mbar_expect_tx(uint32_t bar, uint32_t bytes) {
    asm volatile("mbarrier.arrive.expect_tx.shared::cta.b64 _, [%0], %1;" ::"r"(bar), "r"(bytes) : "memory");
}
__device__ __forceinline__ void mbar_arrive(uint32_t bar) {
    asm volatile("mbarrier.arrive.shared::cta.b64 _, [%0];" ::"r"(bar) : "memory");
}
__device__ __forceinline__ void mbar_arrive8(uint32_t bar) {
    asm volatile("mbarrier.arrive.shared::cta.b64 _, [%0], 8;" ::"r"(bar) : "memory");
}
__device__ __forceinline__ void mbar_wait(uint32_t bar) {
    uint32_t done;
    int it = 0;
    do {
        asm volatile("{\n.reg .pred p;\nmbarrier.try_wait.parity.shared::cta.b64 p, [%1], 0;\nselp.u32 %0, 1, 0, p;\n}"
                     : "=r"(done) : "r"(bar) : "memory");
        if (++it > SPIN_LIMIT) __trap();
    } while (!done);
}
__device__ __forceinline__ uint32_t map_cta(uint32_t a, uint32_t rank) {
    uint32_t r; asm("mapa.shared::cluster.u32 %0, %1, %2;" : "=r"(r) : "r"(a), "r"(rank)); return r;
}
__device__ __forceinline__ void st_async32(uint32_t a, uint32_t v, uint32_t bar) {
    asm volatile("st.async.shared::cluster.mbarrier::complete_tx::bytes.b32 [%0], %1, [%2];" ::"r"(a), "r"(v), "r"(bar) : "memory");
}
__device__ __forceinline__ uint64_t evict_first() {
    uint64_t pol; asm volatile("createpolicy.fractional.L2::evict_first.b64 %0, 1.0;" : "=l"(pol)); return pol;
}
#define ELECT "{\n.reg .pred p;\nelect.sync _|p, 0xffffffff;\n@p "
__device__ __forceinline__ void bulk_load(uint32_t dst, const void* src, uint32_t bytes, uint32_t bar, uint64_t pol) {
    asm volatile(ELECT "cp.async.bulk.shared::cluster.global.mbarrier::complete_tx::bytes.L2::cache_hint [%0], [%1], %2, [%3], %4;\n}"
                 ::"r"(dst), "l"(src), "r"(bytes), "r"(bar), "l"(pol) : "memory");
}
__device__ __forceinline__ void bulk_load_nohint(uint32_t dst, const void* src, uint32_t bytes, uint32_t bar) {
    asm volatile("cp.async.bulk.shared::cluster.global.mbarrier::complete_tx::bytes [%0], [%1], %2, [%3];"
                 ::"r"(dst), "l"(src), "r"(bytes), "r"(bar) : "memory");
}
__device__ __forceinline__ void tma3d(uint32_t dst, const CUtensorMap* tm, int c0, int c1, int c2, uint32_t bar, uint64_t pol) {
    asm volatile(ELECT "cp.async.bulk.tensor.3d.shared::cluster.global.mbarrier::complete_tx::bytes.L2::cache_hint [%0], [%1, {%3, %4, %5}], [%2], %6;\n}"
                 ::"r"(dst), "l"(tm), "r"(bar), "r"(c0), "r"(c1), "r"(c2), "l"(pol) : "memory");
}
__device__ __forceinline__ void tma3d_pair(uint32_t dst, const CUtensorMap* tm, int c0, int c1, int c2, uint32_t bar, uint64_t pol) {
    asm volatile(ELECT "cp.async.bulk.tensor.3d.shared::cluster.global.mbarrier::complete_tx::bytes.multicast::cluster.L2::cache_hint [%0], [%1, {%3, %4, %5}], [%2], %7, %6;\n}"
                 ::"r"(dst), "l"(tm), "r"(bar), "r"(c0), "r"(c1), "r"(c2), "l"(pol), "h"((uint16_t)3) : "memory");
}
__device__ __forceinline__ void ldsm4(uint32_t a, uint32_t& r0, uint32_t& r1, uint32_t& r2, uint32_t& r3) {
    asm volatile("ldmatrix.sync.aligned.m8n8.x4.shared.b16 {%0,%1,%2,%3}, [%4];"
                 : "=r"(r0), "=r"(r1), "=r"(r2), "=r"(r3) : "r"(a) : "memory");
}
__device__ __forceinline__ void ldsm4t(uint32_t a, uint32_t& r0, uint32_t& r1, uint32_t& r2, uint32_t& r3) {
    asm volatile("ldmatrix.sync.aligned.m8n8.x4.trans.shared.b16 {%0,%1,%2,%3}, [%4];"
                 : "=r"(r0), "=r"(r1), "=r"(r2), "=r"(r3) : "r"(a) : "memory");
}
__device__ __forceinline__ void mma16816(float (&c)[4], uint32_t a0, uint32_t a1, uint32_t a2, uint32_t a3,
                                         uint32_t b0, uint32_t b1) {
    asm volatile("mma.sync.aligned.m16n8k16.row.col.f32.bf16.bf16.f32 {%0,%1,%2,%3}, {%4,%5,%6,%7}, {%8,%9}, {%0,%1,%2,%3};"
                 : "+f"(c[0]), "+f"(c[1]), "+f"(c[2]), "+f"(c[3])
                 : "r"(a0), "r"(a1), "r"(a2), "r"(a3), "r"(b0), "r"(b1));
}
__device__ __forceinline__ uint32_t lds32(uint32_t a) {
    uint32_t v; asm volatile("ld.shared.b32 %0, [%1];" : "=r"(v) : "r"(a) : "memory"); return v;
}
__device__ __forceinline__ float ldsf(uint32_t a) {
    float v; asm volatile("ld.shared.f32 %0, [%1];" : "=f"(v) : "r"(a) : "memory"); return v;
}
__device__ __forceinline__ float2 ldsf2(uint32_t a) {
    float2 v; asm volatile("ld.shared.v2.f32 {%0,%1}, [%2];" : "=f"(v.x), "=f"(v.y) : "r"(a) : "memory"); return v;
}
__device__ __forceinline__ float4 ldsf4(uint32_t a) {
    float4 v; asm volatile("ld.shared.v4.f32 {%0,%1,%2,%3}, [%4];" : "=f"(v.x), "=f"(v.y), "=f"(v.z), "=f"(v.w) : "r"(a) : "memory"); return v;
}
__device__ __forceinline__ uint4 lds128(uint32_t a) {
    uint4 v; asm volatile("ld.shared.v4.b32 {%0,%1,%2,%3}, [%4];" : "=r"(v.x), "=r"(v.y), "=r"(v.z), "=r"(v.w) : "r"(a) : "memory"); return v;
}
__device__ __forceinline__ float ldsf_if(uint32_t a, bool on) {
    float v = 0.f;
    asm volatile("{\n.reg .pred p;\nsetp.ne.u32 p, %2, 0;\n@p ld.shared.f32 %0, [%1];\n}" : "+f"(v) : "r"(a), "r"((uint32_t)on) : "memory");
    return v;
}
__device__ __forceinline__ float4 ldv4(uint32_t a) {
    float4 v; asm volatile("ld.volatile.shared.v4.f32 {%0,%1,%2,%3}, [%4];" : "=f"(v.x), "=f"(v.y), "=f"(v.z), "=f"(v.w) : "r"(a) : "memory"); return v;
}
__device__ __forceinline__ void stv(uint32_t a, float v) { asm volatile("st.volatile.shared.f32 [%0], %1;" ::"r"(a), "f"(v) : "memory"); }
__device__ __forceinline__ void sts16(uint32_t a, uint16_t v) { asm volatile("st.shared.b16 [%0], %1;" ::"r"(a), "h"(v) : "memory"); }
__device__ __forceinline__ void sts32(uint32_t a, uint32_t v) { asm volatile("st.shared.b32 [%0], %1;" ::"r"(a), "r"(v) : "memory"); }
__device__ __forceinline__ void stsf(uint32_t a, float v) { asm volatile("st.shared.f32 [%0], %1;" ::"r"(a), "f"(v) : "memory"); }
__device__ __forceinline__ void sts64(uint32_t a, uint32_t x, uint32_t y) {
    asm volatile("st.shared.v2.b32 [%0], {%1,%2};" ::"r"(a), "r"(x), "r"(y) : "memory");
}
__device__ __forceinline__ void sts128(uint32_t a, uint4 v) {
    asm volatile("st.shared.v4.b32 [%0], {%1,%2,%3,%4};" ::"r"(a), "r"(v.x), "r"(v.y), "r"(v.z), "r"(v.w) : "memory");
}
__device__ __forceinline__ uint32_t pack_bf16(float lo, float hi) {
    uint32_t r; asm("cvt.rn.bf16x2.f32 %0, %1, %2;" : "=r"(r) : "f"(hi), "f"(lo)); return r;
}
__device__ __forceinline__ float bf_lo(uint32_t v) { return __uint_as_float(v << 16); }
__device__ __forceinline__ float bf_hi(uint32_t v) { return __uint_as_float(v & 0xffff0000u); }
__device__ __forceinline__ float ex2(float x) { float y; asm("ex2.approx.ftz.f32 %0, %1;" : "=f"(y) : "f"(x)); return y; }
__device__ __forceinline__ uint32_t timer_ns() { uint32_t t; asm volatile("mov.u32 %0, %%globaltimer_lo;" : "=r"(t)); return t; }
__device__ __forceinline__ void bar_consumers() { asm volatile("bar.sync 1, 256;" ::: "memory"); }

__device__ __forceinline__ uint32_t tagf(float v, uint32_t tag) { return (__float_as_uint(v) & 0xffffff00u) | tag; }
__device__ __forceinline__ uint2 ld_rlx2(const float* p) {
    uint2 v; asm volatile("ld.relaxed.gpu.global.v2.b32 {%0,%1}, [%2];" : "=r"(v.x), "=r"(v.y) : "l"(p) : "memory"); return v;
}
__device__ __forceinline__ float untag(uint32_t v) { return __uint_as_float(v & 0xffffff00u); }

__device__ __forceinline__ uint32_t slot_off(int item) { return (uint32_t)(item % NSLOT) * SLOT; }

template <bool TRANS, bool TMA = true>
__device__ __forceinline__ void tile_mma(uint32_t sb, int item, uint32_t in, int w, int lane, float (&acc)[2][2]) {
    const int g = lane >> 2, t = lane & 3;
    float c[4][4];
#pragma unroll
    for (int i = 0; i < 16; i++) (&c[0][0])[i] = 0.f;
    uint32_t a[16];
    const uint32_t ia = in + (g & 3) * 272 + t * 4;
#pragma unroll
    for (int i = 0; i < 16; i++) a[i] = lds32(ia + i * 16);
    const uint32_t s0 = sb + slot_off(item), s1 = sb + slot_off(item + 1);
    if (TRANS) {
        const int r = (lane & 7) + (lane & 8);
        const int ch = 2 * (w & 3) + (lane >> 4);
        const uint32_t off = (TMA ? (w >> 2) * 8192 + r * 128 : (w >> 2) * 128 + r * 256) + ((ch ^ (lane & 7)) << 4);
#pragma unroll
        for (int kk = 0; kk < 8; kk++) {
            if (TMA && (kk & 3) == 0) mbar_wait(sb + SM_FULL + (item + (kk >> 2)) * 8);
            uint32_t r0, r1, r2, r3;
            ldsm4t(((kk >> 2) ? s1 : s0) + off + (kk & 3) * (TMA ? 2048 : 4096), r0, r1, r2, r3);
            mma16816(c[2 * (kk & 1)],     a[2 * kk], 0u, a[2 * kk + 1], 0u, r0, r1);
            mma16816(c[2 * (kk & 1) + 1], a[2 * kk], 0u, a[2 * kk + 1], 0u, r2, r3);
        }
    } else {
        mbar_wait(sb + SM_FULL + (item + (w >> 2)) * 8);
        const int r = 16 * (w & 3) + (lane & 7) + ((lane >> 4) << 3);
        const uint32_t base = ((w >> 2) ? s1 : s0) + (r & 32) * 128 + r * 128 + ((((lane >> 3) & 1) ^ (lane & 7)) << 4);
#pragma unroll
        for (int kk = 0; kk < 8; kk++) {
            uint32_t r0, r1, r2, r3;
            ldsm4((base ^ ((kk & 3) << 5)) + (kk >> 2) * 4096, r0, r1, r2, r3);
            mma16816(c[2 * (kk & 1)],     a[2 * kk], 0u, a[2 * kk + 1], 0u, r0, r1);
            mma16816(c[2 * (kk & 1) + 1], a[2 * kk], 0u, a[2 * kk + 1], 0u, r2, r3);
        }
    }
    __syncwarp();
    if (lane == 0) {
        mbar_arrive(sb + SM_EMPTY + item * 8);
        mbar_arrive(sb + SM_EMPTY + (item + 1) * 8);
    }
    acc[0][0] = c[0][0] + c[2][0]; acc[0][1] = c[0][1] + c[2][1];
    acc[1][0] = c[1][0] + c[3][0]; acc[1][1] = c[1][1] + c[3][1];
}

__device__ __forceinline__ void publish(float* dst, int w, int lane, const float (&acc)[2][2], uint32_t tag) {
    if (lane < 16)
        asm volatile("st.relaxed.gpu.global.v4.b32 [%0], {%1,%2,%3,%4};" ::"l"(dst + w * 64 + lane * 4),
                     "r"(tagf(acc[0][0], tag)), "r"(tagf(acc[0][1], tag)), "r"(tagf(acc[1][0], tag)), "r"(tagf(acc[1][1], tag)) : "memory");
}

__device__ __forceinline__ void gather(const float* part, uint32_t in, int tid, uint32_t tag) {
    const float* p = part + tid * 2;
    uint2 v0, v1, v2, v3;
    int it = 0;
    while (true) {
        v0 = ld_rlx2(p); v1 = ld_rlx2(p + 512); v2 = ld_rlx2(p + 1024); v3 = ld_rlx2(p + 1536);
        uint32_t bad = ((v0.x ^ tag) | (v0.y ^ tag) | (v1.x ^ tag) | (v1.y ^ tag) |
                        (v2.x ^ tag) | (v2.y ^ tag) | (v3.x ^ tag) | (v3.y ^ tag)) & 0xffu;
        if (__all_sync(0xffffffffu, bad == 0)) break;
        if (++it > SPIN_LIMIT) __trap();
    }
    float x = (untag(v0.x) + untag(v1.x)) + (untag(v2.x) + untag(v3.x));
    float y = (untag(v0.y) + untag(v1.y)) + (untag(v2.y) + untag(v3.y));
    sts32(in + ((tid >> 3) & 3) * 272 + (tid >> 5) * 32 + (tid & 1) * 16 + (tid & 6) * 2, pack_bf16(x, y));
    bar_consumers();
}

constexpr uint32_t EMPTY = 0xffffffffu;
__device__ __forceinline__ void st_rlx(uint32_t* p, uint32_t v) {
    asm volatile("st.relaxed.gpu.global.b32 [%0], %1;" ::"l"(p), "r"(v) : "memory");
}
__device__ __forceinline__ void st_rlx_if(uint64_t p, uint32_t v, bool on) {
    asm volatile("{\n.reg .pred p;\nsetp.ne.u32 p, %2, 0;\n@p st.relaxed.gpu.global.b32 [%0], %1;\n}" ::"l"(p), "r"(v), "r"((uint32_t)on) : "memory");
}
__device__ __forceinline__ void st_bf16_if(uint64_t p, float v, bool on) {
    asm volatile("{\n.reg .pred p;\n.reg .b16 h;\nsetp.ne.u32 p, %2, 0;\ncvt.rn.bf16.f32 h, %1;\n@p st.global.b16 [%0], h;\n}" ::"l"(p), "f"(v), "r"((uint32_t)on) : "memory");
}
__device__ __forceinline__ void st_rlx2(uint32_t* p, uint32_t v0, uint32_t v1) {
    asm volatile("st.relaxed.gpu.global.v2.b32 [%0], {%1,%2};" ::"l"(p), "r"(v0), "r"(v1) : "memory");
}
__device__ __forceinline__ void ld_rlx4_if(uint4& v, const void* p, bool need) {
    asm volatile("{\n.reg .pred p;\nsetp.ne.u32 p, %5, 0;\n@p ld.relaxed.gpu.global.v4.b32 {%0,%1,%2,%3}, [%4];\n}"
                 : "+r"(v.x), "+r"(v.y), "+r"(v.z), "+r"(v.w) : "l"(p), "r"((uint32_t)need) : "memory");
}

template <int N, class F>
__device__ __forceinline__ bool refetch(uint4 (&x)[N], F addr) {
    uint32_t m[N], m0 = 0;
#pragma unroll
    for (int i = 0; i < N; i++) {
        m[i] = max(max(x[i].x, x[i].y), max(x[i].z, x[i].w));
        m0 = max(m0, m[i]);
    }
    if (!__any_sync(0xffffffffu, m0 == EMPTY)) return false;
#pragma unroll
    for (int i = 0; i < N; i++) ld_rlx4_if(x[i], addr(i), m[i] == EMPTY);
    return true;
}

__device__ __forceinline__ unsigned read_counter(const unsigned* cnt) {
    unsigned v;
    asm volatile("ld.relaxed.gpu.global.u32 %0, [%1];" : "=r"(v) : "l"(cnt) : "memory");
    return v;
}
__device__ __forceinline__ unsigned epoch_of(unsigned cnt) {
    asm volatile("" : "+r"(cnt) :: "memory");
    return cnt / NCTA + 1;
}
__device__ __forceinline__ uint32_t epoch_tag(unsigned epoch) { return (epoch & 0x7fu) | 0x80u; }

__device__ __forceinline__ void signal_and_wait(unsigned* cnt, unsigned target, int lane) {
    if (lane == 0) asm volatile("red.release.gpu.global.add.u32 [%0], 1;" ::"l"(cnt) : "memory");
    int it = 0;
    while (true) {
        unsigned v;
        asm volatile("ld.acquire.gpu.global.u32 %0, [%1];" : "=r"(v) : "l"(cnt) : "memory");
        if (__all_sync(0xffffffffu, (int)(v - target) >= 0)) break;
        if (++it > SPIN_LIMIT) __trap();
    }
    asm volatile("fence.proxy.async.global;" ::: "memory");
}

__global__ void __cluster_dims__(2, 1, 1) __launch_bounds__(NTHR, 1)
fused_decode_kernel(const __nv_bfloat16* __restrict__ xA, const __nv_bfloat16* __restrict__ xB,
                    const __nv_bfloat16* __restrict__ wqB, const __nv_bfloat16* __restrict__ wqA,
                    const __nv_bfloat16* __restrict__ Kc, const __nv_bfloat16* __restrict__ Vc,
                    __nv_bfloat16* __restrict__ out, Scratch* gs, const __grid_constant__ Maps maps) {
    extern __shared__ __align__(1024) unsigned char smem_raw[];
    const uint32_t sb = smem_u32(smem_raw);
    const int tid = threadIdx.x, lane = tid & 31;
    const int cta = blockIdx.x, h = cta >> 2, j = cta & 3;
    const size_t kv_off = (size_t)blockIdx.x * 4096 * 128;
    const uint32_t trow = threadIdx.x >> 4;
    const uint32_t tile_src = trow * (8192 - 256) + (threadIdx.x * 16 + ((blockIdx.x * 0x100040u) & 0x301f00u));
    const uint32_t tile_dst = sb + ((threadIdx.x ^ (trow & 7)) << 4);
    auto lsu_piece = [&](int k) {
#pragma unroll
        for (int q = 2 * k; q < 2 * k + 2; q++)
            asm volatile("cp.async.cg.shared.global [%0], [%1], 16;" ::"r"(tile_dst + q * 4096),
                         "l"(reinterpret_cast<const char*>((k < 4 ? wqB : wqA) + (q & 7) * 16 * 4096) + tile_src) : "memory");
        if ((k & 3) == 3) asm volatile("cp.async.commit_group;" ::: "memory");
    };
    if (tid < 256) {
#pragma unroll
        for (int k = 0; k < 4; k++) lsu_piece(k);
    }
    const uint32_t tz = timer_ns() - LEAD;
    unsigned cnt1;
    if (tid < 256) cnt1 = read_counter(&gs->cnt[1]);
    uint4 xv;
    if (tid < 128) {
        const __nv_bfloat16* x = (tid < 64 ? xB : xA) + ((tid >> 4) & 3) * 512 + j * 128 + (tid & 15) * 8;
        xv = __ldg(reinterpret_cast<const uint4*>(x));
    }
    const int w = __shfl_sync(0xffffffffu, tid >> 5, 0);
    const int pr = cta >> 1;
    const int slice = pr < 4 ? pr : pr < 36 ? 4 + ((pr - 4) & 7) * 4 + ((pr - 4) >> 3) : 36 + (pr - 36) % 7 * 4 + (pr - 36) / 7;

    if (w >= 8) {
        if (lane == 0) {
            const uint32_t full = sb + SM_FULL + (IT_WUK + (w & 3) * 14) * 8, empty = sb + SM_EMPTY + (w & 3) * 13 * 8,
                           last = sb + SM_LAST + (w & 3) * 32;
#pragma unroll
            for (int i = 0; i < 14; i++) mbar_init(full + i * 8, 1);
#pragma unroll
            for (int i = 0; i < 13; i++) mbar_init(empty + i * 8, 8);
#pragma unroll
            for (int i = 0; i < 4; i++) mbar_init(last + i * 8, 1);
#pragma unroll
            for (int i = 0; i < 14; i++) {
                const int b = IT_WUK + 42 + i;
                mbar_expect_tx(full + i * 8, (w == 10 && b - 14 == IT_OP) ? SLOT + 1024 : w != 11 ? SLOT : b == BAR_LAT ? 4096 :
                                             b == BAR_X ? SLOT + 4096 : b == BAR_PEER ? 8 : SLOT);
            }
#pragma unroll
            for (int i = 0; i < 4; i++) mbar_expect_tx(last + i * 8, i == 1 && w == 8 ? 2048 + 128 : 2048);
            asm volatile("fence.mbarrier_init.release.cluster;" ::: "memory");
            if (w == 10) sts64(sb + SM_PACE, tz, PACE * 16);
        }
        asm volatile("bar.sync 2, 128;" ::: "memory");
        asm volatile("bar.arrive 4, 384;" ::: "memory");
    }
    if (w == 10) {
        if (lane == 0) {
            int slope = 0;
#pragma unroll
            for (int k = 0; k < NWIN; k++) {
                const int c = win_pos(k);
                uint32_t acc = 0;
#pragma unroll
                for (int p = c; p < c + 4; p++) {
                    mbar_wait(sb + SM_FULL + (p < IT_Q ? p : p < IT_OP - 2 ? p + 2 : p + 4) * 8);
                    acc += timer_ns() - tz - p * PACE - ((p * slope) >> 4);
                }
                if (k == 0) mbar_wait(sb + SM_FULL + IT_Q * 8);
                asm volatile("red.relaxed.gpu.global.add.u32 [%0], %1;" ::"l"(&gs->late[k]), "r"((1u << 24) + min(acc >> 2, 65535u)) : "memory");
                uint32_t v;
                int it = 0;
                do { v = read_counter(&gs->late[k]); } while ((v >> 24) != NCTA && ++it < 1000);
                const int late = (v & 0xffffffu) / NCTA;
                slope = max(-320, min(320, slope + (late - win_late(k)) * (GAIN * 2) / (2 * c + 3)));
                sts64(sb + SM_PACE, tz, PACE * 16 + slope);
            }
        }
        return;
    }
    if (w >= 8) {
        auto wait_due = [&](uint32_t p, uint32_t shift) {
            uint32_t a, b;
            do {
                asm volatile("ld.volatile.shared.v2.b32 {%0,%1}, [%2];" : "=r"(a), "=r"(b) : "r"(sb + SM_PACE) : "memory");
            } while (__all_sync(0xffffffffu, (int)(timer_ns() - (a + ((p * b) >> 4) + shift)) < 0));
        };
        if (w != 9) {
            const int half = w & 1;
            const uint64_t pol = evict_first();
            int slot = IT_WUK, tail = IT_WUK - INFLIGHT;
            uint32_t np = IT_WUK, shift = half ? PACE / 4 : -(PACE / 4);
#pragma unroll 1
            for (int i = IT_WUK; i < NITEM; i++) {
                const uint32_t dst = sb + slot * SLOT + half * (SLOT / 2), bar = sb + SM_FULL + i * 8;
                if (++slot == NSLOT) slot = 0;
                if ((i & ~1) == IT_Q || (i & ~1) == IT_OP) continue;
                const bool ckv = i >= IT_C && i < IT_K1, wo = i >= IT_WO;
                const bool tiled = ckv || i < IT_K0 || i >= IT_WUV;
                const CUtensorMap* tm = &maps.wuk + (i < IT_K0 ? 0 : ckv ? 4 : wo ? 2 + (slice >> 5) : 1);
                const int c0 = wo ? (slice & 31) * 16 : i >= IT_WUV ? cta * 32 : 0;
                const int c1 = i < IT_K0 ? j * 128 + (i & 1) * 64 + half * 32 : ckv ? cta * 128 + (i - IT_C) * 16 + half * 8 : wo ? 0 : half * 128;
                const int c2 = i < IT_K0 ? h * 2 : ckv ? 0 : wo ? (i - IT_WO) * 4 + (j & 1) * 2 + half : i & 1;
                const int c = i < IT_Q ? i - IT_K0 : i < IT_V0 ? i - IT_K1 + 8 : i < IT_OP ? i - IT_V0 : i - IT_V1 + 8;
                const __nv_bfloat16* src = (i < IT_V0 ? Kc : Vc) + kv_off + (size_t)((c ^ (j & 1) * 7) * 2 + half) * (SLOT / 4);
                if (i >= NSLOT) mbar_wait(sb + SM_EMPTY + (i - NSLOT) * 8);
                if (tail >= IT_WUK) mbar_wait(sb + SM_FULL + tail * 8);
                ++tail;
                if (tail == IT_Q || tail == IT_OP) tail += 2;
                if (i == NITEM - 1) mbar_wait(sb + SM_FULL + BAR_PEER * 8);
                wait_due(np, shift);
                ++np;
                if (i == IT_WUV - 1) shift += TAPER;
                if (i == NITEM - 1) {
#pragma unroll
                    for (int q = 0; q < 4; q++)
                        tma3d_pair(dst + (j & 1) * (IT_W2 - i) * SLOT + q * 2048, tm + 3, c0, q * 64, c2,
                                   sb + SM_LAST + (j & 1) * 64 + q * 16 + half * 8, pol);
                }
                else if (tiled) tma3d(dst, tm, c0, c1, c2, bar, pol);
                else bulk_load(dst, src, SLOT / 2, bar, pol);
            }
            if (half) return;
            const uint32_t to  = map_cta(sb, (j & 1) ^ 1);
            const uint32_t src = __shfl_sync(0xffffffffu, sb + SM_SND + lane * 16, lane);
            const uint32_t rcv = __shfl_sync(0xffffffffu, to + SM_RCV + lane * 4, lane);
            const uint32_t fin = __shfl_sync(0xffffffffu, to + SM_LAST + 8, lane);
            mbar_wait(sb + SM_FULL + (NITEM - 3) * 8);
            asm volatile("bar.sync 5, 288;" ::: "memory");
            const float4 p0 = ldsf4(src), p1 = ldsf4(src + 512);
            st_async32(rcv, __float_as_uint(((p0.x + p0.y) + (p0.z + p0.w)) + ((p1.x + p1.y) + (p1.z + p1.w))), fin);
        } else {
            if (lane < sizeof(Maps) / 128) asm volatile("prefetch.tensormap [%0];" ::"l"(&maps.wuk + lane) : "memory");
            cnt1 = read_counter(&gs->cnt[1]);
            asm volatile("bar.sync 3, 288;" ::: "memory");
            const unsigned epoch = epoch_of(cnt1);
            signal_and_wait(&gs->cnt[0], epoch * NCTA, lane);
            if (lane == 0) {
                const uint4* q = gs->q[cta >> 5];
                bulk_load_nohint(sb + slot_off(IT_Q), q, SLOT, sb + SM_FULL + IT_Q * 8);
                bulk_load_nohint(sb + slot_off(IT_Q + 1), q + 1024, SLOT, sb + SM_FULL + (IT_Q + 1) * 8);
            }
            asm volatile("bar.sync 3, 288;" ::: "memory");
            signal_and_wait(&gs->cnt[1], epoch * NCTA, lane);
            mbar_wait(sb + SM_EMPTY + (IT_OP - NSLOT) * 8);
            mbar_wait(sb + SM_EMPTY + (IT_OP + 1 - NSLOT) * 8);
            if (lane == 0) {
                const uint4* op = gs->op[cta];
                bulk_load_nohint(sb + SM_MX, gs->stat[h], 1024, sb + SM_FULL + IT_OP * 8);
                uint32_t t1 = timer_ns();
#pragma unroll 1
                for (int i = 0; i < 8; i++) {
                    while ((int)(timer_ns() - t1) < 0) {}
                    t1 += OPGAP;
                    bulk_load_nohint(sb + slot_off(IT_OP) + i * 4096, op + i * 256, 4096, sb + SM_FULL + (IT_OP + i / 4) * 8);
                }
            }
            mbar_wait(sb + SM_FULL + (IT_V1 + 4) * 8);
            if (lane == 0) bulk_load_nohint(sb + SM_LAT, gs->lat[h], 4096, sb + SM_FULL + BAR_LAT * 8);
            mbar_wait(sb + SM_EMPTY + (IT_X - NSLOT) * 8);
            mbar_wait(sb + SM_EMPTY + (IT_X + 1 - NSLOT) * 8);
            mbar_wait(sb + SM_FULL + (IT_WUV + 1) * 8);
            mbar_wait(sb + SM_FULL + BAR_PEER * 8);
            wait_due(NITEM - 5, (uint32_t)(TAPER - XLEAD));
            if (lane == 0)
                bulk_load_nohint(sb + slot_off(IT_X), gs->x[slice >> 5][(j & 1) * 12], SLOT + 4096, sb + SM_FULL + BAR_X * 8);
        }
        return;
    }

    const int g = lane >> 2, t = lane & 3;
    const uint32_t in0 = sb + SM_IN0, in1 = sb + SM_IN1;
    auto xpos = [](int hh) { return (hh & 4) * 4 + (((hh >> 3) + (hh >> 2 & 1)) & 3) * 4 + (hh & 3); };
    const int ba = cta >> 5, ha = cta & 31;
    uint32_t* const ctx_dst = &gs->x[1][xpos(h)][(j * 4 + (w & 3)) * 16 + ((g ^ (w & 2)) & 3) * 4 + ((t - w) & 3)];
    uint32_t* const o_dst = &gs->x[0][xpos(ha)][ba * 64 + ((tid & 60) ^ ((ba & 1) * 16)) + ((t - g) & 3)];
    uint32_t* const lat_dst = &gs->lat[h][g & 3][j * 64 + ((w >> 1) ^ (g & 1)) * 16 + t * 4 + ((w * 2 ^ t) & 2)];
    {
#pragma unroll
        for (int k = 4; k < 8; k++) {
            while (__all_sync(0xffffffffu, (int)(timer_ns() - (tz + (2 * k - 1) * (PACE / 4))) < 0)) {}
            lsu_piece(k);
        }
        if (lane < 16) st_rlx2(lat_dst, EMPTY, EMPTY);
        if (lane >= 16 && w < 4) st_rlx(ctx_dst, EMPTY);
        if (w >= 6) st_rlx(o_dst, EMPTY);
        if (cta == 0 && w == 5) st_rlx(&gs->late[lane], 0u);
        if (tid < 128) sts128((tid < 64 ? in0 : in1) + ((tid >> 4) & 3) * 272 + (tid & 15) * 16, xv);
        asm volatile("cp.async.wait_group 1;" ::: "memory");
    }
    asm volatile("bar.sync 4, 384;" ::: "memory");
    const uint32_t tag = epoch_tag(epoch_of(cnt1));

    float acc[2][2];
    tile_mma<true, false>(sb, IT_WQB, in0, w, lane, acc);
    publish(gs->part[0][cta], w, lane, acc, tag);
    asm volatile("cp.async.wait_group 0;" ::: "memory");
    bar_consumers();
    tile_mma<true, false>(sb, IT_WQA, in1, w, lane, acc);
    publish(gs->part[1][cta], w, lane, acc, tag);
    bar_consumers();

    const float SC = 0.08838834764831845f * 1.4426950408889634f;
    gather(gs->part[0][h * 4], in0, tid, tag);
    tile_mma<false>(sb, IT_WUK, in0, w, lane, acc);
    if (lane < 16) {
        uint32_t* q = reinterpret_cast<uint32_t*>(gs->q[g]) + (2 * j + (w >> 2)) * 1024 + h * 32 + t;
        const int ch = 2 * (w & 3);
        q[((ch) ^ (h & 7)) * 4]     = pack_bf16(acc[0][0] * SC, acc[0][1] * SC);
        q[((ch + 1) ^ (h & 7)) * 4] = pack_bf16(acc[1][0] * SC, acc[1][1] * SC);
    }
    __syncwarp();
    asm volatile("bar.arrive 3, 288;" ::: "memory");
    gather(gs->part[1][ha * 4], in1, tid, tag);

    uint32_t qf[16];
#pragma unroll
    for (int c = 0; c < 8; c++) {
        qf[2 * c]     = lds32(in1 + ba * 272 + ((c ^ g) << 4) + t * 4);
        qf[2 * c + 1] = lds32(in1 + ba * 272 + 128 + ((c ^ g) << 4) + t * 4);
    }
    const uint32_t sc_w = sb + SM_SC + w * 512;
    auto k_item = [&](int item, uint32_t sc) {
        mbar_wait(sb + SM_FULL + item * 8);
        const uint32_t base = sb + slot_off(item) + ((lane & 7) + (lane & 8)) * 256 + ((lane >> 4) << 7);
        float s[4][4];
#pragma unroll
        for (int T = 0; T < 4; T++) { s[T][0] = s[T][1] = s[T][2] = s[T][3] = 0.f; }
#pragma unroll
        for (int c = 0; c < 8; c++) {
            const uint32_t a = base + ((c ^ (lane & 7)) << 4);
#pragma unroll
            for (int T = 0; T < 4; T++) {
                uint32_t r0, r1, r2, r3;
                ldsm4(a + T * 4096, r0, r1, r2, r3);
                mma16816(s[T], r0, r1, r2, r3, qf[2 * c], qf[2 * c + 1]);
            }
        }
        __syncwarp();
        if (lane == 0) mbar_arrive8(sb + SM_EMPTY + item * 8);
        if (t == (g >> 1)) {
#pragma unroll
            for (int T = 0; T < 4; T++) {
                stsf(sc + (16 * T + g) * 4,     (g & 1) ? s[T][1] : s[T][0]);
                stsf(sc + (16 * T + g + 8) * 4, (g & 1) ? s[T][3] : s[T][2]);
            }
        }
    };
    k_item(IT_K0 + w, sc_w);

    {
        float s[2][2][4];
#pragma unroll
        for (int i = 0; i < 16; i++) (&s[0][0][0])[i] = 0.f;
        mbar_wait(sb + SM_FULL + IT_Q * 8);
        mbar_wait(sb + SM_FULL + (IT_Q + 1) * 8);
        mbar_wait(sb + SM_FULL + (IT_C + w) * 8);
        const uint32_t cb0 = sb + slot_off(IT_C + w) + (lane & 7) * 128 + (lane >> 4) * 8192;
        const uint32_t cx = (((lane >> 3) & 1) ^ (lane & 7)) << 4;
        const uint32_t qr = ((lane & 7) + (lane & 8)) * 128;
        const uint32_t qx = ((lane >> 4) ^ (lane & 7)) << 4;
#pragma unroll
        for (int cb = 0; cb < 8; cb++) {
            const uint32_t qb = sb + slot_off(IT_Q + (cb >> 2)) + (cb & 3) * 4096 + qr;
#pragma unroll
            for (int k4 = 0; k4 < 4; k4++) {
                uint32_t b0, b1, b2, b3, a0, a1, a2, a3;
                ldsm4(cb0 + cb * 1024 + (cx ^ (k4 << 5)), b0, b1, b2, b3);
                ldsm4(qb + (qx ^ (k4 << 5)), a0, a1, a2, a3);
                mma16816(s[0][0], a0, a1, a2, a3, b0, b1);
                mma16816(s[0][1], a0, a1, a2, a3, b2, b3);
                ldsm4(qb + 2048 + (qx ^ (k4 << 5)), a0, a1, a2, a3);
                mma16816(s[1][0], a0, a1, a2, a3, b0, b1);
                mma16816(s[1][1], a0, a1, a2, a3, b2, b3);
            }
        }
        __syncwarp();
        if (lane == 0) { mbar_arrive(sb + SM_EMPTY + IT_Q * 8); mbar_arrive(sb + SM_EMPTY + (IT_Q + 1) * 8); }
#pragma unroll
        for (int r = 0; r < 4; r++) {
            const int mt = r >> 1, hi = (r & 1) * 2;
            float m = fmaxf(fmaxf(s[mt][0][hi], s[mt][0][hi + 1]), fmaxf(s[mt][1][hi], s[mt][1][hi + 1]));
            m = fmaxf(m, __shfl_xor_sync(0xffffffffu, m, 1));
            m = fmaxf(m, __shfl_xor_sync(0xffffffffu, m, 2));
            if (t == 0) stsf(sb + SM_MX + (8 * r + g) * 32 + w * 4, m);
        }
        bar_consumers();
        sts32(sb + SM_FIN + tid * 4, EMPTY);
        if (w == 0) sts32(sb + SM_CNT + lane * 4, 0u);
        uint32_t pf[2][4];
#pragma unroll
        for (int r = 0; r < 4; r++) {
            const int mt = r >> 1, hi = r & 1;
            const float4 m0 = ldsf4(sb + SM_MX + (8 * r + g) * 32), m1 = ldsf4(sb + SM_MX + (8 * r + g) * 32 + 16);
            const float m = fmaxf(fmaxf(fmaxf(m0.x, m0.y), fmaxf(m0.z, m0.w)), fmaxf(fmaxf(m1.x, m1.y), fmaxf(m1.z, m1.w)));
            const uint32_t p0 = pack_bf16(ex2(s[mt][0][2 * hi] - m), ex2(s[mt][0][2 * hi + 1] - m));
            const uint32_t p1 = pack_bf16(ex2(s[mt][1][2 * hi] - m), ex2(s[mt][1][2 * hi + 1] - m));
            pf[mt][hi] = p0; pf[mt][2 + hi] = p1;
            float l = (bf_lo(p0) + bf_hi(p0)) + (bf_lo(p1) + bf_hi(p1));
            l += __shfl_xor_sync(0xffffffffu, l, 1);
            l += __shfl_xor_sync(0xffffffffu, l, 2);
            if (t == 0) stsf(sb + SM_SUM + (8 * r + g) * 32 + w * 4, l);
        }
        sts128(sb + SM_PF + (w * 2 + 0) * 512 + lane * 16, make_uint4(pf[0][0], pf[0][1], pf[0][2], pf[0][3]));
        sts128(sb + SM_PF + (w * 2 + 1) * 512 + lane * 16, make_uint4(pf[1][0], pf[1][1], pf[1][2], pf[1][3]));
        bar_consumers();
        if (w == 0) {
            const float4 m0 = ldsf4(sb + SM_MX + lane * 32), m1 = ldsf4(sb + SM_MX + lane * 32 + 16);
            const float4 l0 = ldsf4(sb + SM_SUM + lane * 32), l1 = ldsf4(sb + SM_SUM + lane * 32 + 16);
            const float m = fmaxf(fmaxf(fmaxf(m0.x, m0.y), fmaxf(m0.z, m0.w)), fmaxf(fmaxf(m1.x, m1.y), fmaxf(m1.z, m1.w)));
            const float l = ((l0.x + l0.y) + (l0.z + l0.w)) + ((l1.x + l1.y) + (l1.z + l1.w));
            gs->stat[lane][cta] = make_float2(m, l);
        }
        float o[2][8][4];
#pragma unroll
        for (int i = 0; i < 64; i++) (&o[0][0][0])[i] = 0.f;
        const uint32_t vr = w * 1024 + (lane & 7) * 128 + (lane & 8) * 1024;
        const uint32_t vx = ((lane >> 4) ^ (lane & 7)) << 4;
#pragma unroll
        for (int ks = 0; ks < 8; ks++) {
            const uint4 p0 = lds128(sb + SM_PF + (ks * 2 + 0) * 512 + lane * 16);
            const uint4 p1 = lds128(sb + SM_PF + (ks * 2 + 1) * 512 + lane * 16);
            const uint32_t vb = sb + slot_off(IT_C + ks) + vr;
#pragma unroll
            for (int n2 = 0; n2 < 4; n2++) {
                uint32_t b0, b1, b2, b3;
                ldsm4t(vb + (vx ^ (n2 << 5)), b0, b1, b2, b3);
                mma16816(o[0][2 * n2],     p0.x, p0.y, p0.z, p0.w, b0, b1);
                mma16816(o[0][2 * n2 + 1], p0.x, p0.y, p0.z, p0.w, b2, b3);
                mma16816(o[1][2 * n2],     p1.x, p1.y, p1.z, p1.w, b0, b1);
                mma16816(o[1][2 * n2 + 1], p1.x, p1.y, p1.z, p1.w, b2, b3);
            }
            __syncwarp();
            if (lane == 0) mbar_arrive(sb + SM_EMPTY + (IT_C + ks) * 8);
        }
        mbar_wait(sb + SM_FULL + (IT_K1 + 1 + (w * 3 >> 2)) * 8);
#pragma unroll
        for (int r = 0; r < 4; r++) {
            const int mt = r >> 1, hi = (r & 1) * 2;
            uint4* dst = gs->op[(8 * r + g) * 4 + (w >> 1)] + (cta >> 6) * 1024 + (w & 1) * 512 + (cta & 63) * 8;
#pragma unroll
            for (int u = 0; u < 2; u++) {
                uint4 v;
                v.x = pack_bf16(o[mt][4 * u][hi],     o[mt][4 * u][hi + 1]);
                v.y = pack_bf16(o[mt][4 * u + 1][hi], o[mt][4 * u + 1][hi + 1]);
                v.z = pack_bf16(o[mt][4 * u + 2][hi], o[mt][4 * u + 2][hi + 1]);
                v.w = pack_bf16(o[mt][4 * u + 3][hi], o[mt][4 * u + 3][hi + 1]);
                dst[(t + 4 * u) ^ (cta & 7)] = v;
            }
        }
        asm volatile("bar.arrive 3, 288;" ::: "memory");
    }

    k_item(IT_K1 + w, sc_w + 256);
    __syncwarp();
    {
        const float4 s = ldsf4(sc_w + lane * 16);
        float m = fmaxf(fmaxf(s.x, s.y), fmaxf(s.z, s.w));
#pragma unroll
        for (int d = 1; d < 32; d <<= 1) m = fmaxf(m, __shfl_xor_sync(0xffffffffu, m, d));
        if (lane == 0) stsf(sb + SM_ML + w * 4, m);
        bar_consumers();
        const float4 m0 = ldsf4(sb + SM_ML), m1 = ldsf4(sb + SM_ML + 16);
        m = fmaxf(fmaxf(fmaxf(m0.x, m0.y), fmaxf(m0.z, m0.w)), fmaxf(fmaxf(m1.x, m1.y), fmaxf(m1.z, m1.w))) * SC;
        const uint32_t p0 = pack_bf16(ex2(fmaf(s.x, SC, -m)), ex2(fmaf(s.y, SC, -m)));
        const uint32_t p1 = pack_bf16(ex2(fmaf(s.z, SC, -m)), ex2(fmaf(s.w, SC, -m)));
        float l = (bf_lo(p0) + bf_hi(p0)) + (bf_lo(p1) + bf_hi(p1));
#pragma unroll
        for (int d = 1; d < 32; d <<= 1) l += __shfl_xor_sync(0xffffffffu, l, d);
        if (lane == 0) stsf(sb + SM_ML + 32 + w * 4, l);
        sts64(sb + SM_PA + w * 256 + lane * 8, p0, p1);
        __syncwarp();
    }

    float oa[4][4];
#pragma unroll
    for (int i = 0; i < 16; i++) (&oa[0][0])[i] = 0.f;
    auto v_item = [&](int item, uint32_t pa) {
        uint32_t p[8];
#pragma unroll
        for (int i = 0; i < 8; i++) p[i] = lds32(pa + i * 16 + t * 4);
        mbar_wait(sb + SM_FULL + item * 8);
        const uint32_t base = sb + slot_off(item) + ((lane & 7) + ((lane >> 4) << 3)) * 256 + ((lane & 8) << 4);
#pragma unroll
        for (int c = 0; c < 8; c++) {
            const uint32_t a = base + ((c ^ (lane & 7)) << 4);
            const uint32_t mask = ((c == (g ^ (2 * t))) ? 0x0000ffffu : 0u) | ((c == (g ^ (2 * t + 1))) ? 0xffff0000u : 0u);
#pragma unroll
            for (int T = 0; T < 4; T++) {
                uint32_t r0, r1, r2, r3;
                ldsm4t(a + T * 4096, r0, r1, r2, r3);
                mma16816(oa[T], r0, r1, r2, r3, p[2 * T] & mask, p[2 * T + 1] & mask);
            }
        }
        __syncwarp();
        if (lane == 0) mbar_arrive8(sb + SM_EMPTY + item * 8);
    };
    v_item(IT_V0 + w, sb + SM_PA + w * 256);

    mbar_wait(sb + SM_FULL + IT_OP * 8);
    if (w < 4) {
        const float2 st = ldsf2(sb + SM_MX + tid * 8);
        float m = st.x;
#pragma unroll
        for (int d = 1; d < 32; d <<= 1) m = fmaxf(m, __shfl_xor_sync(0xffffffffu, m, d));
        const uint32_t wb = pack_bf16(ex2(st.x - m), 0.f);
        float l = bf_lo(wb) * st.y;
#pragma unroll
        for (int d = 1; d < 32; d <<= 1) l += __shfl_xor_sync(0xffffffffu, l, d);
#pragma unroll
        for (int bb = 0; bb < 4; bb++) sts16(in0 + bb * 272 + tid * 2, bb == w ? (uint16_t)wb : (uint16_t)0);
        if (lane == 0) stsf(sb + SM_ML + 64 + w * 4, 1.f / l);
    }
    bar_consumers();
    tile_mma<true>(sb, IT_OP, in0, w, lane, acc);
    if (lane < 16) {
        const float inv = ldsf(sb + SM_ML + 64 + g * 4);
        const uint32_t v0 = pack_bf16(acc[0][0] * inv, acc[0][1] * inv), v1 = pack_bf16(acc[1][0] * inv, acc[1][1] * inv);
        st_rlx2(lat_dst, (t & 1) ? v1 : v0, (t & 1) ? v0 : v1);
    }

    {
        const float4 l0 = ldsf4(sb + SM_ML + 32), l1 = ldsf4(sb + SM_ML + 48);
        const float inv = 1.f / (((l0.x + l0.y) + (l0.z + l0.w)) + ((l1.x + l1.y) + (l1.z + l1.w)));
        v_item(IT_V1 + w, sb + SM_PA + w * 256 + 128);
        const uint32_t so = sb + SM_PF + w * 512 + (16 * t + g) * 4;
        stsf(so,       (oa[0][0] + oa[1][0]) + (oa[2][0] + oa[3][0]));
        stsf(so + 32,  (oa[0][1] + oa[1][1]) + (oa[2][1] + oa[3][1]));
        stsf(so + 256, (oa[0][2] + oa[1][2]) + (oa[2][2] + oa[3][2]));
        stsf(so + 288, (oa[0][3] + oa[1][3]) + (oa[2][3] + oa[3][3]));
        if (w < 6) {
            asm volatile("bar.arrive 1, 256;" ::: "memory");
        } else {
            bar_consumers();
            float x = 0.f, y = 0.f;
#pragma unroll
            for (int i = 0; i < 8; i++) {
                const float2 v = ldsf2(sb + SM_PF + i * 512 + (tid & 63) * 8);
                x += v.x; y += v.y;
            }
            st_rlx(o_dst, pack_bf16(x * inv, y * inv));
            if (lane == 0) {
                const uint32_t to = map_cta(sb, w & 1);
                st_async32(to + SM_PACE + 16 + (j & 1) * 4, 0u, to + SM_FULL + BAR_PEER * 8);
            }
        }
    }

    if (w < 4) {
        const uint32_t lo = (g & 3) * 1024 + (g >> 2) * 512 + (g & 1) * 64 + t * 16;
        const int wd = ((lane >> 2 & 2) + (lane >> 4)) ^ (lane >> 1 & 3);
        const uint32_t base = sb + ((lane & 6) * 4 + wd * 2 + (lane & 1)) * 64 + (((w ^ wd) & 3) << 4);
        const uint64_t dst = __shfl_sync(0xffffffffu, (unsigned long long)ctx_dst, lane);
        mbar_wait(sb + SM_FULL + BAR_LAT * 8);
        uint4 a[8];
#pragma unroll
        for (int i = 0; i < 8; i++) a[i] = lds128(sb + SM_LAT + (lo ^ (i * 64)));
        int it = 0;
        while (refetch(a, [&](int i) { return (const char*)gs->lat[h] + (lo ^ (i * 64)); }))
            if (++it > SPIN_LIMIT) __trap();
        float v0 = 0.f, v1 = 0.f;
#pragma unroll
        for (int i = 0; i < 2; i++) {
            float c[4][4];
#pragma unroll
            for (int k = 0; k < 16; k++) (&c[0][0])[k] = 0.f;
            c[0][0] = v0; c[0][1] = v1;
            mbar_wait(sb + SM_FULL + (IT_WUV + i) * 8);
#pragma unroll
            for (int kk = 0; kk < 8; kk++) {
                uint32_t r0, r1, r2, r3;
                ldsm4t(base + slot_off(IT_WUV + i) + kk * 2048, r0, r1, r2, r3);
                mma16816(c[2 * (kk & 1)],     a[kk].x, a[kk].y, a[kk].z, a[kk].w, r0, r1);
                mma16816(c[2 * (kk & 1) + 1], a[kk].x, a[kk].y, a[kk].z, a[kk].w, r2, r3);
            }
            v0 = (c[0][0] + c[1][2]) + (c[2][0] + c[3][2]);
            v1 = (c[0][1] + c[1][3]) + (c[2][1] + c[3][3]);
            if (i == 0) { v0 = __shfl_xor_sync(0xffffffffu, v0, 16); v1 = __shfl_xor_sync(0xffffffffu, v1, 16); }
        }
        st_rlx_if(dst, pack_bf16(v0, v1), lane >= 16);
    }

    {
        const bool isB = slice >= 32, on = lane < 16;
        const int r = j & 1;
        const uint32_t xl = (isB ? t * 64 + (((g ^ (t & 2)) & 3) << 4) : (g & 3) * 256 + ((g & 1) * 4 + t) * 16) + (w & 1) * (isB ? 512 : 128);
        const uint32_t cs = isB ? 256 : 64;
        const uint32_t xo = r * 8192 + (w >> 1) * 1024, xz = (1 - r) * 12288 + ((w & 4) + (w >> 1 & 1)) * 1024;
        auto xoff = [&](int i) { return (i < 6 ? xo + (i >> 1) * 4096 : xz + (i >> 3) * 2048) + (xl ^ ((i & 1) * cs)); };
        const char* src = (const char*)gs->x[slice >> 5][r * 12];
        const int tt = (lane & 7) >> 1, row = 8 * tt + 2 * (((lane >> 2 & 2) + (lane >> 4) + tt) & 3) + (lane & 1);
        const uint32_t wl = row * 32 + (((r ^ (row >> 2)) & 1) << 4), own = sb + w * 2048 + wl;
        const uint32_t end = __shfl_sync(0xffffffffu, sb + (w < 4 ? slot_off(IT_WO + 3) : slot_off(IT_W2)) + (w & 3) * 2048 + wl, lane);
        const uint32_t ln  = __shfl_sync(0xffffffffu, sb + lane * 4, lane), l16 = __shfl_sync(0xffffffffu, sb + lane * 16, lane);
        const uint32_t fin = __shfl_sync(0xffffffffu, l16 + (w >> 2) * 512 + ((w ^ (lane >> 3)) & 3) * 4, lane);
        const uint32_t one = __shfl_sync(0xffffffffu, lane, 1);
        const uint64_t dst = __shfl_sync(0xffffffffu, (unsigned long long)(out + (g & 3) * 1024 + slice * 16 + r * 8 + t * 2 + (lane >> 4)), lane);
        uint32_t b[3][2][2][4];
        uint4 x[10];
        float c[4][4], d[4][4];
        auto load_w = [&](int i) {
            mbar_wait(sb + SM_FULL + (IT_WO + i) * 8);
#pragma unroll
            for (int q = 0; q < 4; q++) {
                uint32_t (&v)[4] = b[i][q >> 1][q & 1];
                ldsm4t(slot_off(IT_WO + i) + (q < 2 ? own ^ 16 : own) + (q & 1) * 1024, v[0], v[1], v[2], v[3]);
            }
        };
        auto mma_w = [&](float (&c)[4][4], int i, const uint32_t (&v)[2][4]) {
#pragma unroll
            for (int q = 0; q < 4; q++) {
                const uint4& a = x[2 * i + (q >> 1)];
                if (i == 0) c[q][0] = c[q][1] = c[q][2] = c[q][3] = 0.f;
                mma16816(c[q], a.x, a.y, a.z, a.w, v[q >> 1][(q & 1) * 2], v[q >> 1][(q & 1) * 2 + 1]);
            }
        };
        load_w(0); load_w(1);
        mbar_wait(sb + SM_FULL + BAR_X * 8);
#pragma unroll
        for (int i = 0; i < 10; i++) x[i] = lds128(sb + slot_off(IT_X) + xoff(i));
        int it = 0;
        while (true) {
            mma_w(d, 0, b[0][0]); mma_w(d, 1, b[1][0]);
            mma_w(c, 0, b[0][1]); mma_w(c, 1, b[1][1]);
            if (!refetch(x, [&](int i) { return src + xoff(i); })) break;
            if (++it > SPIN_LIMIT) __trap();
        }
        load_w(2);
        mma_w(d, 2, b[2][0]);
        stsf(fin + SM_SND, on ? ((d[0][0] + d[1][2]) + d[2][0]) + d[3][2] : ((d[0][1] + d[1][3]) + d[2][1]) + d[3][3]);
        asm volatile("bar.arrive 5, 288;" ::: "memory");
        mma_w(c, 2, b[2][1]);
        uint32_t v[2][4];
        mbar_wait(sb + SM_LAST + w * 16);
        ldsm4t(end, v[0][0], v[0][1], v[0][2], v[0][3]);
        ldsm4t(end + 1024, v[1][0], v[1][1], v[1][2], v[1][3]);
        mma_w(c, 3, v);
        mbar_wait(sb + SM_LAST + w * 16 + 8);
        ldsm4t(end + 8192, v[0][0], v[0][1], v[0][2], v[0][3]);
        ldsm4t(end + 9216, v[1][0], v[1][1], v[1][2], v[1][3]);
        const float pr = ldsf_if(ln + SM_RCV, w == 0);
        mma_w(c, 4, v);
        stv(fin + SM_FIN, on ? (((c[0][0] + pr) + c[1][2]) + c[2][0]) + c[3][2] : (((c[0][1] + pr) + c[1][3]) + c[2][1]) + c[3][3]);
        uint32_t rank;
        asm volatile("atom.relaxed.cta.shared.add.u32 %0, [%1], %2;" : "=r"(rank) : "r"(ln + SM_CNT), "r"(one) : "memory");
        float4 p0 = ldv4(l16 + SM_FIN), p1 = ldv4(l16 + SM_FIN + 512);
        const float sum = ((p0.x + p0.y) + (p0.z + p0.w)) + ((p1.x + p1.y) + (p1.z + p1.w));
        st_bf16_if(dst, sum, rank == 7);
        if (rank != 7 || sum == sum) return;
        auto mx = [](float4 q) { return max(max(__float_as_uint(q.x), __float_as_uint(q.y)), max(__float_as_uint(q.z), __float_as_uint(q.w))); };
        for (it = 0; max(mx(p0), mx(p1)) == EMPTY; it++) {
            p0 = ldv4(l16 + SM_FIN); p1 = ldv4(l16 + SM_FIN + 512);
            if (it > SPIN_LIMIT) __trap();
        }
        st_bf16_if(dst, ((p0.x + p0.y) + (p0.z + p0.w)) + ((p1.x + p1.y) + (p1.z + p1.w)), true);
    }
}

typedef CUresult (*EncodeTiledFn)(CUtensorMap*, CUtensorMapDataType, cuuint32_t, void*, const cuuint64_t*,
                                  const cuuint64_t*, const cuuint32_t*, const cuuint32_t*, CUtensorMapInterleave,
                                  CUtensorMapSwizzle, CUtensorMapL2promotion, CUtensorMapFloatOOBfill);

void encode_map(EncodeTiledFn enc, CUtensorMap* tm, const void* p, cuuint64_t cols, cuuint64_t rows,
                cuuint32_t brows, cuuint32_t bblk) {
    cuuint64_t dims[3] = {64, rows, cols / 64};
    cuuint64_t strides[2] = {cols * 2, 128};
    cuuint32_t box[3] = {64, brows, bblk};
    cuuint32_t es[3] = {1, 1, 1};
    enc(tm, CU_TENSOR_MAP_DATA_TYPE_BFLOAT16, 3, const_cast<void*>(p), dims, strides, box, es,
        CU_TENSOR_MAP_INTERLEAVE_NONE, CU_TENSOR_MAP_SWIZZLE_128B, CU_TENSOR_MAP_L2_PROMOTION_L2_256B,
        CU_TENSOR_MAP_FLOAT_OOB_FILL_NONE);
}

void encode_slice_map(EncodeTiledFn enc, CUtensorMap* tm, const void* p, cuuint64_t cols, cuuint64_t rows,
                      cuuint32_t bcols, cuuint32_t brows) {
    cuuint64_t dims[3] = {cols, 256, rows / 256};
    cuuint64_t strides[2] = {cols * 2, cols * 512};
    cuuint32_t box[3] = {bcols, brows, 1};
    cuuint32_t es[3] = {1, 1, 1};
    enc(tm, CU_TENSOR_MAP_DATA_TYPE_BFLOAT16, 3, const_cast<void*>(p), dims, strides, box, es, CU_TENSOR_MAP_INTERLEAVE_NONE,
        bcols == 16 ? CU_TENSOR_MAP_SWIZZLE_32B : CU_TENSOR_MAP_SWIZZLE_64B, CU_TENSOR_MAP_L2_PROMOTION_L2_128B,
        CU_TENSOR_MAP_FLOAT_OOB_FILL_NONE);
}

}

extern "C" void kernel_launch(void* const* d_in, const int* in_sizes, int n_in, void* d_out, int out_size) {
    (void)in_sizes; (void)n_in; (void)out_size;
    static EncodeTiledFn enc = nullptr;
    static Scratch* gs = nullptr;
    if (!enc) {
        cudaGetSymbolAddress((void**)&gs, g_scratch);
        void* fn = nullptr;
        cudaDriverEntryPointQueryResult qr;
        cudaGetDriverEntryPoint("cuTensorMapEncodeTiled", &fn, cudaEnableDefault, &qr);
        enc = (EncodeTiledFn)fn;
        cudaFuncSetAttribute(fused_decode_kernel, cudaFuncAttributeMaxDynamicSharedMemorySize, SM_END);
    }
    Maps maps;
    encode_map(enc, &maps.wuk, d_in[8], 4096, 512, 32, 2);
    encode_slice_map(enc, &maps.wuv, d_in[9], 4096, 512, 32, 128);
    encode_slice_map(enc, &maps.woB, d_in[10], 512, 4096, 16, 256);
    encode_slice_map(enc, &maps.woA, d_in[4], 512, 4096, 16, 256);
    encode_slice_map(enc, &maps.endB, d_in[10], 512, 4096, 16, 64);
    encode_slice_map(enc, &maps.endA, d_in[4], 512, 4096, 16, 64);
    encode_map(enc, &maps.ckv, d_in[6], 512, 16384, 8, 8);
    fused_decode_kernel<<<NCTA, NTHR, SM_END>>>((const __nv_bfloat16*)d_in[0], (const __nv_bfloat16*)d_in[5],
                                                (const __nv_bfloat16*)d_in[7], (const __nv_bfloat16*)d_in[3],
                                                (const __nv_bfloat16*)d_in[1] + 3072 * 128, (const __nv_bfloat16*)d_in[2] + 3072 * 128,
                                                (__nv_bfloat16*)d_out, gs, maps);
}
```

```cpp
#include <cuda_runtime.h>
#include <cuda_bf16.h>
#include <cuda.h>
#include <stdint.h>

namespace {

constexpr int NCTA   = 128;
constexpr int NSLOT  = 13;
constexpr int SLOT   = 16384;
constexpr int NITEM  = 56;
constexpr int NTHR   = 384;

constexpr int INFLIGHT = 4;
constexpr int PACE     = 644;
constexpr int LEAD     = 550;
constexpr int TAPER    = 260;
constexpr int OS0      = -161;
constexpr int OS1      = 241;
constexpr int OF0      = -241;
constexpr int OF1      = 460;
constexpr int OF2      = 1700;
constexpr int OF3      = 180;
constexpr int XS       = 1270;
constexpr int XF       = 1680;
constexpr int OPGAP    = 250;
constexpr int NWIN     = 4;
__device__ constexpr int win_pos(int k)  { return k == 0 ? 10 : k == 1 ? 20 : k == 2 ? 31 : 38; }
__device__ constexpr int win_late(int k) { return k == 0 ? 1860 : k == 1 ? 1880 : k == 2 ? 1870 : 1760; }
constexpr int GAIN     = 11;

constexpr int IT_WQB = 0, IT_WQA = 2, IT_WUK = 4, IT_K0 = 6, IT_Q = 14, IT_C = 16, IT_K1 = 24, IT_V0 = 32,
              IT_OP = 40, IT_V1 = 42, IT_WUV = 50, IT_WO = 52;
constexpr int IT_X = 56;
constexpr int BAR_LAT = 55;

constexpr int SM_FULL  = NSLOT * SLOT;
constexpr int SM_EMPTY = SM_FULL + 512;
constexpr int SM_IN0   = SM_EMPTY + 512;
constexpr int SM_IN1   = SM_IN0 + 1088;
constexpr int SM_SC    = SM_IN1 + 1088;
constexpr int SM_PA    = SM_SC + 4096;
constexpr int SM_PF    = SM_PA + 2048;
constexpr int SM_MX    = SM_PF + 8192;
constexpr int SM_ML    = SM_MX + 1024;
constexpr int SM_LAST  = SM_ML + 128;
constexpr int SM_CNT   = SM_LAST + 128;
constexpr int SM_RCV   = SM_CNT + 128;
constexpr int SM_PACE  = SM_RCV + 256;
constexpr int SM_END   = SM_PACE + 32;
constexpr int SM_LAT   = SM_PF + 4096;
constexpr int SM_FIN   = SM_SC;
constexpr int SM_SUM   = SM_IN0;
static_assert(SM_END <= 232448, "smem");

struct Maps { CUtensorMap wuk, wuv, woA, woB, ckv, endA, endB; };

struct Scratch {
    unsigned cnt[32];
    unsigned late[32];
    float    part[2][NCTA][512];
    uint32_t x[2][32][256];
    uint32_t lat[32][4][256];
    uint4    q[4][2048];
    uint4    op[NCTA][2048];
    float2   stat[32][128];
};
__device__ __align__(128) Scratch g_scratch;

constexpr int SPIN_LIMIT = 1 << 22;

__device__ __forceinline__ uint32_t smem_u32(const void* p) { return (uint32_t)__cvta_generic_to_shared(p); }
__device__ __forceinline__ void mbar_init(uint32_t bar, uint32_t cnt) {
    asm volatile("mbarrier.init.shared::cta.b64 [%0], %1;" ::"r"(bar), "r"(cnt) : "memory");
}
__device__ __forceinline__ void mbar_expect_tx(uint32_t bar, uint32_t bytes) {
    asm volatile("mbarrier.arrive.expect_tx.shared::cta.b64 _, [%0], %1;" ::"r"(bar), "r"(bytes) : "memory");
}
__device__ __forceinline__ void mbar_arrive(uint32_t bar) {
    asm volatile("mbarrier.arrive.shared::cta.b64 _, [%0];" ::"r"(bar) : "memory");
}
__device__ __forceinline__ void mbar_arrive8(uint32_t bar) {
    asm volatile("mbarrier.arrive.shared::cta.b64 _, [%0], 8;" ::"r"(bar) : "memory");
}
__device__ __forceinline__ void mbar_wait(uint32_t bar) {
    uint32_t done;
    int it = 0;
    do {
        asm volatile("{\n.reg .pred p;\nmbarrier.try_wait.parity.shared::cta.b64 p, [%1], 0;\nselp.u32 %0, 1, 0, p;\n}"
                     : "=r"(done) : "r"(bar) : "memory");
        if (++it > SPIN_LIMIT) __trap();
    } while (!done);
}
__device__ __forceinline__ uint32_t map_cta(uint32_t a, uint32_t rank) {
    uint32_t r; asm("mapa.shared::cluster.u32 %0, %1, %2;" : "=r"(r) : "r"(a), "r"(rank)); return r;
}
__device__ __forceinline__ void st_async64(uint32_t a, float x, float y, uint32_t bar) {
    asm volatile("st.async.shared::cluster.mbarrier::complete_tx::bytes.v2.f32 [%0], {%1,%2}, [%3];" ::"r"(a), "f"(x), "f"(y), "r"(bar) : "memory");
}
__device__ __forceinline__ uint64_t evict_first() {
    uint64_t pol; asm volatile("createpolicy.fractional.L2::evict_first.b64 %0, 1.0;" : "=l"(pol)); return pol;
}
#define ELECT "{\n.reg .pred p;\nelect.sync _|p, 0xffffffff;\n@p "
__device__ __forceinline__ void bulk_load(uint32_t dst, const void* src, uint32_t bytes, uint32_t bar, uint64_t pol) {
    asm volatile(ELECT "cp.async.bulk.shared::cluster.global.mbarrier::complete_tx::bytes.L2::cache_hint [%0], [%1], %2, [%3], %4;\n}"
                 ::"r"(dst), "l"(src), "r"(bytes), "r"(bar), "l"(pol) : "memory");
}
__device__ __forceinline__ void bulk_load_nohint(uint32_t dst, const void* src, uint32_t bytes, uint32_t bar) {
    asm volatile("cp.async.bulk.shared::cluster.global.mbarrier::complete_tx::bytes [%0], [%1], %2, [%3];"
                 ::"r"(dst), "l"(src), "r"(bytes), "r"(bar) : "memory");
}
__device__ __forceinline__ void tma3d(uint32_t dst, const CUtensorMap* tm, int c0, int c1, int c2, uint32_t bar, uint64_t pol) {
    asm volatile(ELECT "cp.async.bulk.tensor.3d.shared::cluster.global.mbarrier::complete_tx::bytes.L2::cache_hint [%0], [%1, {%3, %4, %5}], [%2], %6;\n}"
                 ::"r"(dst), "l"(tm), "r"(bar), "r"(c0), "r"(c1), "r"(c2), "l"(pol) : "memory");
}
__device__ __forceinline__ void ldsm4(uint32_t a, uint32_t& r0, uint32_t& r1, uint32_t& r2, uint32_t& r3) {
    asm volatile("ldmatrix.sync.aligned.m8n8.x4.shared.b16 {%0,%1,%2,%3}, [%4];"
                 : "=r"(r0), "=r"(r1), "=r"(r2), "=r"(r3) : "r"(a) : "memory");
}
__device__ __forceinline__ void ldsm4t(uint32_t a, uint32_t& r0, uint32_t& r1, uint32_t& r2, uint32_t& r3) {
    asm volatile("ldmatrix.sync.aligned.m8n8.x4.trans.shared.b16 {%0,%1,%2,%3}, [%4];"
                 : "=r"(r0), "=r"(r1), "=r"(r2), "=r"(r3) : "r"(a) : "memory");
}
__device__ __forceinline__ void mma16816(float (&c)[4], uint32_t a0, uint32_t a1, uint32_t a2, uint32_t a3,
                                         uint32_t b0, uint32_t b1) {
    asm volatile("mma.sync.aligned.m16n8k16.row.col.f32.bf16.bf16.f32 {%0,%1,%2,%3}, {%4,%5,%6,%7}, {%8,%9}, {%0,%1,%2,%3};"
                 : "+f"(c[0]), "+f"(c[1]), "+f"(c[2]), "+f"(c[3])
                 : "r"(a0), "r"(a1), "r"(a2), "r"(a3), "r"(b0), "r"(b1));
}
__device__ __forceinline__ uint32_t lds32(uint32_t a) {
    uint32_t v; asm volatile("ld.shared.b32 %0, [%1];" : "=r"(v) : "r"(a) : "memory"); return v;
}
__device__ __forceinline__ float ldsf(uint32_t a) {
    float v; asm volatile("ld.shared.f32 %0, [%1];" : "=f"(v) : "r"(a) : "memory"); return v;
}
__device__ __forceinline__ float2 ldsf2(uint32_t a) {
    float2 v; asm volatile("ld.shared.v2.f32 {%0,%1}, [%2];" : "=f"(v.x), "=f"(v.y) : "r"(a) : "memory"); return v;
}
__device__ __forceinline__ float4 ldsf4(uint32_t a) {
    float4 v; asm volatile("ld.shared.v4.f32 {%0,%1,%2,%3}, [%4];" : "=f"(v.x), "=f"(v.y), "=f"(v.z), "=f"(v.w) : "r"(a) : "memory"); return v;
}
__device__ __forceinline__ uint4 lds128(uint32_t a) {
    uint4 v; asm volatile("ld.shared.v4.b32 {%0,%1,%2,%3}, [%4];" : "=r"(v.x), "=r"(v.y), "=r"(v.z), "=r"(v.w) : "r"(a) : "memory"); return v;
}
__device__ __forceinline__ float ldsf_if(uint32_t a, bool on) {
    float v = 0.f;
    asm volatile("{\n.reg .pred p;\nsetp.ne.u32 p, %2, 0;\n@p ld.shared.f32 %0, [%1];\n}" : "+f"(v) : "r"(a), "r"((uint32_t)on) : "memory");
    return v;
}
__device__ __forceinline__ float4 ldv4(uint32_t a) {
    float4 v; asm volatile("ld.volatile.shared.v4.f32 {%0,%1,%2,%3}, [%4];" : "=f"(v.x), "=f"(v.y), "=f"(v.z), "=f"(v.w) : "r"(a) : "memory"); return v;
}
__device__ __forceinline__ void stv(uint32_t a, float v) { asm volatile("st.volatile.shared.f32 [%0], %1;" ::"r"(a), "f"(v) : "memory"); }
__device__ __forceinline__ void sts16(uint32_t a, uint16_t v) { asm volatile("st.shared.b16 [%0], %1;" ::"r"(a), "h"(v) : "memory"); }
__device__ __forceinline__ void sts32(uint32_t a, uint32_t v) { asm volatile("st.shared.b32 [%0], %1;" ::"r"(a), "r"(v) : "memory"); }
__device__ __forceinline__ void stsf(uint32_t a, float v) { asm volatile("st.shared.f32 [%0], %1;" ::"r"(a), "f"(v) : "memory"); }
__device__ __forceinline__ void sts64(uint32_t a, uint32_t x, uint32_t y) {
    asm volatile("st.shared.v2.b32 [%0], {%1,%2};" ::"r"(a), "r"(x), "r"(y) : "memory");
}
__device__ __forceinline__ void sts128(uint32_t a, uint4 v) {
    asm volatile("st.shared.v4.b32 [%0], {%1,%2,%3,%4};" ::"r"(a), "r"(v.x), "r"(v.y), "r"(v.z), "r"(v.w) : "memory");
}
__device__ __forceinline__ uint32_t pack_bf16(float lo, float hi) {
    uint32_t r; asm("cvt.rn.bf16x2.f32 %0, %1, %2;" : "=r"(r) : "f"(hi), "f"(lo)); return r;
}
__device__ __forceinline__ float bf_lo(uint32_t v) { return __uint_as_float(v << 16); }
__device__ __forceinline__ float bf_hi(uint32_t v) { return __uint_as_float(v & 0xffff0000u); }
__device__ __forceinline__ float ex2(float x) { float y; asm("ex2.approx.ftz.f32 %0, %1;" : "=f"(y) : "f"(x)); return y; }
__device__ __forceinline__ uint32_t timer_ns() { uint32_t t; asm volatile("mov.u32 %0, %%globaltimer_lo;" : "=r"(t)); return t; }
__device__ __forceinline__ void bar_consumers() { asm volatile("bar.sync 1, 256;" ::: "memory"); }

__device__ __forceinline__ uint32_t tagf(float v, uint32_t tag) { return (__float_as_uint(v) & 0xffffff00u) | tag; }
__device__ __forceinline__ uint2 ld_rlx2(const float* p) {
    uint2 v; asm volatile("ld.relaxed.gpu.global.v2.b32 {%0,%1}, [%2];" : "=r"(v.x), "=r"(v.y) : "l"(p) : "memory"); return v;
}
__device__ __forceinline__ float untag(uint32_t v) { return __uint_as_float(v & 0xffffff00u); }

__device__ __forceinline__ uint32_t slot_off(int item) { return (uint32_t)(item % NSLOT) * SLOT; }

template <bool TRANS, bool TMA = true>
__device__ __forceinline__ void tile_mma(uint32_t sb, int item, uint32_t in, int w, int lane, float (&acc)[2][2]) {
    const int g = lane >> 2, t = lane & 3;
    float c[4][4];
#pragma unroll
    for (int i = 0; i < 16; i++) (&c[0][0])[i] = 0.f;
    uint32_t a[16];
    const uint32_t ia = in + (g & 3) * 272 + t * 4;
#pragma unroll
    for (int i = 0; i < 16; i++) a[i] = lds32(ia + i * 16);
    const uint32_t s0 = sb + slot_off(item), s1 = sb + slot_off(item + 1);
    if (TRANS) {
        const int r = (lane & 7) + (lane & 8);
        const int ch = 2 * (w & 3) + (lane >> 4);
        const uint32_t off = (TMA ? (w >> 2) * 8192 + r * 128 : (w >> 2) * 128 + r * 256) + ((ch ^ (lane & 7)) << 4);
#pragma unroll
        for (int kk = 0; kk < 8; kk++) {
            if (TMA && (kk & 3) == 0) mbar_wait(sb + SM_FULL + (item + (kk >> 2)) * 8);
            uint32_t r0, r1, r2, r3;
            ldsm4t(((kk >> 2) ? s1 : s0) + off + (kk & 3) * (TMA ? 2048 : 4096), r0, r1, r2, r3);
            mma16816(c[2 * (kk & 1)],     a[2 * kk], 0u, a[2 * kk + 1], 0u, r0, r1);
            mma16816(c[2 * (kk & 1) + 1], a[2 * kk], 0u, a[2 * kk + 1], 0u, r2, r3);
        }
    } else {
        mbar_wait(sb + SM_FULL + (item + (w >> 2)) * 8);
        const int r = 16 * (w & 3) + (lane & 7) + ((lane >> 4) << 3);
        const uint32_t base = ((w >> 2) ? s1 : s0) + (r & 32) * 128 + r * 128 + ((((lane >> 3) & 1) ^ (lane & 7)) << 4);
#pragma unroll
        for (int kk = 0; kk < 8; kk++) {
            uint32_t r0, r1, r2, r3;
            ldsm4((base ^ ((kk & 3) << 5)) + (kk >> 2) * 4096, r0, r1, r2, r3);
            mma16816(c[2 * (kk & 1)],     a[2 * kk], 0u, a[2 * kk + 1], 0u, r0, r1);
            mma16816(c[2 * (kk & 1) + 1], a[2 * kk], 0u, a[2 * kk + 1], 0u, r2, r3);
        }
    }
    __syncwarp();
    if (lane == 0) {
        mbar_arrive(sb + SM_EMPTY + item * 8);
        mbar_arrive(sb + SM_EMPTY + (item + 1) * 8);
    }
    acc[0][0] = c[0][0] + c[2][0]; acc[0][1] = c[0][1] + c[2][1];
    acc[1][0] = c[1][0] + c[3][0]; acc[1][1] = c[1][1] + c[3][1];
}

__device__ __forceinline__ void publish(float* dst, int w, int lane, const float (&acc)[2][2], uint32_t tag) {
    if (lane < 16)
        asm volatile("st.relaxed.gpu.global.v4.b32 [%0], {%1,%2,%3,%4};" ::"l"(dst + w * 64 + lane * 4),
                     "r"(tagf(acc[0][0], tag)), "r"(tagf(acc[0][1], tag)), "r"(tagf(acc[1][0], tag)), "r"(tagf(acc[1][1], tag)) : "memory");
}

__device__ __forceinline__ void gather(const float* part, uint32_t in, int tid, uint32_t tag) {
    const float* p = part + tid * 2;
    uint2 v0, v1, v2, v3;
    int it = 0;
    while (true) {
        v0 = ld_rlx2(p); v1 = ld_rlx2(p + 512); v2 = ld_rlx2(p + 1024); v3 = ld_rlx2(p + 1536);
        uint32_t bad = ((v0.x ^ tag) | (v0.y ^ tag) | (v1.x ^ tag) | (v1.y ^ tag) |
                        (v2.x ^ tag) | (v2.y ^ tag) | (v3.x ^ tag) | (v3.y ^ tag)) & 0xffu;
        if (__all_sync(0xffffffffu, bad == 0)) break;
        if (++it > SPIN_LIMIT) __trap();
    }
    float x = (untag(v0.x) + untag(v1.x)) + (untag(v2.x) + untag(v3.x));
    float y = (untag(v0.y) + untag(v1.y)) + (untag(v2.y) + untag(v3.y));
    sts32(in + ((tid >> 3) & 3) * 272 + (tid >> 5) * 32 + (tid & 1) * 16 + (tid & 6) * 2, pack_bf16(x, y));
    bar_consumers();
}

constexpr uint32_t EMPTY = 0xffffffffu;
__device__ __forceinline__ void st_rlx(uint32_t* p, uint32_t v) {
    asm volatile("st.relaxed.gpu.global.b32 [%0], %1;" ::"l"(p), "r"(v) : "memory");
}
__device__ __forceinline__ void st_rlx_if(uint64_t p, uint32_t v, bool on) {
    asm volatile("{\n.reg .pred p;\nsetp.ne.u32 p, %2, 0;\n@p st.relaxed.gpu.global.b32 [%0], %1;\n}" ::"l"(p), "r"(v), "r"((uint32_t)on) : "memory");
}
__device__ __forceinline__ void st_if(uint64_t p, uint32_t v, bool on) {
    asm volatile("{\n.reg .pred p;\nsetp.ne.u32 p, %2, 0;\n@p st.global.b32 [%0], %1;\n}" ::"l"(p), "r"(v), "r"((uint32_t)on) : "memory");
}
__device__ __forceinline__ void st_rlx2(uint32_t* p, uint32_t v0, uint32_t v1) {
    asm volatile("st.relaxed.gpu.global.v2.b32 [%0], {%1,%2};" ::"l"(p), "r"(v0), "r"(v1) : "memory");
}
__device__ __forceinline__ void ld_rlx4_if(uint4& v, const void* p, bool need) {
    asm volatile("{\n.reg .pred p;\nsetp.ne.u32 p, %5, 0;\n@p ld.relaxed.gpu.global.v4.b32 {%0,%1,%2,%3}, [%4];\n}"
                 : "+r"(v.x), "+r"(v.y), "+r"(v.z), "+r"(v.w) : "l"(p), "r"((uint32_t)need) : "memory");
}

template <class F>
__device__ __forceinline__ bool refetch(uint4 (&x)[8], F addr) {
    uint32_t m[8], m0 = 0;
#pragma unroll
    for (int i = 0; i < 8; i++) {
        m[i] = max(max(x[i].x, x[i].y), max(x[i].z, x[i].w));
        m0 = max(m0, m[i]);
    }
    if (!__any_sync(0xffffffffu, m0 == EMPTY)) return false;
#pragma unroll
    for (int i = 0; i < 8; i++) ld_rlx4_if(x[i], addr(i), m[i] == EMPTY);
    return true;
}

__device__ __forceinline__ unsigned read_counter(const unsigned* cnt) {
    unsigned v;
    asm volatile("ld.relaxed.gpu.global.u32 %0, [%1];" : "=r"(v) : "l"(cnt) : "memory");
    return v;
}
__device__ __forceinline__ unsigned epoch_of(unsigned cnt) {
    asm volatile("" : "+r"(cnt) :: "memory");
    return cnt / NCTA + 1;
}
__device__ __forceinline__ uint32_t epoch_tag(unsigned epoch) { return (epoch & 0x7fu) | 0x80u; }

__device__ __forceinline__ void signal_and_wait(unsigned* cnt, unsigned target, int lane) {
    if (lane == 0) asm volatile("red.release.gpu.global.add.u32 [%0], 1;" ::"l"(cnt) : "memory");
    int it = 0;
    while (true) {
        unsigned v;
        asm volatile("ld.acquire.gpu.global.u32 %0, [%1];" : "=r"(v) : "l"(cnt) : "memory");
        if (__all_sync(0xffffffffu, (int)(v - target) >= 0)) break;
        if (++it > SPIN_LIMIT) __trap();
    }
    asm volatile("fence.proxy.async.global;" ::: "memory");
}

__global__ void __cluster_dims__(2, 1, 1) __launch_bounds__(NTHR, 1)
fused_decode_kernel(const __nv_bfloat16* __restrict__ xA, const __nv_bfloat16* __restrict__ xB,
                    const __nv_bfloat16* __restrict__ wqB, const __nv_bfloat16* __restrict__ wqA,
                    const __nv_bfloat16* __restrict__ Kc, const __nv_bfloat16* __restrict__ Vc,
                    __nv_bfloat16* __restrict__ out, Scratch* gs, const __grid_constant__ Maps maps) {
    extern __shared__ __align__(1024) unsigned char smem_raw[];
    const uint32_t sb = smem_u32(smem_raw);
    const int tid = threadIdx.x, lane = tid & 31;
    const int cta = blockIdx.x, h = cta >> 2, j = cta & 3;
    const size_t kv_off = (size_t)blockIdx.x * 4096 * 128;
    const uint32_t trow = threadIdx.x >> 4;
    const uint32_t tile_src = trow * (8192 - 256) + (threadIdx.x * 16 + ((blockIdx.x * 0x100040u) & 0x301f00u));
    const uint32_t tile_dst = sb + ((threadIdx.x ^ (trow & 7)) << 4);
    auto lsu_piece = [&](int k) {
#pragma unroll
        for (int q = 2 * k; q < 2 * k + 2; q++)
            asm volatile("cp.async.cg.shared.global [%0], [%1], 16;" ::"r"(tile_dst + q * 4096),
                         "l"(reinterpret_cast<const char*>((k < 4 ? wqB : wqA) + (q & 7) * 16 * 4096) + tile_src) : "memory");
        if ((k & 3) == 3) asm volatile("cp.async.commit_group;" ::: "memory");
    };
    if (tid < 256) {
#pragma unroll
        for (int k = 0; k < 4; k++) lsu_piece(k);
    }
    const uint32_t tz = timer_ns() - LEAD;
    unsigned cnt1;
    if (tid < 256) cnt1 = read_counter(&gs->cnt[1]);
    uint4 xv;
    if (tid < 128) {
        const __nv_bfloat16* x = (tid < 64 ? xB : xA) + ((tid >> 4) & 3) * 512 + j * 128 + (tid & 15) * 8;
        xv = __ldg(reinterpret_cast<const uint4*>(x));
    }
    const int w = __shfl_sync(0xffffffffu, tid >> 5, 0);
    const int pr = cta >> 1;
    const int slice = pr < 4 ? pr : pr < 36 ? 4 + ((pr - 4) & 7) * 4 + ((pr - 4) >> 3) : 36 + (pr - 36) % 7 * 4 + (pr - 36) / 7;

    if (w >= 8) {
        if (lane == 0) {
            const uint32_t full = sb + SM_FULL + (IT_WUK + (w & 3) * 14) * 8, empty = sb + SM_EMPTY + (w & 3) * 13 * 8,
                           last = sb + SM_LAST + (w & 3) * 32;
#pragma unroll
            for (int i = 0; i < 14; i++) mbar_init(full + i * 8, 1);
#pragma unroll
            for (int i = 0; i < 13; i++) mbar_init(empty + i * 8, 8);
#pragma unroll
            for (int i = 0; i < 4; i++) mbar_init(last + i * 8, 1);
#pragma unroll
            for (int i = 0; i < 14; i++) {
                const int b = IT_WUK + 42 + i;
                mbar_expect_tx(full + i * 8, (w == 10 && b - 14 == IT_OP) ? SLOT + 1024 : (w == 11 && b == BAR_LAT) ? 4096 : SLOT);
            }
#pragma unroll
            for (int i = 0; i < 4; i++) mbar_expect_tx(last + i * 8, i == 1 && w == 8 && !(j & 1) ? 2048 + 256 : 2048);
            asm volatile("fence.mbarrier_init.release.cluster;" ::: "memory");
            if (w == 10) sts64(sb + SM_PACE, tz, PACE * 16);
        }
        asm volatile("bar.sync 2, 128;" ::: "memory");
        asm volatile("bar.arrive 4, 384;" ::: "memory");
    }
    if (w == 10) {
        if (lane == 0) {
            int slope = 0;
#pragma unroll
            for (int k = 0; k < NWIN; k++) {
                const int c = win_pos(k);
                uint32_t acc = 0;
#pragma unroll
                for (int p = c; p < c + 4; p++) {
                    mbar_wait(sb + SM_FULL + (p < IT_Q ? p : p < IT_OP - 2 ? p + 2 : p + 4) * 8);
                    acc += timer_ns() - tz - p * PACE - ((p * slope) >> 4);
                }
                if (k == 0) mbar_wait(sb + SM_FULL + IT_Q * 8);
                asm volatile("red.relaxed.gpu.global.add.u32 [%0], %1;" ::"l"(&gs->late[k]), "r"((1u << 24) + min(acc >> 2, 65535u)) : "memory");
                uint32_t v;
                int it = 0;
                do { v = read_counter(&gs->late[k]); } while ((v >> 24) != NCTA && ++it < 1000);
                const int late = (v & 0xffffffu) / NCTA;
                slope = max(-320, min(320, slope + (late - win_late(k)) * (GAIN * 2) / (2 * c + 3)));
                sts64(sb + SM_PACE, tz, PACE * 16 + slope);
            }
        }
        return;
    }
    if (w >= 8) {
        auto wait_due = [&](uint32_t p, uint32_t shift) {
            uint32_t a, b;
            do {
                asm volatile("ld.volatile.shared.v2.b32 {%0,%1}, [%2];" : "=r"(a), "=r"(b) : "r"(sb + SM_PACE) : "memory");
            } while (__all_sync(0xffffffffu, (int)(timer_ns() - (a + ((p * b) >> 4) + shift)) < 0));
        };
        if (w != 9) {
            const int half = w & 1;
            const uint64_t pol = evict_first();
            int slot = IT_WUK, tail = IT_WUK - INFLIGHT;
            uint32_t np = IT_WUK, shift = half ? PACE / 4 : -(PACE / 4);
#pragma unroll 1
            for (int i = IT_WUK; i < NITEM; i++) {
                const uint32_t dst = sb + slot * SLOT + half * (SLOT / 2), bar = sb + SM_FULL + i * 8;
                if (++slot == NSLOT) slot = 0;
                if ((i & ~1) == IT_Q || (i & ~1) == IT_OP) continue;
                const bool ckv = i >= IT_C && i < IT_K1, wo = i >= IT_WO;
                const bool tiled = ckv || i < IT_K0 || i >= IT_WUV;
                const CUtensorMap* tm = &maps.wuk + (i < IT_K0 ? 0 : ckv ? 4 : wo ? 2 + (slice >> 5) : 1);
                const int c0 = wo ? (slice & 31) * 16 : i >= IT_WUV ? cta * 32 : 0;
                const int c1 = i < IT_K0 ? j * 128 + (i & 1) * 64 + half * 32 : ckv ? cta * 128 + (i - IT_C) * 16 + half * 8 : wo ? 0 : half * 128;
                const int c2 = i < IT_K0 ? h * 2 : ckv ? 0 : wo ? (j & 1) * 8 + (i - IT_WO) * 2 + half : i & 1;
                const int c = i < IT_Q ? i - IT_K0 : i < IT_V0 ? i - IT_K1 + 8 : i < IT_OP ? i - IT_V0 : i - IT_V1 + 8;
                const __nv_bfloat16* src = (i < IT_V0 ? Kc : Vc) + kv_off + (size_t)((c ^ (j & 1) * 7) * 2 + half) * (SLOT / 4);
                if (i >= NSLOT) mbar_wait(sb + SM_EMPTY + (i - NSLOT) * 8);
                if (tail >= IT_WUK && !wo) mbar_wait(sb + SM_FULL + tail * 8);
                ++tail;
                if (tail == IT_Q || tail == IT_OP) tail += 2;
                if (wo) {
                    const int n = c2 & 7;
                    np = IT_WO - 4;
                    shift = TAPER + ((j & 1) ? OS0 + n * OS1 : n < 4 ? OF0 + n * OF1 : OF2 + (n - 4) * OF3);
                }
                wait_due(np, shift);
                ++np;
                if (i == IT_WUV - 1) shift += TAPER;
                if (i >= NITEM - 2) {
#pragma unroll
                    for (int q = 0; q < 4; q++)
                        tma3d(dst + q * 2048, tm + 3, c0, q * 64, c2, sb + SM_LAST + half * 64 + q * 16 + (i & 1) * 8, pol);
                }
                else if (tiled) tma3d(dst, tm, c0, c1, c2, bar, pol);
                else bulk_load(dst, src, SLOT / 2, bar, pol);
            }
        } else {
            if (lane < sizeof(Maps) / 128) asm volatile("prefetch.tensormap [%0];" ::"l"(&maps.wuk + lane) : "memory");
            cnt1 = read_counter(&gs->cnt[1]);
            asm volatile("bar.sync 3, 288;" ::: "memory");
            const unsigned epoch = epoch_of(cnt1);
            signal_and_wait(&gs->cnt[0], epoch * NCTA, lane);
            if (lane == 0) {
                const uint4* q = gs->q[cta >> 5];
                bulk_load_nohint(sb + slot_off(IT_Q), q, SLOT, sb + SM_FULL + IT_Q * 8);
                bulk_load_nohint(sb + slot_off(IT_Q + 1), q + 1024, SLOT, sb + SM_FULL + (IT_Q + 1) * 8);
            }
            asm volatile("bar.sync 3, 288;" ::: "memory");
            signal_and_wait(&gs->cnt[1], epoch * NCTA, lane);
            mbar_wait(sb + SM_EMPTY + (IT_OP - NSLOT) * 8);
            mbar_wait(sb + SM_EMPTY + (IT_OP + 1 - NSLOT) * 8);
            if (lane == 0) {
                const uint4* op = gs->op[cta];
                bulk_load_nohint(sb + SM_MX, gs->stat[h], 1024, sb + SM_FULL + IT_OP * 8);
                uint32_t t1 = timer_ns();
#pragma unroll 1
                for (int i = 0; i < 8; i++) {
                    while ((int)(timer_ns() - t1) < 0) {}
                    t1 += OPGAP;
                    bulk_load_nohint(sb + slot_off(IT_OP) + i * 4096, op + i * 256, 4096, sb + SM_FULL + (IT_OP + i / 4) * 8);
                }
            }
            mbar_wait(sb + SM_FULL + (IT_V1 + 4) * 8);
            if (lane == 0) bulk_load_nohint(sb + SM_LAT, gs->lat[h], 4096, sb + SM_FULL + BAR_LAT * 8);
            mbar_wait(sb + SM_EMPTY + (IT_X - NSLOT) * 8);
            mbar_wait(sb + SM_FULL + (IT_WUV + 1) * 8);
            wait_due(IT_WO - 4, TAPER + ((j & 1) ? XS : XF));
            if (lane == 0) bulk_load_nohint(sb + slot_off(IT_X), gs->x[slice >> 5][(j & 1) * 16], SLOT, sb + SM_FULL + IT_X * 8);
        }
        return;
    }

    const int g = lane >> 2, t = lane & 3;
    const uint32_t in0 = sb + SM_IN0, in1 = sb + SM_IN1;
    const int ba = cta >> 5, ha = cta & 31;
    uint32_t* const ctx_dst = &gs->x[1][h][(j * 4 + (w & 3)) * 16 + ((g ^ (w & 2)) & 3) * 4 + ((t - w) & 3)];
    uint32_t* const o_dst = &gs->x[0][ha][ba * 64 + ((tid & 60) ^ ((ba & 1) * 16)) + ((t - g) & 3)];
    uint32_t* const lat_dst = &gs->lat[h][g & 3][j * 64 + ((w >> 1) ^ (g & 1)) * 16 + t * 4 + ((w * 2 ^ t) & 2)];
    {
#pragma unroll
        for (int k = 4; k < 8; k++) {
            while (__all_sync(0xffffffffu, (int)(timer_ns() - (tz + (2 * k - 1) * (PACE / 4))) < 0)) {}
            lsu_piece(k);
        }
        if (lane < 16) st_rlx2(lat_dst, EMPTY, EMPTY);
        if (lane >= 16 && w < 4) st_rlx(ctx_dst, EMPTY);
        if (w >= 6) st_rlx(o_dst, EMPTY);
        if (cta == 0 && w == 5) st_rlx(&gs->late[lane], 0u);
        if (tid < 128) sts128((tid < 64 ? in0 : in1) + ((tid >> 4) & 3) * 272 + (tid & 15) * 16, xv);
        asm volatile("cp.async.wait_group 1;" ::: "memory");
    }
    asm volatile("bar.sync 4, 384;" ::: "memory");
    const uint32_t tag = epoch_tag(epoch_of(cnt1));

    float acc[2][2];
    tile_mma<true, false>(sb, IT_WQB, in0, w, lane, acc);
    publish(gs->part[0][cta], w, lane, acc, tag);
    asm volatile("cp.async.wait_group 0;" ::: "memory");
    bar_consumers();
    tile_mma<true, false>(sb, IT_WQA, in1, w, lane, acc);
    publish(gs->part[1][cta], w, lane, acc, tag);
    bar_consumers();

    const float SC = 0.08838834764831845f * 1.4426950408889634f;
    gather(gs->part[0][h * 4], in0, tid, tag);
    tile_mma<false>(sb, IT_WUK, in0, w, lane, acc);
    if (lane < 16) {
        uint32_t* q = reinterpret_cast<uint32_t*>(gs->q[g]) + (2 * j + (w >> 2)) * 1024 + h * 32 + t;
        const int ch = 2 * (w & 3);
        q[((ch) ^ (h & 7)) * 4]     = pack_bf16(acc[0][0] * SC, acc[0][1] * SC);
        q[((ch + 1) ^ (h & 7)) * 4] = pack_bf16(acc[1][0] * SC, acc[1][1] * SC);
    }
    __syncwarp();
    asm volatile("bar.arrive 3, 288;" ::: "memory");
    gather(gs->part[1][ha * 4], in1, tid, tag);

    uint32_t qf[16];
#pragma unroll
    for (int c = 0; c < 8; c++) {
        qf[2 * c]     = lds32(in1 + ba * 272 + ((c ^ g) << 4) + t * 4);
        qf[2 * c + 1] = lds32(in1 + ba * 272 + 128 + ((c ^ g) << 4) + t * 4);
    }
    const uint32_t sc_w = sb + SM_SC + w * 512;
    auto k_item = [&](int item, uint32_t sc) {
        mbar_wait(sb + SM_FULL + item * 8);
        const uint32_t base = sb + slot_off(item) + ((lane & 7) + (lane & 8)) * 256 + ((lane >> 4) << 7);
        float s[4][4];
#pragma unroll
        for (int T = 0; T < 4; T++) { s[T][0] = s[T][1] = s[T][2] = s[T][3] = 0.f; }
#pragma unroll
        for (int c = 0; c < 8; c++) {
            const uint32_t a = base + ((c ^ (lane & 7)) << 4);
#pragma unroll
            for (int T = 0; T < 4; T++) {
                uint32_t r0, r1, r2, r3;
                ldsm4(a + T * 4096, r0, r1, r2, r3);
                mma16816(s[T], r0, r1, r2, r3, qf[2 * c], qf[2 * c + 1]);
            }
        }
        __syncwarp();
        if (lane == 0) mbar_arrive8(sb + SM_EMPTY + item * 8);
        if (t == (g >> 1)) {
#pragma unroll
            for (int T = 0; T < 4; T++) {
                stsf(sc + (16 * T + g) * 4,     (g & 1) ? s[T][1] : s[T][0]);
                stsf(sc + (16 * T + g + 8) * 4, (g & 1) ? s[T][3] : s[T][2]);
            }
        }
    };
    k_item(IT_K0 + w, sc_w);

    {
        float s[2][2][4];
#pragma unroll
        for (int i = 0; i < 16; i++) (&s[0][0][0])[i] = 0.f;
        mbar_wait(sb + SM_FULL + IT_Q * 8);
        mbar_wait(sb + SM_FULL + (IT_Q + 1) * 8);
        mbar_wait(sb + SM_FULL + (IT_C + w) * 8);
        const uint32_t cb0 = sb + slot_off(IT_C + w) + (lane & 7) * 128 + (lane >> 4) * 8192;
        const uint32_t cx = (((lane >> 3) & 1) ^ (lane & 7)) << 4;
        const uint32_t qr = ((lane & 7) + (lane & 8)) * 128;
        const uint32_t qx = ((lane >> 4) ^ (lane & 7)) << 4;
#pragma unroll
        for (int cb = 0; cb < 8; cb++) {
            const uint32_t qb = sb + slot_off(IT_Q + (cb >> 2)) + (cb & 3) * 4096 + qr;
#pragma unroll
            for (int k4 = 0; k4 < 4; k4++) {
                uint32_t b0, b1, b2, b3, a0, a1, a2, a3;
                ldsm4(cb0 + cb * 1024 + (cx ^ (k4 << 5)), b0, b1, b2, b3);
                ldsm4(qb + (qx ^ (k4 << 5)), a0, a1, a2, a3);
                mma16816(s[0][0], a0, a1, a2, a3, b0, b1);
                mma16816(s[0][1], a0, a1, a2, a3, b2, b3);
                ldsm4(qb + 2048 + (qx ^ (k4 << 5)), a0, a1, a2, a3);
                mma16816(s[1][0], a0, a1, a2, a3, b0, b1);
                mma16816(s[1][1], a0, a1, a2, a3, b2, b3);
            }
        }
        __syncwarp();
        if (lane == 0) { mbar_arrive(sb + SM_EMPTY + IT_Q * 8); mbar_arrive(sb + SM_EMPTY + (IT_Q + 1) * 8); }
#pragma unroll
        for (int r = 0; r < 4; r++) {
            const int mt = r >> 1, hi = (r & 1) * 2;
            float m = fmaxf(fmaxf(s[mt][0][hi], s[mt][0][hi + 1]), fmaxf(s[mt][1][hi], s[mt][1][hi + 1]));
            m = fmaxf(m, __shfl_xor_sync(0xffffffffu, m, 1));
            m = fmaxf(m, __shfl_xor_sync(0xffffffffu, m, 2));
            if (t == 0) stsf(sb + SM_MX + (8 * r + g) * 32 + w * 4, m);
        }
        bar_consumers();
        uint32_t pf[2][4];
#pragma unroll
        for (int r = 0; r < 4; r++) {
            const int mt = r >> 1, hi = r & 1;
            const float4 m0 = ldsf4(sb + SM_MX + (8 * r + g) * 32), m1 = ldsf4(sb + SM_MX + (8 * r + g) * 32 + 16);
            const float m = fmaxf(fmaxf(fmaxf(m0.x, m0.y), fmaxf(m0.z, m0.w)), fmaxf(fmaxf(m1.x, m1.y), fmaxf(m1.z, m1.w)));
            const uint32_t p0 = pack_bf16(ex2(s[mt][0][2 * hi] - m), ex2(s[mt][0][2 * hi + 1] - m));
            const uint32_t p1 = pack_bf16(ex2(s[mt][1][2 * hi] - m), ex2(s[mt][1][2 * hi + 1] - m));
            pf[mt][hi] = p0; pf[mt][2 + hi] = p1;
            float l = (bf_lo(p0) + bf_hi(p0)) + (bf_lo(p1) + bf_hi(p1));
            l += __shfl_xor_sync(0xffffffffu, l, 1);
            l += __shfl_xor_sync(0xffffffffu, l, 2);
            if (t == 0) stsf(sb + SM_SUM + (8 * r + g) * 32 + w * 4, l);
        }
        sts128(sb + SM_PF + (w * 2 + 0) * 512 + lane * 16, make_uint4(pf[0][0], pf[0][1], pf[0][2], pf[0][3]));
        sts128(sb + SM_PF + (w * 2 + 1) * 512 + lane * 16, make_uint4(pf[1][0], pf[1][1], pf[1][2], pf[1][3]));
        bar_consumers();
        if (w == 0) {
            const float4 m0 = ldsf4(sb + SM_MX + lane * 32), m1 = ldsf4(sb + SM_MX + lane * 32 + 16);
            const float4 l0 = ldsf4(sb + SM_SUM + lane * 32), l1 = ldsf4(sb + SM_SUM + lane * 32 + 16);
            const float m = fmaxf(fmaxf(fmaxf(m0.x, m0.y), fmaxf(m0.z, m0.w)), fmaxf(fmaxf(m1.x, m1.y), fmaxf(m1.z, m1.w)));
            const float l = ((l0.x + l0.y) + (l0.z + l0.w)) + ((l1.x + l1.y) + (l1.z + l1.w));
            gs->stat[lane][cta] = make_float2(m, l);
        }
        float o[2][8][4];
#pragma unroll
        for (int i = 0; i < 64; i++) (&o[0][0][0])[i] = 0.f;
        const uint32_t vr = w * 1024 + (lane & 7) * 128 + (lane & 8) * 1024;
        const uint32_t vx = ((lane >> 4) ^ (lane & 7)) << 4;
#pragma unroll
        for (int ks = 0; ks < 8; ks++) {
            const uint4 p0 = lds128(sb + SM_PF + (ks * 2 + 0) * 512 + lane * 16);
            const uint4 p1 = lds128(sb + SM_PF + (ks * 2 + 1) * 512 + lane * 16);
            const uint32_t vb = sb + slot_off(IT_C + ks) + vr;
#pragma unroll
            for (int n2 = 0; n2 < 4; n2++) {
                uint32_t b0, b1, b2, b3;
                ldsm4t(vb + (vx ^ (n2 << 5)), b0, b1, b2, b3);
                mma16816(o[0][2 * n2],     p0.x, p0.y, p0.z, p0.w, b0, b1);
                mma16816(o[0][2 * n2 + 1], p0.x, p0.y, p0.z, p0.w, b2, b3);
                mma16816(o[1][2 * n2],     p1.x, p1.y, p1.z, p1.w, b0, b1);
                mma16816(o[1][2 * n2 + 1], p1.x, p1.y, p1.z, p1.w, b2, b3);
            }
            __syncwarp();
            if (lane == 0) mbar_arrive(sb + SM_EMPTY + (IT_C + ks) * 8);
        }
        mbar_wait(sb + SM_FULL + (IT_K1 + 1 + (w * 3 >> 2)) * 8);
#pragma unroll
        for (int r = 0; r < 4; r++) {
            const int mt = r >> 1, hi = (r & 1) * 2;
            uint4* dst = gs->op[(8 * r + g) * 4 + (w >> 1)] + (cta >> 6) * 1024 + (w & 1) * 512 + (cta & 63) * 8;
#pragma unroll
            for (int u = 0; u < 2; u++) {
                uint4 v;
                v.x = pack_bf16(o[mt][4 * u][hi],     o[mt][4 * u][hi + 1]);
                v.y = pack_bf16(o[mt][4 * u + 1][hi], o[mt][4 * u + 1][hi + 1]);
                v.z = pack_bf16(o[mt][4 * u + 2][hi], o[mt][4 * u + 2][hi + 1]);
                v.w = pack_bf16(o[mt][4 * u + 3][hi], o[mt][4 * u + 3][hi + 1]);
                dst[(t + 4 * u) ^ (cta & 7)] = v;
            }
        }
        asm volatile("bar.arrive 3, 288;" ::: "memory");
    }

    k_item(IT_K1 + w, sc_w + 256);
    __syncwarp();
    {
        const float4 s = ldsf4(sc_w + lane * 16);
        float m = fmaxf(fmaxf(s.x, s.y), fmaxf(s.z, s.w));
#pragma unroll
        for (int d = 1; d < 32; d <<= 1) m = fmaxf(m, __shfl_xor_sync(0xffffffffu, m, d));
        if (lane == 0) stsf(sb + SM_ML + w * 4, m);
        bar_consumers();
        const float4 m0 = ldsf4(sb + SM_ML), m1 = ldsf4(sb + SM_ML + 16);
        m = fmaxf(fmaxf(fmaxf(m0.x, m0.y), fmaxf(m0.z, m0.w)), fmaxf(fmaxf(m1.x, m1.y), fmaxf(m1.z, m1.w))) * SC;
        const uint32_t p0 = pack_bf16(ex2(fmaf(s.x, SC, -m)), ex2(fmaf(s.y, SC, -m)));
        const uint32_t p1 = pack_bf16(ex2(fmaf(s.z, SC, -m)), ex2(fmaf(s.w, SC, -m)));
        float l = (bf_lo(p0) + bf_hi(p0)) + (bf_lo(p1) + bf_hi(p1));
#pragma unroll
        for (int d = 1; d < 32; d <<= 1) l += __shfl_xor_sync(0xffffffffu, l, d);
        if (lane == 0) stsf(sb + SM_ML + 32 + w * 4, l);
        sts64(sb + SM_PA + w * 256 + lane * 8, p0, p1);
        __syncwarp();
    }

    float oa[4][4];
#pragma unroll
    for (int i = 0; i < 16; i++) (&oa[0][0])[i] = 0.f;
    auto v_item = [&](int item, uint32_t pa) {
        uint32_t p[8];
#pragma unroll
        for (int i = 0; i < 8; i++) p[i] = lds32(pa + i * 16 + t * 4);
        mbar_wait(sb + SM_FULL + item * 8);
        const uint32_t base = sb + slot_off(item) + ((lane & 7) + ((lane >> 4) << 3)) * 256 + ((lane & 8) << 4);
#pragma unroll
        for (int c = 0; c < 8; c++) {
            const uint32_t a = base + ((c ^ (lane & 7)) << 4);
            const uint32_t mask = ((c == (g ^ (2 * t))) ? 0x0000ffffu : 0u) | ((c == (g ^ (2 * t + 1))) ? 0xffff0000u : 0u);
#pragma unroll
            for (int T = 0; T < 4; T++) {
                uint32_t r0, r1, r2, r3;
                ldsm4t(a + T * 4096, r0, r1, r2, r3);
                mma16816(oa[T], r0, r1, r2, r3, p[2 * T] & mask, p[2 * T + 1] & mask);
            }
        }
        __syncwarp();
        if (lane == 0) mbar_arrive8(sb + SM_EMPTY + item * 8);
    };
    sts64(sb + SM_FIN + tid * 8, EMPTY, EMPTY);
    if (w == 0) sts32(sb + SM_CNT + lane * 4, 0u);
    v_item(IT_V0 + w, sb + SM_PA + w * 256);

    mbar_wait(sb + SM_FULL + IT_OP * 8);
    if (w < 4) {
        const float2 st = ldsf2(sb + SM_MX + tid * 8);
        float m = st.x;
#pragma unroll
        for (int d = 1; d < 32; d <<= 1) m = fmaxf(m, __shfl_xor_sync(0xffffffffu, m, d));
        const uint32_t wb = pack_bf16(ex2(st.x - m), 0.f);
        float l = bf_lo(wb) * st.y;
#pragma unroll
        for (int d = 1; d < 32; d <<= 1) l += __shfl_xor_sync(0xffffffffu, l, d);
#pragma unroll
        for (int bb = 0; bb < 4; bb++) sts16(in0 + bb * 272 + tid * 2, bb == w ? (uint16_t)wb : (uint16_t)0);
        if (lane == 0) stsf(sb + SM_ML + 64 + w * 4, 1.f / l);
    }
    bar_consumers();
    tile_mma<true>(sb, IT_OP, in0, w, lane, acc);
    if (lane < 16) {
        const float inv = ldsf(sb + SM_ML + 64 + g * 4);
        const uint32_t v0 = pack_bf16(acc[0][0] * inv, acc[0][1] * inv), v1 = pack_bf16(acc[1][0] * inv, acc[1][1] * inv);
        st_rlx2(lat_dst, (t & 1) ? v1 : v0, (t & 1) ? v0 : v1);
    }

    {
        const float4 l0 = ldsf4(sb + SM_ML + 32), l1 = ldsf4(sb + SM_ML + 48);
        const float inv = 1.f / (((l0.x + l0.y) + (l0.z + l0.w)) + ((l1.x + l1.y) + (l1.z + l1.w)));
        v_item(IT_V1 + w, sb + SM_PA + w * 256 + 128);
        const uint32_t so = sb + SM_PF + w * 512 + (16 * t + g) * 4;
        stsf(so,       (oa[0][0] + oa[1][0]) + (oa[2][0] + oa[3][0]));
        stsf(so + 32,  (oa[0][1] + oa[1][1]) + (oa[2][1] + oa[3][1]));
        stsf(so + 256, (oa[0][2] + oa[1][2]) + (oa[2][2] + oa[3][2]));
        stsf(so + 288, (oa[0][3] + oa[1][3]) + (oa[2][3] + oa[3][3]));
        if (w < 6) {
            asm volatile("bar.arrive 1, 256;" ::: "memory");
        } else {
            bar_consumers();
            float x = 0.f, y = 0.f;
#pragma unroll
            for (int i = 0; i < 8; i++) {
                const float2 v = ldsf2(sb + SM_PF + i * 512 + (tid & 63) * 8);
                x += v.x; y += v.y;
            }
            st_rlx(o_dst, pack_bf16(x * inv, y * inv));
        }
    }

    if (w < 4) {
        const uint32_t lo = (g & 3) * 1024 + (g >> 2) * 512 + (g & 1) * 64 + t * 16;
        const int wd = ((lane >> 2 & 2) + (lane >> 4)) ^ (lane >> 1 & 3);
        const uint32_t base = sb + ((lane & 6) * 4 + wd * 2 + (lane & 1)) * 64 + (((w ^ wd) & 3) << 4);
        const uint64_t dst = __shfl_sync(0xffffffffu, (unsigned long long)ctx_dst, lane);
        mbar_wait(sb + SM_FULL + BAR_LAT * 8);
        uint4 a[8];
#pragma unroll
        for (int i = 0; i < 8; i++) a[i] = lds128(sb + SM_LAT + (lo ^ (i * 64)));
        int it = 0;
        while (refetch(a, [&](int i) { return (const char*)gs->lat[h] + (lo ^ (i * 64)); }))
            if (++it > SPIN_LIMIT) __trap();
        float v0 = 0.f, v1 = 0.f;
#pragma unroll
        for (int i = 0; i < 2; i++) {
            float c[4][4];
#pragma unroll
            for (int k = 0; k < 16; k++) (&c[0][0])[k] = 0.f;
            c[0][0] = v0; c[0][1] = v1;
            mbar_wait(sb + SM_FULL + (IT_WUV + i) * 8);
#pragma unroll
            for (int kk = 0; kk < 8; kk++) {
                uint32_t r0, r1, r2, r3;
                ldsm4t(base + slot_off(IT_WUV + i) + kk * 2048, r0, r1, r2, r3);
                mma16816(c[2 * (kk & 1)],     a[kk].x, a[kk].y, a[kk].z, a[kk].w, r0, r1);
                mma16816(c[2 * (kk & 1) + 1], a[kk].x, a[kk].y, a[kk].z, a[kk].w, r2, r3);
            }
            v0 = (c[0][0] + c[1][2]) + (c[2][0] + c[3][2]);
            v1 = (c[0][1] + c[1][3]) + (c[2][1] + c[3][3]);
            if (i == 0) { v0 = __shfl_xor_sync(0xffffffffu, v0, 16); v1 = __shfl_xor_sync(0xffffffffu, v1, 16); }
        }
        st_rlx_if(dst, pack_bf16(v0, v1), lane >= 16);
    }

    {
        const bool isB = slice >= 32;
        const int r = j & 1;
        const uint32_t cs = isB ? 256 : 64;
        const uint32_t xl = (isB ? t * 64 + (((g ^ (t & 2)) & 3) << 4) : (g & 3) * 256 + ((g & 1) * 4 + t) * 16) + (w >> 1) * 1024 + (w & 1) * 2 * cs;
        auto xoff = [&](int i) { return (i >> 1) * 4096 + (xl ^ ((i & 1) * cs)); };
        const char* src = (const char*)gs->x[slice >> 5][r * 16];
        uint32_t off[2];
#pragma unroll
        for (int u = 0; u < 2; u++) {
            const int tt = (lane & 7) >> 1, row = 8 * tt + 2 * ((2 * u + (lane >> 4) + tt) & 3) + (lane & 1);
            off[u] = sb + w * 2048 + row * 32 + ((((lane >> 3) ^ (row >> 2)) & 1) << 4);
        }
        const uint32_t fin = __shfl_sync(0xffffffffu, sb + SM_FIN + (g & 1) * 1024 + (w >> 2) * 512 + (t & 1) * 256 + (t >> 1) * 64 +
                                                      (g >> 1) * 16 + ((w ^ (t * 2) ^ (g & 1)) & 3) * 4, lane);
        const uint32_t rcv = __shfl_sync(0xffffffffu, sb + SM_RCV + (t & 1) * 128 + (t >> 1) * 32 + g * 4, lane);
        const uint32_t cnt = __shfl_sync(0xffffffffu, sb + SM_CNT + lane * 4, lane), sum = __shfl_sync(0xffffffffu, sb + SM_FIN + lane * 16, lane);
        const uint32_t inc = __shfl_sync(0xffffffffu, lane, 1 + r);
        const uint64_t dst = __shfl_sync(0xffffffffu, (unsigned long long)(out + (lane >> 3) * 1024 + slice * 16 + (lane & 7) * 2), lane);
        uint32_t a[2][4][4];
        uint4 x[8];
        float c[4][4];
        auto load_w = [&](int i) {
            mbar_wait(i < 2 ? sb + SM_FULL + (IT_WO + i) * 8 : sb + SM_LAST + w * 16 + (i & 1) * 8);
#pragma unroll
            for (int q = 0; q < 4; q++)
                ldsm4t(slot_off(IT_WO + i) + off[q & 1] + (q >> 1) * 1024, a[i & 1][q][0], a[i & 1][q][1], a[i & 1][q][2], a[i & 1][q][3]);
        };
        auto mma_w = [&](int i) {
#pragma unroll
            for (int q = 0; q < 4; q++) {
                const uint4& b = x[2 * i + (q >> 1)];
                if (i == 0) c[q][0] = c[q][1] = c[q][2] = c[q][3] = 0.f;
                mma16816(c[q], a[i & 1][q][0], a[i & 1][q][1], a[i & 1][q][2], a[i & 1][q][3], (q & 1) ? b.z : b.x, (q & 1) ? b.w : b.y);
            }
        };
        load_w(0); load_w(1);
        mbar_wait(sb + SM_FULL + IT_X * 8);
#pragma unroll
        for (int i = 0; i < 8; i++) x[i] = lds128(sb + slot_off(IT_X) + xoff(i));
        int it = 0;
        while (true) {
            mma_w(0); mma_w(1);
            if (!refetch(x, [&](int i) { return src + xoff(i); })) break;
            if (++it > SPIN_LIMIT) __trap();
        }
        load_w(2);
        mma_w(2);
        load_w(3);
        const float pr[2] = {ldsf_if(rcv, w == 0 && r == 0), ldsf_if(rcv + 64, w == 0 && r == 0)};
        mma_w(3);
#pragma unroll
        for (int e = 0; e < 2; e++)
            stv(fin + e * 128, t < 2 ? (((c[0][e] + pr[e]) + c[1][e]) + c[2][e]) + c[3][e]
                                     : (((c[0][e + 2] + pr[e]) + c[1][e + 2]) + c[2][e + 2]) + c[3][e + 2]);
        uint32_t rank;
        asm volatile("atom.relaxed.cta.shared.add.u32 %0, [%1], %2;" : "=r"(rank) : "r"(cnt), "r"(inc) : "memory");
        float4 p[4];
        float s0, s1;
        auto add_up = [&]() {
#pragma unroll
            for (int k = 0; k < 4; k++) p[k] = ldv4(sum + k * 512);
            s0 = ((p[0].x + p[0].y) + (p[0].z + p[0].w)) + ((p[1].x + p[1].y) + (p[1].z + p[1].w));
            s1 = ((p[2].x + p[2].y) + (p[2].z + p[2].w)) + ((p[3].x + p[3].y) + (p[3].z + p[3].w));
        };
        add_up();
        st_if(dst, pack_bf16(s0, s1), rank == 7);
        if (rank != ((s0 != s0 || s1 != s1) ? 7 * inc : 14)) return;
        auto mx = [](float4 q) { return max(max(__float_as_uint(q.x), __float_as_uint(q.y)), max(__float_as_uint(q.z), __float_as_uint(q.w))); };
        for (it = 0; max(max(mx(p[0]), mx(p[1])), max(mx(p[2]), mx(p[3]))) == EMPTY; it++) {
            add_up();
            if (it > SPIN_LIMIT) __trap();
        }
        if (r) st_async64(map_cta(sb + SM_RCV + lane * 8, 0), s0, s1, map_cta(sb + SM_LAST + 8, 0));
        else st_if(dst, pack_bf16(s0, s1), true);
    }
}

typedef CUresult (*EncodeTiledFn)(CUtensorMap*, CUtensorMapDataType, cuuint32_t, void*, const cuuint64_t*,
                                  const cuuint64_t*, const cuuint32_t*, const cuuint32_t*, CUtensorMapInterleave,
                                  CUtensorMapSwizzle, CUtensorMapL2promotion, CUtensorMapFloatOOBfill);

void encode_map(EncodeTiledFn enc, CUtensorMap* tm, const void* p, cuuint64_t cols, cuuint64_t rows,
                cuuint32_t brows, cuuint32_t bblk) {
    cuuint64_t dims[3] = {64, rows, cols / 64};
    cuuint64_t strides[2] = {cols * 2, 128};
    cuuint32_t box[3] = {64, brows, bblk};
    cuuint32_t es[3] = {1, 1, 1};
    enc(tm, CU_TENSOR_MAP_DATA_TYPE_BFLOAT16, 3, const_cast<void*>(p), dims, strides, box, es,
        CU_TENSOR_MAP_INTERLEAVE_NONE, CU_TENSOR_MAP_SWIZZLE_128B, CU_TENSOR_MAP_L2_PROMOTION_L2_256B,
        CU_TENSOR_MAP_FLOAT_OOB_FILL_NONE);
}

void encode_slice_map(EncodeTiledFn enc, CUtensorMap* tm, const void* p, cuuint64_t cols, cuuint64_t rows,
                      cuuint32_t bcols, cuuint32_t brows) {
    cuuint64_t dims[3] = {cols, 256, rows / 256};
    cuuint64_t strides[2] = {cols * 2, cols * 512};
    cuuint32_t box[3] = {bcols, brows, 1};
    cuuint32_t es[3] = {1, 1, 1};
    enc(tm, CU_TENSOR_MAP_DATA_TYPE_BFLOAT16, 3, const_cast<void*>(p), dims, strides, box, es, CU_TENSOR_MAP_INTERLEAVE_NONE,
        bcols == 16 ? CU_TENSOR_MAP_SWIZZLE_32B : CU_TENSOR_MAP_SWIZZLE_64B, CU_TENSOR_MAP_L2_PROMOTION_L2_128B,
        CU_TENSOR_MAP_FLOAT_OOB_FILL_NONE);
}

}

extern "C" void kernel_launch(void* const* d_in, const int* in_sizes, int n_in, void* d_out, int out_size) {
    (void)in_sizes; (void)n_in; (void)out_size;
    static EncodeTiledFn enc = nullptr;
    static Scratch* gs = nullptr;
    if (!enc) {
        cudaGetSymbolAddress((void**)&gs, g_scratch);
        void* fn = nullptr;
        cudaDriverEntryPointQueryResult qr;
        cudaGetDriverEntryPoint("cuTensorMapEncodeTiled", &fn, cudaEnableDefault, &qr);
        enc = (EncodeTiledFn)fn;
        cudaFuncSetAttribute(fused_decode_kernel, cudaFuncAttributeMaxDynamicSharedMemorySize, SM_END);
    }
    Maps maps;
    encode_map(enc, &maps.wuk, d_in[8], 4096, 512, 32, 2);
    encode_slice_map(enc, &maps.wuv, d_in[9], 4096, 512, 32, 128);
    encode_slice_map(enc, &maps.woB, d_in[10], 512, 4096, 16, 256);
    encode_slice_map(enc, &maps.woA, d_in[4], 512, 4096, 16, 256);
    encode_slice_map(enc, &maps.endB, d_in[10], 512, 4096, 16, 64);
    encode_slice_map(enc, &maps.endA, d_in[4], 512, 4096, 16, 64);
    encode_map(enc, &maps.ckv, d_in[6], 512, 16384, 8, 8);
    fused_decode_kernel<<<NCTA, NTHR, SM_END>>>((const __nv_bfloat16*)d_in[0], (const __nv_bfloat16*)d_in[5],
                                                (const __nv_bfloat16*)d_in[7], (const __nv_bfloat16*)d_in[3],
                                                (const __nv_bfloat16*)d_in[1] + 3072 * 128, (const __nv_bfloat16*)d_in[2] + 3072 * 128,
                                                (__nv_bfloat16*)d_out, gs, maps);
}
```

```cpp
#include <cuda_runtime.h>
#include <cuda_bf16.h>
#include <cuda.h>
#include <stdint.h>

namespace {

constexpr int NCTA   = 128;
constexpr int NSLOT  = 13;
constexpr int SLOT   = 16384;
constexpr int NITEM  = 56;
constexpr int NTHR   = 384;

constexpr int INFLIGHT = 4;
constexpr int PACE     = 644;
constexpr int LEAD     = 530;
constexpr int TAPER    = 260;
constexpr int OS0      = -120;
constexpr int OS1      = 241;
constexpr int OF0      = -241;
constexpr int OF1      = 460;
constexpr int OF2      = 1700;
constexpr int OF3      = 180;
constexpr int XS       = 1310;
constexpr int XF       = 1680;
constexpr int OPGAP    = 250;
constexpr int NWIN     = 4;
__device__ constexpr int win_pos(int k)  { return k == 0 ? 10 : k == 1 ? 20 : k == 2 ? 31 : 38; }
__device__ constexpr int win_late(int k) { return k == 0 ? 1835 : k == 1 ? 1855 : k == 2 ? 1845 : 1735; }
constexpr int GAIN     = 11;

constexpr int IT_WQB = 0, IT_WQA = 2, IT_WUK = 4, IT_K0 = 6, IT_Q = 14, IT_C = 16, IT_K1 = 24, IT_V0 = 32,
              IT_OP = 40, IT_V1 = 42, IT_WUV = 50, IT_WO = 52;
constexpr int IT_X = 56;
constexpr int BAR_LAT = 55;

constexpr int SM_FULL  = NSLOT * SLOT;
constexpr int SM_EMPTY = SM_FULL + 512;
constexpr int SM_IN0   = SM_EMPTY + 512;
constexpr int SM_IN1   = SM_IN0 + 1088;
constexpr int SM_SC    = SM_IN1 + 1088;
constexpr int SM_PA    = SM_SC + 4096;
constexpr int SM_PF    = SM_PA + 2048;
constexpr int SM_MX    = SM_PF + 8192;
constexpr int SM_ML    = SM_MX + 1024;
constexpr int SM_LAST  = SM_ML + 128;
constexpr int SM_CNT   = SM_LAST + 128;
constexpr int SM_RCV   = SM_CNT + 128;
constexpr int SM_PACE  = SM_RCV + 256;
constexpr int SM_END   = SM_PACE + 32;
constexpr int SM_LAT   = SM_PF + 4096;
constexpr int SM_FIN   = SM_SC;
constexpr int SM_SUM   = SM_IN0;
static_assert(SM_END <= 232448, "smem");

struct Maps { CUtensorMap wuk, wuv, woA, woB, ckv, endA, endB; };

struct Scratch {
    unsigned cnt[32];
    unsigned late[32];
    float    part[2][NCTA][512];
    uint32_t x[2][32][256];
    uint32_t lat[32][4][256];
    uint4    q[4][2048];
    uint4    op[NCTA][2048];
    float2   stat[32][128];
};
__device__ __align__(128) Scratch g_scratch;

constexpr int SPIN_LIMIT = 1 << 22;

__device__ __forceinline__ uint32_t smem_u32(const void* p) { return (uint32_t)__cvta_generic_to_shared(p); }
__device__ __forceinline__ void mbar_init(uint32_t bar, uint32_t cnt) {
    asm volatile("mbarrier.init.shared::cta.b64 [%0], %1;" ::"r"(bar), "r"(cnt) : "memory");
}
__device__ __forceinline__ void mbar_expect_tx(uint32_t bar, uint32_t bytes) {
    asm volatile("mbarrier.arrive.expect_tx.shared::cta.b64 _, [%0], %1;" ::"r"(bar), "r"(bytes) : "memory");
}
__device__ __forceinline__ void mbar_arrive(uint32_t bar) {
    asm volatile("mbarrier.arrive.shared::cta.b64 _, [%0];" ::"r"(bar) : "memory");
}
__device__ __forceinline__ void mbar_arrive8(uint32_t bar) {
    asm volatile("mbarrier.arrive.shared::cta.b64 _, [%0], 8;" ::"r"(bar) : "memory");
}
__device__ __forceinline__ void mbar_wait(uint32_t bar) {
    uint32_t done;
    int it = 0;
    do {
        asm volatile("{\n.reg .pred p;\nmbarrier.try_wait.parity.shared::cta.b64 p, [%1], 0;\nselp.u32 %0, 1, 0, p;\n}"
                     : "=r"(done) : "r"(bar) : "memory");
        if (++it > SPIN_LIMIT) __trap();
    } while (!done);
}
__device__ __forceinline__ uint32_t map_cta(uint32_t a, uint32_t rank) {
    uint32_t r; asm("mapa.shared::cluster.u32 %0, %1, %2;" : "=r"(r) : "r"(a), "r"(rank)); return r;
}
__device__ __forceinline__ void st_async64_if(uint32_t a, float x, float y, uint32_t bar, bool on) {
    asm volatile("{\n.reg .pred p;\nsetp.ne.u32 p, %4, 0;\n@p st.async.shared::cluster.mbarrier::complete_tx::bytes.v2.f32 [%0], {%1,%2}, [%3];\n}"
                 ::"r"(a), "f"(x), "f"(y), "r"(bar), "r"((uint32_t)on) : "memory");
}
__device__ __forceinline__ uint64_t evict_first() {
    uint64_t pol; asm volatile("createpolicy.fractional.L2::evict_first.b64 %0, 1.0;" : "=l"(pol)); return pol;
}
#define ELECT "{\n.reg .pred p;\nelect.sync _|p, 0xffffffff;\n@p "
__device__ __forceinline__ void bulk_load(uint32_t dst, const void* src, uint32_t bytes, uint32_t bar, uint64_t pol) {
    asm volatile(ELECT "cp.async.bulk.shared::cluster.global.mbarrier::complete_tx::bytes.L2::cache_hint [%0], [%1], %2, [%3], %4;\n}"
                 ::"r"(dst), "l"(src), "r"(bytes), "r"(bar), "l"(pol) : "memory");
}
__device__ __forceinline__ void bulk_load_nohint(uint32_t dst, const void* src, uint32_t bytes, uint32_t bar) {
    asm volatile("cp.async.bulk.shared::cluster.global.mbarrier::complete_tx::bytes [%0], [%1], %2, [%3];"
                 ::"r"(dst), "l"(src), "r"(bytes), "r"(bar) : "memory");
}
__device__ __forceinline__ void tma3d(uint32_t dst, const CUtensorMap* tm, int c0, int c1, int c2, uint32_t bar, uint64_t pol) {
    asm volatile(ELECT "cp.async.bulk.tensor.3d.shared::cluster.global.mbarrier::complete_tx::bytes.L2::cache_hint [%0], [%1, {%3, %4, %5}], [%2], %6;\n}"
                 ::"r"(dst), "l"(tm), "r"(bar), "r"(c0), "r"(c1), "r"(c2), "l"(pol) : "memory");
}
__device__ __forceinline__ void ldsm4(uint32_t a, uint32_t& r0, uint32_t& r1, uint32_t& r2, uint32_t& r3) {
    asm volatile("ldmatrix.sync.aligned.m8n8.x4.shared.b16 {%0,%1,%2,%3}, [%4];"
                 : "=r"(r0), "=r"(r1), "=r"(r2), "=r"(r3) : "r"(a) : "memory");
}
__device__ __forceinline__ void ldsm4t(uint32_t a, uint32_t& r0, uint32_t& r1, uint32_t& r2, uint32_t& r3) {
    asm volatile("ldmatrix.sync.aligned.m8n8.x4.trans.shared.b16 {%0,%1,%2,%3}, [%4];"
                 : "=r"(r0), "=r"(r1), "=r"(r2), "=r"(r3) : "r"(a) : "memory");
}
__device__ __forceinline__ void mma16816(float (&c)[4], uint32_t a0, uint32_t a1, uint32_t a2, uint32_t a3,
                                         uint32_t b0, uint32_t b1) {
    asm volatile("mma.sync.aligned.m16n8k16.row.col.f32.bf16.bf16.f32 {%0,%1,%2,%3}, {%4,%5,%6,%7}, {%8,%9}, {%0,%1,%2,%3};"
                 : "+f"(c[0]), "+f"(c[1]), "+f"(c[2]), "+f"(c[3])
                 : "r"(a0), "r"(a1), "r"(a2), "r"(a3), "r"(b0), "r"(b1));
}
__device__ __forceinline__ uint32_t lds32(uint32_t a) {
    uint32_t v; asm volatile("ld.shared.b32 %0, [%1];" : "=r"(v) : "r"(a) : "memory"); return v;
}
__device__ __forceinline__ float ldsf(uint32_t a) {
    float v; asm volatile("ld.shared.f32 %0, [%1];" : "=f"(v) : "r"(a) : "memory"); return v;
}
__device__ __forceinline__ float2 ldsf2(uint32_t a) {
    float2 v; asm volatile("ld.shared.v2.f32 {%0,%1}, [%2];" : "=f"(v.x), "=f"(v.y) : "r"(a) : "memory"); return v;
}
__device__ __forceinline__ float4 ldsf4(uint32_t a) {
    float4 v; asm volatile("ld.shared.v4.f32 {%0,%1,%2,%3}, [%4];" : "=f"(v.x), "=f"(v.y), "=f"(v.z), "=f"(v.w) : "r"(a) : "memory"); return v;
}
__device__ __forceinline__ uint4 lds128(uint32_t a) {
    uint4 v; asm volatile("ld.shared.v4.b32 {%0,%1,%2,%3}, [%4];" : "=r"(v.x), "=r"(v.y), "=r"(v.z), "=r"(v.w) : "r"(a) : "memory"); return v;
}
__device__ __forceinline__ float ldsf_if(uint32_t a, bool on) {
    float v = 0.f;
    asm volatile("{\n.reg .pred p;\nsetp.ne.u32 p, %2, 0;\n@p ld.shared.f32 %0, [%1];\n}" : "+f"(v) : "r"(a), "r"((uint32_t)on) : "memory");
    return v;
}
__device__ __forceinline__ float4 ldv4(uint32_t a) {
    float4 v; asm volatile("ld.volatile.shared.v4.f32 {%0,%1,%2,%3}, [%4];" : "=f"(v.x), "=f"(v.y), "=f"(v.z), "=f"(v.w) : "r"(a) : "memory"); return v;
}
__device__ __forceinline__ void stv(uint32_t a, float v) { asm volatile("st.volatile.shared.f32 [%0], %1;" ::"r"(a), "f"(v) : "memory"); }
__device__ __forceinline__ void sts16(uint32_t a, uint16_t v) { asm volatile("st.shared.b16 [%0], %1;" ::"r"(a), "h"(v) : "memory"); }
__device__ __forceinline__ void sts32(uint32_t a, uint32_t v) { asm volatile("st.shared.b32 [%0], %1;" ::"r"(a), "r"(v) : "memory"); }
__device__ __forceinline__ void stsf(uint32_t a, float v) { asm volatile("st.shared.f32 [%0], %1;" ::"r"(a), "f"(v) : "memory"); }
__device__ __forceinline__ void sts64(uint32_t a, uint32_t x, uint32_t y) {
    asm volatile("st.shared.v2.b32 [%0], {%1,%2};" ::"r"(a), "r"(x), "r"(y) : "memory");
}
__device__ __forceinline__ void sts128(uint32_t a, uint4 v) {
    asm volatile("st.shared.v4.b32 [%0], {%1,%2,%3,%4};" ::"r"(a), "r"(v.x), "r"(v.y), "r"(v.z), "r"(v.w) : "memory");
}
__device__ __forceinline__ uint32_t pack_bf16(float lo, float hi) {
    uint32_t r; asm("cvt.rn.bf16x2.f32 %0, %1, %2;" : "=r"(r) : "f"(hi), "f"(lo)); return r;
}
__device__ __forceinline__ float bf_lo(uint32_t v) { return __uint_as_float(v << 16); }
__device__ __forceinline__ float bf_hi(uint32_t v) { return __uint_as_float(v & 0xffff0000u); }
__device__ __forceinline__ float ex2(float x) { float y; asm("ex2.approx.ftz.f32 %0, %1;" : "=f"(y) : "f"(x)); return y; }
__device__ __forceinline__ uint32_t timer_ns() { uint32_t t; asm volatile("mov.u32 %0, %%globaltimer_lo;" : "=r"(t)); return t; }
__device__ __forceinline__ void bar_consumers() { asm volatile("bar.sync 1, 256;" ::: "memory"); }

__device__ __forceinline__ uint32_t tagf(float v, uint32_t tag) { return (__float_as_uint(v) & 0xffffff00u) | tag; }
__device__ __forceinline__ uint2 ld_rlx2(const float* p) {
    uint2 v; asm volatile("ld.relaxed.gpu.global.v2.b32 {%0,%1}, [%2];" : "=r"(v.x), "=r"(v.y) : "l"(p) : "memory"); return v;
}
__device__ __forceinline__ float untag(uint32_t v) { return __uint_as_float(v & 0xffffff00u); }

__device__ __forceinline__ uint32_t slot_off(int item) { return (uint32_t)(item % NSLOT) * SLOT; }

template <bool TRANS, bool TMA = true>
__device__ __forceinline__ void tile_mma(uint32_t sb, int item, uint32_t in, int w, int lane, float (&acc)[2][2]) {
    const int g = lane >> 2, t = lane & 3;
    float c[4][4];
#pragma unroll
    for (int i = 0; i < 16; i++) (&c[0][0])[i] = 0.f;
    uint32_t a[16];
    const uint32_t ia = in + (g & 3) * 272 + t * 4;
#pragma unroll
    for (int i = 0; i < 16; i++) a[i] = lds32(ia + i * 16);
    const uint32_t s0 = sb + slot_off(item), s1 = sb + slot_off(item + 1);
    if (TRANS) {
        const int r = (lane & 7) + (lane & 8);
        const int ch = 2 * (w & 3) + (lane >> 4);
        const uint32_t off = (TMA ? (w >> 2) * 8192 + r * 128 : (w >> 2) * 128 + r * 256) + ((ch ^ (lane & 7)) << 4);
#pragma unroll
        for (int kk = 0; kk < 8; kk++) {
            if (TMA && (kk & 3) == 0) mbar_wait(sb + SM_FULL + (item + (kk >> 2)) * 8);
            uint32_t r0, r1, r2, r3;
            ldsm4t(((kk >> 2) ? s1 : s0) + off + (kk & 3) * (TMA ? 2048 : 4096), r0, r1, r2, r3);
            mma16816(c[2 * (kk & 1)],     a[2 * kk], 0u, a[2 * kk + 1], 0u, r0, r1);
            mma16816(c[2 * (kk & 1) + 1], a[2 * kk], 0u, a[2 * kk + 1], 0u, r2, r3);
        }
    } else {
        mbar_wait(sb + SM_FULL + (item + (w >> 2)) * 8);
        const int r = 16 * (w & 3) + (lane & 7) + ((lane >> 4) << 3);
        const uint32_t base = ((w >> 2) ? s1 : s0) + (r & 32) * 128 + r * 128 + ((((lane >> 3) & 1) ^ (lane & 7)) << 4);
#pragma unroll
        for (int kk = 0; kk < 8; kk++) {
            uint32_t r0, r1, r2, r3;
            ldsm4((base ^ ((kk & 3) << 5)) + (kk >> 2) * 4096, r0, r1, r2, r3);
            mma16816(c[2 * (kk & 1)],     a[2 * kk], 0u, a[2 * kk + 1], 0u, r0, r1);
            mma16816(c[2 * (kk & 1) + 1], a[2 * kk], 0u, a[2 * kk + 1], 0u, r2, r3);
        }
    }
    __syncwarp();
    if (lane == 0) {
        mbar_arrive(sb + SM_EMPTY + item * 8);
        mbar_arrive(sb + SM_EMPTY + (item + 1) * 8);
    }
    acc[0][0] = c[0][0] + c[2][0]; acc[0][1] = c[0][1] + c[2][1];
    acc[1][0] = c[1][0] + c[3][0]; acc[1][1] = c[1][1] + c[3][1];
}

__device__ __forceinline__ void publish(float* dst, int w, int lane, const float (&acc)[2][2], uint32_t tag) {
    if (lane < 16)
        asm volatile("st.relaxed.gpu.global.v4.b32 [%0], {%1,%2,%3,%4};" ::"l"(dst + w * 64 + lane * 4),
                     "r"(tagf(acc[0][0], tag)), "r"(tagf(acc[0][1], tag)), "r"(tagf(acc[1][0], tag)), "r"(tagf(acc[1][1], tag)) : "memory");
}

__device__ __forceinline__ void gather(const float* part, uint32_t in, int tid, uint32_t tag) {
    const float* p = part + tid * 2;
    uint2 v0, v1, v2, v3;
    int it = 0;
    while (true) {
        v0 = ld_rlx2(p); v1 = ld_rlx2(p + 512); v2 = ld_rlx2(p + 1024); v3 = ld_rlx2(p + 1536);
        uint32_t bad = ((v0.x ^ tag) | (v0.y ^ tag) | (v1.x ^ tag) | (v1.y ^ tag) |
                        (v2.x ^ tag) | (v2.y ^ tag) | (v3.x ^ tag) | (v3.y ^ tag)) & 0xffu;
        if (__all_sync(0xffffffffu, bad == 0)) break;
        if (++it > SPIN_LIMIT) __trap();
    }
    float x = (untag(v0.x) + untag(v1.x)) + (untag(v2.x) + untag(v3.x));
    float y = (untag(v0.y) + untag(v1.y)) + (untag(v2.y) + untag(v3.y));
    sts32(in + ((tid >> 3) & 3) * 272 + (tid >> 5) * 32 + (tid & 1) * 16 + (tid & 6) * 2, pack_bf16(x, y));
    bar_consumers();
}

constexpr uint32_t EMPTY = 0xffffffffu;
__device__ __forceinline__ void st_rlx(uint32_t* p, uint32_t v) {
    asm volatile("st.relaxed.gpu.global.b32 [%0], %1;" ::"l"(p), "r"(v) : "memory");
}
__device__ __forceinline__ void st_rlx_if(uint64_t p, uint32_t v, bool on) {
    asm volatile("{\n.reg .pred p;\nsetp.ne.u32 p, %2, 0;\n@p st.relaxed.gpu.global.b32 [%0], %1;\n}" ::"l"(p), "r"(v), "r"((uint32_t)on) : "memory");
}
__device__ __forceinline__ void st_if(uint64_t p, uint32_t v, bool on) {
    asm volatile("{\n.reg .pred p;\nsetp.ne.u32 p, %2, 0;\n@p st.global.b32 [%0], %1;\n}" ::"l"(p), "r"(v), "r"((uint32_t)on) : "memory");
}
__device__ __forceinline__ void st_rlx2(uint32_t* p, uint32_t v0, uint32_t v1) {
    asm volatile("st.relaxed.gpu.global.v2.b32 [%0], {%1,%2};" ::"l"(p), "r"(v0), "r"(v1) : "memory");
}
__device__ __forceinline__ void ld_rlx4_if(uint4& v, const void* p, bool need) {
    asm volatile("{\n.reg .pred p;\nsetp.ne.u32 p, %5, 0;\n@p ld.relaxed.gpu.global.v4.b32 {%0,%1,%2,%3}, [%4];\n}"
                 : "+r"(v.x), "+r"(v.y), "+r"(v.z), "+r"(v.w) : "l"(p), "r"((uint32_t)need) : "memory");
}

template <class F>
__device__ __forceinline__ bool refetch(uint4 (&x)[8], F addr) {
    uint32_t m[8], m0 = 0;
#pragma unroll
    for (int i = 0; i < 8; i++) {
        m[i] = max(max(x[i].x, x[i].y), max(x[i].z, x[i].w));
        m0 = max(m0, m[i]);
    }
    if (!__any_sync(0xffffffffu, m0 == EMPTY)) return false;
#pragma unroll
    for (int i = 0; i < 8; i++) ld_rlx4_if(x[i], addr(i), m[i] == EMPTY);
    return true;
}

__device__ __forceinline__ unsigned read_counter(const unsigned* cnt) {
    unsigned v;
    asm volatile("ld.relaxed.gpu.global.u32 %0, [%1];" : "=r"(v) : "l"(cnt) : "memory");
    return v;
}
__device__ __forceinline__ unsigned epoch_of(unsigned cnt) {
    asm volatile("" : "+r"(cnt) :: "memory");
    return cnt / NCTA + 1;
}
__device__ __forceinline__ uint32_t epoch_tag(unsigned epoch) { return (epoch & 0x7fu) | 0x80u; }

__device__ __forceinline__ void signal_and_wait(unsigned* cnt, unsigned target, int lane) {
    if (lane == 0) asm volatile("red.release.gpu.global.add.u32 [%0], 1;" ::"l"(cnt) : "memory");
    int it = 0;
    while (true) {
        unsigned v;
        asm volatile("ld.acquire.gpu.global.u32 %0, [%1];" : "=r"(v) : "l"(cnt) : "memory");
        if (__all_sync(0xffffffffu, (int)(v - target) >= 0)) break;
        if (++it > SPIN_LIMIT) __trap();
    }
    asm volatile("fence.proxy.async.global;" ::: "memory");
}

__global__ void __cluster_dims__(2, 1, 1) __launch_bounds__(NTHR, 1)
fused_decode_kernel(const __nv_bfloat16* __restrict__ xA, const __nv_bfloat16* __restrict__ xB,
                    const __nv_bfloat16* __restrict__ wqB, const __nv_bfloat16* __restrict__ wqA,
                    const __nv_bfloat16* __restrict__ Kc, const __nv_bfloat16* __restrict__ Vc,
                    __nv_bfloat16* __restrict__ out, Scratch* gs, const __grid_constant__ Maps maps) {
    extern __shared__ __align__(1024) unsigned char smem_raw[];
    const uint32_t sb = smem_u32(smem_raw);
    const int tid = threadIdx.x, lane = tid & 31;
    const int cta = blockIdx.x, h = cta >> 2, j = cta & 3;
    const size_t kv_off = (size_t)blockIdx.x * 4096 * 128;
    const uint32_t trow = threadIdx.x >> 4;
    const uint32_t tile_src = trow * (8192 - 256) + (threadIdx.x * 16 + ((blockIdx.x * 0x100040u) & 0x301f00u));
    const uint32_t tile_dst = sb + ((threadIdx.x ^ (trow & 7)) << 4);
    asm volatile("prefetch.global.L2 [%0];" ::"l"(reinterpret_cast<const char*>(wqB) + tile_src) : "memory");
    auto lsu_piece = [&](int k) {
#pragma unroll
        for (int q = 2 * k; q < 2 * k + 2; q++)
            asm volatile("cp.async.cg.shared.global [%0], [%1], 16;" ::"r"(tile_dst + q * 4096),
                         "l"(reinterpret_cast<const char*>((k < 4 ? wqB : wqA) + (q & 7) * 16 * 4096) + tile_src) : "memory");
        if ((k & 3) == 3) asm volatile("cp.async.commit_group;" ::: "memory");
    };
    if (tid < 256) {
#pragma unroll
        for (int k = 0; k < 4; k++) lsu_piece(k);
    }
    const uint32_t tz = timer_ns() - LEAD;
    unsigned cnt1;
    if (tid < 256) cnt1 = read_counter(&gs->cnt[1]);
    uint4 xv;
    if (tid < 128) {
        const __nv_bfloat16* x = (tid < 64 ? xB : xA) + ((tid >> 4) & 3) * 512 + j * 128 + (tid & 15) * 8;
        xv = __ldg(reinterpret_cast<const uint4*>(x));
    }
    const int w = __shfl_sync(0xffffffffu, tid >> 5, 0);
    const int pr = cta >> 1;
    const int slice = pr < 4 ? pr : pr < 36 ? 4 + ((pr - 4) & 7) * 4 + ((pr - 4) >> 3) : 36 + (pr - 36) % 7 * 4 + (pr - 36) / 7;

    if (w >= 8) {
        if (lane == 0) {
            const uint32_t full = sb + SM_FULL + (IT_WUK + (w & 3) * 14) * 8, empty = sb + SM_EMPTY + (w & 3) * 13 * 8,
                           last = sb + SM_LAST + (w & 3) * 32;
#pragma unroll
            for (int i = 0; i < 14; i++) mbar_init(full + i * 8, 1);
#pragma unroll
            for (int i = 0; i < 13; i++) mbar_init(empty + i * 8, 8);
#pragma unroll
            for (int i = 0; i < 4; i++) mbar_init(last + i * 8, 1);
#pragma unroll
            for (int i = 0; i < 14; i++) {
                const int b = IT_WUK + 42 + i;
                mbar_expect_tx(full + i * 8, (w == 10 && b - 14 == IT_OP) ? SLOT + 1024 : (w == 11 && b == BAR_LAT) ? 4096 : SLOT);
            }
#pragma unroll
            for (int i = 0; i < 4; i++) mbar_expect_tx(last + i * 8, i == 1 && w == 8 && !(j & 1) ? 2048 + 256 : 2048);
            asm volatile("fence.mbarrier_init.release.cluster;" ::: "memory");
            if (w == 10) sts64(sb + SM_PACE, tz, PACE * 16);
        }
        asm volatile("bar.sync 2, 128;" ::: "memory");
        asm volatile("bar.arrive 4, 384;" ::: "memory");
    }
    if (w == 10) {
        if (lane == 0) {
            int slope = 0;
#pragma unroll
            for (int k = 0; k < NWIN; k++) {
                const int c = win_pos(k);
                uint32_t acc = 0;
#pragma unroll
                for (int p = c; p < c + 4; p++) {
                    mbar_wait(sb + SM_FULL + (p < IT_Q ? p : p < IT_OP - 2 ? p + 2 : p + 4) * 8);
                    acc += timer_ns() - tz - p * PACE - ((p * slope) >> 4);
                }
                if (k == 0) mbar_wait(sb + SM_FULL + IT_Q * 8);
                asm volatile("red.relaxed.gpu.global.add.u32 [%0], %1;" ::"l"(&gs->late[k]), "r"((1u << 24) + min(acc >> 2, 65535u)) : "memory");
                uint32_t v;
                int it = 0;
                do { v = read_counter(&gs->late[k]); } while ((v >> 24) != NCTA && ++it < 1000);
                const int late = (v & 0xffffffu) / NCTA;
                slope = max(-320, min(320, slope + (late - win_late(k)) * (GAIN * 2) / (2 * c + 3)));
                sts64(sb + SM_PACE, tz, PACE * 16 + slope);
            }
        }
        return;
    }
    if (w >= 8) {
        auto wait_due = [&](uint32_t p, uint32_t shift) {
            uint32_t a, b;
            do {
                asm volatile("ld.volatile.shared.v2.b32 {%0,%1}, [%2];" : "=r"(a), "=r"(b) : "r"(sb + SM_PACE) : "memory");
            } while (__all_sync(0xffffffffu, (int)(timer_ns() - (a + ((p * b) >> 4) + shift)) < 0));
        };
        if (w != 9) {
            const int half = w & 1;
            const uint64_t pol = evict_first();
            int slot = IT_WUK, tail = IT_WUK - INFLIGHT;
            uint32_t np = IT_WUK, shift = half ? PACE / 4 : -(PACE / 4);
#pragma unroll 1
            for (int i = IT_WUK; i < NITEM; i++) {
                const uint32_t dst = sb + slot * SLOT + half * (SLOT / 2), bar = sb + SM_FULL + i * 8;
                if (++slot == NSLOT) slot = 0;
                if ((i & ~1) == IT_Q || (i & ~1) == IT_OP) continue;
                const bool ckv = i >= IT_C && i < IT_K1, wo = i >= IT_WO;
                const bool tiled = ckv || i < IT_K0 || i >= IT_WUV;
                const CUtensorMap* tm = &maps.wuk + (i < IT_K0 ? 0 : ckv ? 4 : wo ? 2 + (slice >> 5) : 1);
                const int c0 = wo ? (slice & 31) * 16 : i >= IT_WUV ? cta * 32 : 0;
                const int c1 = i < IT_K0 ? j * 128 + (i & 1) * 64 + half * 32 : ckv ? cta * 128 + (i - IT_C) * 16 + half * 8 : wo ? 0 : half * 128;
                const int c2 = i < IT_K0 ? h * 2 : ckv ? 0 : wo ? (j & 1) * 8 + (i - IT_WO) * 2 + half : i & 1;
                const int c = i < IT_Q ? i - IT_K0 : i < IT_V0 ? i - IT_K1 + 8 : i < IT_OP ? i - IT_V0 : i - IT_V1 + 8;
                const __nv_bfloat16* src = (i < IT_V0 ? Kc : Vc) + kv_off + (size_t)((c ^ (j & 1) * 7) * 2 + half) * (SLOT / 4);
                if (i >= NSLOT) mbar_wait(sb + SM_EMPTY + (i - NSLOT) * 8);
                if (tail >= IT_WUK && !wo) mbar_wait(sb + SM_FULL + tail * 8);
                ++tail;
                if (tail == IT_Q || tail == IT_OP) tail += 2;
                if (wo) {
                    const int n = c2 & 7;
                    np = IT_WO - 4;
                    shift = TAPER + ((j & 1) ? OS0 + n * OS1 : n < 4 ? OF0 + n * OF1 : OF2 + (n - 4) * OF3);
                }
                wait_due(np, shift);
                ++np;
                if (i == IT_WUV - 1) shift += TAPER;
                if (i >= NITEM - 2) {
#pragma unroll
                    for (int q = 0; q < 4; q++)
                        tma3d(dst + q * 2048, tm + 3, c0, q * 64, c2, sb + SM_LAST + half * 64 + q * 16 + (i & 1) * 8, pol);
                }
                else if (tiled) tma3d(dst, tm, c0, c1, c2, bar, pol);
                else bulk_load(dst, src, SLOT / 2, bar, pol);
            }
        } else {
            if (lane < sizeof(Maps) / 128) asm volatile("prefetch.tensormap [%0];" ::"l"(&maps.wuk + lane) : "memory");
            cnt1 = read_counter(&gs->cnt[1]);
            asm volatile("bar.sync 3, 288;" ::: "memory");
            const unsigned epoch = epoch_of(cnt1);
            signal_and_wait(&gs->cnt[0], epoch * NCTA, lane);
            if (lane == 0) {
                const uint4* q = gs->q[cta >> 5];
                bulk_load_nohint(sb + slot_off(IT_Q), q, SLOT, sb + SM_FULL + IT_Q * 8);
                bulk_load_nohint(sb + slot_off(IT_Q + 1), q + 1024, SLOT, sb + SM_FULL + (IT_Q + 1) * 8);
            }
            asm volatile("bar.sync 3, 288;" ::: "memory");
            signal_and_wait(&gs->cnt[1], epoch * NCTA, lane);
            mbar_wait(sb + SM_EMPTY + (IT_OP - NSLOT) * 8);
            mbar_wait(sb + SM_EMPTY + (IT_OP + 1 - NSLOT) * 8);
            if (lane == 0) {
                const uint4* op = gs->op[cta];
                bulk_load_nohint(sb + SM_MX, gs->stat[h], 1024, sb + SM_FULL + IT_OP * 8);
                uint32_t t1 = timer_ns();
#pragma unroll 1
                for (int i = 0; i < 8; i++) {
                    while ((int)(timer_ns() - t1) < 0) {}
                    t1 += OPGAP;
                    bulk_load_nohint(sb + slot_off(IT_OP) + i * 4096, op + i * 256, 4096, sb + SM_FULL + (IT_OP + i / 4) * 8);
                }
            }
            mbar_wait(sb + SM_FULL + (IT_V1 + 4) * 8);
            if (lane == 0) bulk_load_nohint(sb + SM_LAT, gs->lat[h], 4096, sb + SM_FULL + BAR_LAT * 8);
            mbar_wait(sb + SM_EMPTY + (IT_X - NSLOT) * 8);
            mbar_wait(sb + SM_FULL + (IT_WUV + 1) * 8);
            wait_due(IT_WO - 4, TAPER + ((j & 1) ? XS : XF));
            if (lane == 0) bulk_load_nohint(sb + slot_off(IT_X), gs->x[slice >> 5][(j & 1) * 16], SLOT, sb + SM_FULL + IT_X * 8);
        }
        return;
    }

    const int g = lane >> 2, t = lane & 3;
    const uint32_t in0 = sb + SM_IN0, in1 = sb + SM_IN1;
    const int ba = cta >> 5, ha = cta & 31;
    uint32_t* const ctx_dst = &gs->x[1][h][(j * 4 + (w & 3)) * 16 + ((g ^ (w & 2)) & 3) * 4 + ((t - w) & 3)];
    uint32_t* const o_dst = &gs->x[0][ha][ba * 64 + ((tid & 60) ^ ((ba & 1) * 16)) + ((t - g) & 3)];
    uint32_t* const lat_dst = &gs->lat[h][g & 3][j * 64 + ((w >> 1) ^ (g & 1)) * 16 + t * 4 + ((w * 2 ^ t) & 2)];
    {
#pragma unroll
        for (int k = 4; k < 8; k++) {
            while (__all_sync(0xffffffffu, (int)(timer_ns() - (tz + (2 * k - 1) * (PACE / 4))) < 0)) {}
            lsu_piece(k);
        }
        if (lane < 16) st_rlx2(lat_dst, EMPTY, EMPTY);
        if (lane >= 16 && w < 4) st_rlx(ctx_dst, EMPTY);
        if (w >= 6) st_rlx(o_dst, EMPTY);
        if (cta == 0 && w == 5) st_rlx(&gs->late[lane], 0u);
        if (tid < 128) sts128((tid < 64 ? in0 : in1) + ((tid >> 4) & 3) * 272 + (tid & 15) * 16, xv);
        asm volatile("cp.async.wait_group 1;" ::: "memory");
    }
    asm volatile("bar.sync 4, 384;" ::: "memory");
    const uint32_t tag = epoch_tag(epoch_of(cnt1));

    float acc[2][2];
    tile_mma<true, false>(sb, IT_WQB, in0, w, lane, acc);
    publish(gs->part[0][cta], w, lane, acc, tag);
    asm volatile("cp.async.wait_group 0;" ::: "memory");
    bar_consumers();
    tile_mma<true, false>(sb, IT_WQA, in1, w, lane, acc);
    publish(gs->part[1][cta], w, lane, acc, tag);
    bar_consumers();

    const float SC = 0.08838834764831845f * 1.4426950408889634f;
    gather(gs->part[0][h * 4], in0, tid, tag);
    tile_mma<false>(sb, IT_WUK, in0, w, lane, acc);
    if (lane < 16) {
        uint32_t* q = reinterpret_cast<uint32_t*>(gs->q[g]) + (2 * j + (w >> 2)) * 1024 + h * 32 + t;
        const int ch = 2 * (w & 3);
        q[((ch) ^ (h & 7)) * 4]     = pack_bf16(acc[0][0] * SC, acc[0][1] * SC);
        q[((ch + 1) ^ (h & 7)) * 4] = pack_bf16(acc[1][0] * SC, acc[1][1] * SC);
    }
    __syncwarp();
    asm volatile("bar.arrive 3, 288;" ::: "memory");
    gather(gs->part[1][ha * 4], in1, tid, tag);

    uint32_t qf[16];
#pragma unroll
    for (int c = 0; c < 8; c++) {
        qf[2 * c]     = lds32(in1 + ba * 272 + ((c ^ g) << 4) + t * 4);
        qf[2 * c + 1] = lds32(in1 + ba * 272 + 128 + ((c ^ g) << 4) + t * 4);
    }
    const uint32_t sc_w = sb + SM_SC + w * 512;
    auto k_item = [&](int item, uint32_t sc) {
        mbar_wait(sb + SM_FULL + item * 8);
        const uint32_t base = sb + slot_off(item) + ((lane & 7) + (lane & 8)) * 256 + ((lane >> 4) << 7);
        float s[4][4];
#pragma unroll
        for (int T = 0; T < 4; T++) { s[T][0] = s[T][1] = s[T][2] = s[T][3] = 0.f; }
#pragma unroll
        for (int c = 0; c < 8; c++) {
            const uint32_t a = base + ((c ^ (lane & 7)) << 4);
#pragma unroll
            for (int T = 0; T < 4; T++) {
                uint32_t r0, r1, r2, r3;
                ldsm4(a + T * 4096, r0, r1, r2, r3);
                mma16816(s[T], r0, r1, r2, r3, qf[2 * c], qf[2 * c + 1]);
            }
        }
        __syncwarp();
        if (lane == 0) mbar_arrive8(sb + SM_EMPTY + item * 8);
        if (t == (g >> 1)) {
#pragma unroll
            for (int T = 0; T < 4; T++) {
                stsf(sc + (16 * T + g) * 4,     (g & 1) ? s[T][1] : s[T][0]);
                stsf(sc + (16 * T + g + 8) * 4, (g & 1) ? s[T][3] : s[T][2]);
            }
        }
    };
    k_item(IT_K0 + w, sc_w);

    {
        float s[2][2][4];
#pragma unroll
        for (int i = 0; i < 16; i++) (&s[0][0][0])[i] = 0.f;
        mbar_wait(sb + SM_FULL + IT_Q * 8);
        mbar_wait(sb + SM_FULL + (IT_Q + 1) * 8);
        mbar_wait(sb + SM_FULL + (IT_C + w) * 8);
        const uint32_t cb0 = sb + slot_off(IT_C + w) + (lane & 7) * 128 + (lane >> 4) * 8192;
        const uint32_t cx = (((lane >> 3) & 1) ^ (lane & 7)) << 4;
        const uint32_t qr = ((lane & 7) + (lane & 8)) * 128;
        const uint32_t qx = ((lane >> 4) ^ (lane & 7)) << 4;
#pragma unroll
        for (int cb = 0; cb < 8; cb++) {
            const uint32_t qb = sb + slot_off(IT_Q + (cb >> 2)) + (cb & 3) * 4096 + qr;
#pragma unroll
            for (int k4 = 0; k4 < 4; k4++) {
                uint32_t b0, b1, b2, b3, a0, a1, a2, a3;
                ldsm4(cb0 + cb * 1024 + (cx ^ (k4 << 5)), b0, b1, b2, b3);
                ldsm4(qb + (qx ^ (k4 << 5)), a0, a1, a2, a3);
                mma16816(s[0][0], a0, a1, a2, a3, b0, b1);
                mma16816(s[0][1], a0, a1, a2, a3, b2, b3);
                ldsm4(qb + 2048 + (qx ^ (k4 << 5)), a0, a1, a2, a3);
                mma16816(s[1][0], a0, a1, a2, a3, b0, b1);
                mma16816(s[1][1], a0, a1, a2, a3, b2, b3);
            }
        }
        __syncwarp();
        if (lane == 0) { mbar_arrive(sb + SM_EMPTY + IT_Q * 8); mbar_arrive(sb + SM_EMPTY + (IT_Q + 1) * 8); }
#pragma unroll
        for (int r = 0; r < 4; r++) {
            const int mt = r >> 1, hi = (r & 1) * 2;
            float m = fmaxf(fmaxf(s[mt][0][hi], s[mt][0][hi + 1]), fmaxf(s[mt][1][hi], s[mt][1][hi + 1]));
            m = fmaxf(m, __shfl_xor_sync(0xffffffffu, m, 1));
            m = fmaxf(m, __shfl_xor_sync(0xffffffffu, m, 2));
            if (t == 0) stsf(sb + SM_MX + (8 * r + g) * 32 + w * 4, m);
        }
        bar_consumers();
        uint32_t pf[2][4];
#pragma unroll
        for (int r = 0; r < 4; r++) {
            const int mt = r >> 1, hi = r & 1;
            const float4 m0 = ldsf4(sb + SM_MX + (8 * r + g) * 32), m1 = ldsf4(sb + SM_MX + (8 * r + g) * 32 + 16);
            const float m = fmaxf(fmaxf(fmaxf(m0.x, m0.y), fmaxf(m0.z, m0.w)), fmaxf(fmaxf(m1.x, m1.y), fmaxf(m1.z, m1.w)));
            const uint32_t p0 = pack_bf16(ex2(s[mt][0][2 * hi] - m), ex2(s[mt][0][2 * hi + 1] - m));
            const uint32_t p1 = pack_bf16(ex2(s[mt][1][2 * hi] - m), ex2(s[mt][1][2 * hi + 1] - m));
            pf[mt][hi] = p0; pf[mt][2 + hi] = p1;
            float l = (bf_lo(p0) + bf_hi(p0)) + (bf_lo(p1) + bf_hi(p1));
            l += __shfl_xor_sync(0xffffffffu, l, 1);
            l += __shfl_xor_sync(0xffffffffu, l, 2);
            if (t == 0) stsf(sb + SM_SUM + (8 * r + g) * 32 + w * 4, l);
        }
        sts128(sb + SM_PF + (w * 2 + 0) * 512 + lane * 16, make_uint4(pf[0][0], pf[0][1], pf[0][2], pf[0][3]));
        sts128(sb + SM_PF + (w * 2 + 1) * 512 + lane * 16, make_uint4(pf[1][0], pf[1][1], pf[1][2], pf[1][3]));
        bar_consumers();
        if (w == 0) {
            const float4 m0 = ldsf4(sb + SM_MX + lane * 32), m1 = ldsf4(sb + SM_MX + lane * 32 + 16);
            const float4 l0 = ldsf4(sb + SM_SUM + lane * 32), l1 = ldsf4(sb + SM_SUM + lane * 32 + 16);
            const float m = fmaxf(fmaxf(fmaxf(m0.x, m0.y), fmaxf(m0.z, m0.w)), fmaxf(fmaxf(m1.x, m1.y), fmaxf(m1.z, m1.w)));
            const float l = ((l0.x + l0.y) + (l0.z + l0.w)) + ((l1.x + l1.y) + (l1.z + l1.w));
            gs->stat[lane][cta] = make_float2(m, l);
        }
        float o[2][8][4];
#pragma unroll
        for (int i = 0; i < 64; i++) (&o[0][0][0])[i] = 0.f;
        const uint32_t vr = w * 1024 + (lane & 7) * 128 + (lane & 8) * 1024;
        const uint32_t vx = ((lane >> 4) ^ (lane & 7)) << 4;
#pragma unroll
        for (int ks = 0; ks < 8; ks++) {
            const uint4 p0 = lds128(sb + SM_PF + (ks * 2 + 0) * 512 + lane * 16);
            const uint4 p1 = lds128(sb + SM_PF + (ks * 2 + 1) * 512 + lane * 16);
            const uint32_t vb = sb + slot_off(IT_C + ks) + vr;
#pragma unroll
            for (int n2 = 0; n2 < 4; n2++) {
                uint32_t b0, b1, b2, b3;
                ldsm4t(vb + (vx ^ (n2 << 5)), b0, b1, b2, b3);
                mma16816(o[0][2 * n2],     p0.x, p0.y, p0.z, p0.w, b0, b1);
                mma16816(o[0][2 * n2 + 1], p0.x, p0.y, p0.z, p0.w, b2, b3);
                mma16816(o[1][2 * n2],     p1.x, p1.y, p1.z, p1.w, b0, b1);
                mma16816(o[1][2 * n2 + 1], p1.x, p1.y, p1.z, p1.w, b2, b3);
            }
            __syncwarp();
            if (lane == 0) mbar_arrive(sb + SM_EMPTY + (IT_C + ks) * 8);
        }
        mbar_wait(sb + SM_FULL + (IT_K1 + 1 + (w * 3 >> 2)) * 8);
#pragma unroll
        for (int r = 0; r < 4; r++) {
            const int mt = r >> 1, hi = (r & 1) * 2;
            uint4* dst = gs->op[(8 * r + g) * 4 + (w >> 1)] + (cta >> 6) * 1024 + (w & 1) * 512 + (cta & 63) * 8;
#pragma unroll
            for (int u = 0; u < 2; u++) {
                uint4 v;
                v.x = pack_bf16(o[mt][4 * u][hi],     o[mt][4 * u][hi + 1]);
                v.y = pack_bf16(o[mt][4 * u + 1][hi], o[mt][4 * u + 1][hi + 1]);
                v.z = pack_bf16(o[mt][4 * u + 2][hi], o[mt][4 * u + 2][hi + 1]);
                v.w = pack_bf16(o[mt][4 * u + 3][hi], o[mt][4 * u + 3][hi + 1]);
                dst[(t + 4 * u) ^ (cta & 7)] = v;
            }
        }
        asm volatile("bar.arrive 3, 288;" ::: "memory");
    }

    k_item(IT_K1 + w, sc_w + 256);
    __syncwarp();
    {
        const float4 s = ldsf4(sc_w + lane * 16);
        float m = fmaxf(fmaxf(s.x, s.y), fmaxf(s.z, s.w));
#pragma unroll
        for (int d = 1; d < 32; d <<= 1) m = fmaxf(m, __shfl_xor_sync(0xffffffffu, m, d));
        if (lane == 0) stsf(sb + SM_ML + w * 4, m);
        bar_consumers();
        const float4 m0 = ldsf4(sb + SM_ML), m1 = ldsf4(sb + SM_ML + 16);
        m = fmaxf(fmaxf(fmaxf(m0.x, m0.y), fmaxf(m0.z, m0.w)), fmaxf(fmaxf(m1.x, m1.y), fmaxf(m1.z, m1.w))) * SC;
        const uint32_t p0 = pack_bf16(ex2(fmaf(s.x, SC, -m)), ex2(fmaf(s.y, SC, -m)));
        const uint32_t p1 = pack_bf16(ex2(fmaf(s.z, SC, -m)), ex2(fmaf(s.w, SC, -m)));
        float l = (bf_lo(p0) + bf_hi(p0)) + (bf_lo(p1) + bf_hi(p1));
#pragma unroll
        for (int d = 1; d < 32; d <<= 1) l += __shfl_xor_sync(0xffffffffu, l, d);
        if (lane == 0) stsf(sb + SM_ML + 32 + w * 4, l);
        sts64(sb + SM_PA + w * 256 + lane * 8, p0, p1);
        __syncwarp();
    }

    float oa[4][4];
#pragma unroll
    for (int i = 0; i < 16; i++) (&oa[0][0])[i] = 0.f;
    auto v_item = [&](int item, uint32_t pa) {
        uint32_t p[8];
#pragma unroll
        for (int i = 0; i < 8; i++) p[i] = lds32(pa + i * 16 + t * 4);
        mbar_wait(sb + SM_FULL + item * 8);
        const uint32_t base = sb + slot_off(item) + ((lane & 7) + ((lane >> 4) << 3)) * 256 + ((lane & 8) << 4);
#pragma unroll
        for (int c = 0; c < 8; c++) {
            const uint32_t a = base + ((c ^ (lane & 7)) << 4);
            const uint32_t mask = ((c == (g ^ (2 * t))) ? 0x0000ffffu : 0u) | ((c == (g ^ (2 * t + 1))) ? 0xffff0000u : 0u);
#pragma unroll
            for (int T = 0; T < 4; T++) {
                uint32_t r0, r1, r2, r3;
                ldsm4t(a + T * 4096, r0, r1, r2, r3);
                mma16816(oa[T], r0, r1, r2, r3, p[2 * T] & mask, p[2 * T + 1] & mask);
            }
        }
        __syncwarp();
        if (lane == 0) mbar_arrive8(sb + SM_EMPTY + item * 8);
    };
    sts64(sb + SM_FIN + tid * 8, EMPTY, EMPTY);
    if (w == 0) sts32(sb + SM_CNT + lane * 4, 0u);
    v_item(IT_V0 + w, sb + SM_PA + w * 256);

    mbar_wait(sb + SM_FULL + IT_OP * 8);
    if (w < 4) {
        const float2 st = ldsf2(sb + SM_MX + tid * 8);
        float m = st.x;
#pragma unroll
        for (int d = 1; d < 32; d <<= 1) m = fmaxf(m, __shfl_xor_sync(0xffffffffu, m, d));
        const uint32_t wb = pack_bf16(ex2(st.x - m), 0.f);
        float l = bf_lo(wb) * st.y;
#pragma unroll
        for (int d = 1; d < 32; d <<= 1) l += __shfl_xor_sync(0xffffffffu, l, d);
#pragma unroll
        for (int bb = 0; bb < 4; bb++) sts16(in0 + bb * 272 + tid * 2, bb == w ? (uint16_t)wb : (uint16_t)0);
        if (lane == 0) stsf(sb + SM_ML + 64 + w * 4, 1.f / l);
    }
    bar_consumers();
    tile_mma<true>(sb, IT_OP, in0, w, lane, acc);
    if (lane < 16) {
        const float inv = ldsf(sb + SM_ML + 64 + g * 4);
        const uint32_t v0 = pack_bf16(acc[0][0] * inv, acc[0][1] * inv), v1 = pack_bf16(acc[1][0] * inv, acc[1][1] * inv);
        st_rlx2(lat_dst, (t & 1) ? v1 : v0, (t & 1) ? v0 : v1);
    }

    {
        const float4 l0 = ldsf4(sb + SM_ML + 32), l1 = ldsf4(sb + SM_ML + 48);
        const float inv = 1.f / (((l0.x + l0.y) + (l0.z + l0.w)) + ((l1.x + l1.y) + (l1.z + l1.w)));
        v_item(IT_V1 + w, sb + SM_PA + w * 256 + 128);
        const uint32_t so = sb + SM_PF + w * 512 + (16 * t + g) * 4;
        stsf(so,       (oa[0][0] + oa[1][0]) + (oa[2][0] + oa[3][0]));
        stsf(so + 32,  (oa[0][1] + oa[1][1]) + (oa[2][1] + oa[3][1]));
        stsf(so + 256, (oa[0][2] + oa[1][2]) + (oa[2][2] + oa[3][2]));
        stsf(so + 288, (oa[0][3] + oa[1][3]) + (oa[2][3] + oa[3][3]));
        if (w < 6) {
            asm volatile("bar.arrive 1, 256;" ::: "memory");
        } else {
            bar_consumers();
            float x = 0.f, y = 0.f;
#pragma unroll
            for (int i = 0; i < 8; i++) {
                const float2 v = ldsf2(sb + SM_PF + i * 512 + (tid & 63) * 8);
                x += v.x; y += v.y;
            }
            st_rlx(o_dst, pack_bf16(x * inv, y * inv));
        }
    }

    if (w < 4) {
        const uint32_t lo = (g & 3) * 1024 + (g >> 2) * 512 + (g & 1) * 64 + t * 16;
        const int wd = ((lane >> 2 & 2) + (lane >> 4)) ^ (lane >> 1 & 3);
        const uint32_t base = sb + ((lane & 6) * 4 + wd * 2 + (lane & 1)) * 64 + (((w ^ wd) & 3) << 4);
        const uint64_t dst = __shfl_sync(0xffffffffu, (unsigned long long)ctx_dst, lane);
        mbar_wait(sb + SM_FULL + BAR_LAT * 8);
        uint4 a[8];
#pragma unroll
        for (int i = 0; i < 8; i++) a[i] = lds128(sb + SM_LAT + (lo ^ (i * 64)));
        int it = 0;
        while (refetch(a, [&](int i) { return (const char*)gs->lat[h] + (lo ^ (i * 64)); }))
            if (++it > SPIN_LIMIT) __trap();
        float v0 = 0.f, v1 = 0.f;
#pragma unroll
        for (int i = 0; i < 2; i++) {
            float c[4][4];
#pragma unroll
            for (int k = 0; k < 16; k++) (&c[0][0])[k] = 0.f;
            c[0][0] = v0; c[0][1] = v1;
            mbar_wait(sb + SM_FULL + (IT_WUV + i) * 8);
#pragma unroll
            for (int kk = 0; kk < 8; kk++) {
                uint32_t r0, r1, r2, r3;
                ldsm4t(base + slot_off(IT_WUV + i) + kk * 2048, r0, r1, r2, r3);
                mma16816(c[2 * (kk & 1)],     a[kk].x, a[kk].y, a[kk].z, a[kk].w, r0, r1);
                mma16816(c[2 * (kk & 1) + 1], a[kk].x, a[kk].y, a[kk].z, a[kk].w, r2, r3);
            }
            v0 = (c[0][0] + c[1][2]) + (c[2][0] + c[3][2]);
            v1 = (c[0][1] + c[1][3]) + (c[2][1] + c[3][3]);
            if (i == 0) { v0 = __shfl_xor_sync(0xffffffffu, v0, 16); v1 = __shfl_xor_sync(0xffffffffu, v1, 16); }
        }
        st_rlx_if(dst, pack_bf16(v0, v1), lane >= 16);
    }

    {
        const bool isB = slice >= 32;
        const int r = j & 1;
        const uint32_t cs = isB ? 256 : 64;
        const uint32_t xl = (isB ? t * 64 + (((g >> 1) ^ (t & 2)) << 4) : (g >> 1) * 256 + ((g & 2) * 2 + t) * 16) + (w >> 1) * 1024 + (w & 1) * 2 * cs;
        auto xoff = [&](int i) { return (i >> 1) * 4096 + (xl ^ ((i & 1) * cs)); };
        const char* src = (const char*)gs->x[slice >> 5][r * 16];
        uint32_t off[2];
#pragma unroll
        for (int u = 0; u < 2; u++) {
            const int tt = (lane & 7) >> 1, row = 8 * tt + 2 * ((2 * u + (lane >> 4) + tt) & 3) + (lane & 1);
            off[u] = sb + w * 2048 + row * 32 + ((((lane >> 3) ^ (row >> 2)) & 1) << 4);
        }
        uint32_t fin[2], rcv[2];
#pragma unroll
        for (int e = 0; e < 2; e++) {
            const uint32_t o = t * 16 + (e ^ (t >> 1)) * 8 + g;
            fin[e] = __shfl_sync(0xffffffffu, sb + SM_FIN + (w >> 1) * 512 + o * 8 + ((w ^ t) & 1) * 4, lane);
            rcv[e] = __shfl_sync(0xffffffffu, sb + SM_RCV + o * 4, lane);
        }
        const uint32_t cnt = __shfl_sync(0xffffffffu, sb + SM_CNT + lane * 4, lane), sum = __shfl_sync(0xffffffffu, sb + SM_FIN + lane * 16, lane);
        const uint32_t inc = __shfl_sync(0xffffffffu, lane, 1 + r), last = __shfl_sync(0xffffffffu, lane, 7 + 7 * r);
        const uint32_t snd = __shfl_sync(0xffffffffu, map_cta(sb + SM_RCV + lane * 8, 0), lane),
                       sbar = __shfl_sync(0xffffffffu, map_cta(sb + SM_LAST + 8 + (lane & 16), 0), lane & 15);
        const uint64_t dst = __shfl_sync(0xffffffffu, (unsigned long long)(out + (lane >> 3) * 1024 + slice * 16 + ((lane ^ (lane >> 2 & 4)) & 7) * 2), lane);
        uint32_t a[2][4][4];
        uint4 x[8];
        float c[4][4];
        auto load_w = [&](int i) {
            mbar_wait(i < 2 ? sb + SM_FULL + (IT_WO + i) * 8 : sb + SM_LAST + w * 16 + (i & 1) * 8);
#pragma unroll
            for (int q = 0; q < 4; q++)
                ldsm4t(slot_off(IT_WO + i) + off[q & 1] + (q >> 1) * 1024, a[i & 1][q][0], a[i & 1][q][1], a[i & 1][q][2], a[i & 1][q][3]);
        };
        auto mma_w = [&](int i) {
#pragma unroll
            for (int q = 0; q < 4; q++) {
                const uint4& b = x[2 * i + (q >> 1)];
                if (i == 0) c[q][0] = c[q][1] = c[q][2] = c[q][3] = 0.f;
                mma16816(c[q], a[i & 1][q][0], a[i & 1][q][1], a[i & 1][q][2], a[i & 1][q][3], (q & 1) ? b.z : b.x, (q & 1) ? b.w : b.y);
            }
        };
        load_w(0); load_w(1);
        mbar_wait(sb + SM_FULL + IT_X * 8);
#pragma unroll
        for (int i = 0; i < 8; i++) x[i] = lds128(sb + slot_off(IT_X) + xoff(i));
        int it = 0;
        while (true) {
            mma_w(0); mma_w(1);
            if (!refetch(x, [&](int i) { return src + xoff(i); })) break;
            if (++it > SPIN_LIMIT) __trap();
        }
        load_w(2);
        mma_w(2);
        load_w(3);
        uint32_t rank;
        const float pr[2] = {ldsf_if(rcv[0], w == 0 && r == 0), ldsf_if(rcv[1], w == 0 && r == 0)};
        mma_w(3);
#pragma unroll
        for (int e = 0; e < 2; e++) stv(fin[e], (((c[0][2 * e] + pr[e]) + c[1][2 * e]) + c[2][2 * e]) + c[3][2 * e]);
        float4 p[4];
        float s0, s1;
        auto add_up = [&]() {
#pragma unroll
            for (int k = 0; k < 4; k++) p[k] = ldv4(sum + k * 512);
            const float a0 = ((p[0].x + p[0].y) + (p[1].x + p[1].y)) + (p[2].x + p[2].y), b0 = p[3].x + p[3].y;
            const float a1 = ((p[0].z + p[0].w) + (p[1].z + p[1].w)) + (p[2].z + p[2].w), b1 = p[3].z + p[3].w;
            s0 = a0 + b0; s1 = a1 + b1;
            uint32_t nan;
            asm("{\n.reg .pred p;\nsetp.ne.u32 p, %5, 0;\nsetp.nan.or.f32 p, %1, %2, p;\nsetp.nan.or.f32 p, %3, %4, p;\nselp.u32 %0, 1, 0, p;\n}"
                : "=r"(nan) : "f"(a0), "f"(a1), "f"(b0), "f"(b1), "r"(r));
            return nan;
        };
        asm volatile("atom.relaxed.cta.shared.add.u32 %0, [%1], %2;" : "=r"(rank) : "r"(cnt), "r"(inc) : "memory");
        const uint32_t redo = add_up();
        st_if(dst, pack_bf16(s0, s1), rank == 7);
        if (!redo) return;
        const bool num = s0 == s0 && s1 == s1;
        st_async64_if(snd, s0, s1, sbar, rank == 14 && num);
        if (rank != last || num) return;
        auto mx = [](float4 q) { return max(max(__float_as_uint(q.x), __float_as_uint(q.y)), max(__float_as_uint(q.z), __float_as_uint(q.w))); };
        for (it = 0; max(max(mx(p[0]), mx(p[1])), max(mx(p[2]), mx(p[3]))) == EMPTY; it++) {
            add_up();
            if (it > SPIN_LIMIT) __trap();
        }
        if (r) st_async64_if(snd, s0, s1, sbar, true);
        else st_if(dst, pack_bf16(s0, s1), true);
    }
}

typedef CUresult (*EncodeTiledFn)(CUtensorMap*, CUtensorMapDataType, cuuint32_t, void*, const cuuint64_t*,
                                  const cuuint64_t*, const cuuint32_t*, const cuuint32_t*, CUtensorMapInterleave,
                                  CUtensorMapSwizzle, CUtensorMapL2promotion, CUtensorMapFloatOOBfill);

void encode_map(EncodeTiledFn enc, CUtensorMap* tm, const void* p, cuuint64_t cols, cuuint64_t rows,
                cuuint32_t brows, cuuint32_t bblk) {
    cuuint64_t dims[3] = {64, rows, cols / 64};
    cuuint64_t strides[2] = {cols * 2, 128};
    cuuint32_t box[3] = {64, brows, bblk};
    cuuint32_t es[3] = {1, 1, 1};
    enc(tm, CU_TENSOR_MAP_DATA_TYPE_BFLOAT16, 3, const_cast<void*>(p), dims, strides, box, es,
        CU_TENSOR_MAP_INTERLEAVE_NONE, CU_TENSOR_MAP_SWIZZLE_128B, CU_TENSOR_MAP_L2_PROMOTION_L2_256B,
        CU_TENSOR_MAP_FLOAT_OOB_FILL_NONE);
}

void encode_slice_map(EncodeTiledFn enc, CUtensorMap* tm, const void* p, cuuint64_t cols, cuuint64_t rows,
                      cuuint32_t bcols, cuuint32_t brows) {
    cuuint64_t dims[3] = {cols, 256, rows / 256};
    cuuint64_t strides[2] = {cols * 2, cols * 512};
    cuuint32_t box[3] = {bcols, brows, 1};
    cuuint32_t es[3] = {1, 1, 1};
    enc(tm, CU_TENSOR_MAP_DATA_TYPE_BFLOAT16, 3, const_cast<void*>(p), dims, strides, box, es, CU_TENSOR_MAP_INTERLEAVE_NONE,
        bcols == 16 ? CU_TENSOR_MAP_SWIZZLE_32B : CU_TENSOR_MAP_SWIZZLE_64B, CU_TENSOR_MAP_L2_PROMOTION_L2_128B,
        CU_TENSOR_MAP_FLOAT_OOB_FILL_NONE);
}

}

extern "C" void kernel_launch(void* const* d_in, const int* in_sizes, int n_in, void* d_out, int out_size) {
    (void)in_sizes; (void)n_in; (void)out_size;
    static EncodeTiledFn enc = nullptr;
    static Scratch* gs = nullptr;
    if (!enc) {
        cudaGetSymbolAddress((void**)&gs, g_scratch);
        void* fn = nullptr;
        cudaDriverEntryPointQueryResult qr;
        cudaGetDriverEntryPoint("cuTensorMapEncodeTiled", &fn, cudaEnableDefault, &qr);
        enc = (EncodeTiledFn)fn;
        cudaFuncSetAttribute(fused_decode_kernel, cudaFuncAttributeMaxDynamicSharedMemorySize, SM_END);
    }
    Maps maps;
    encode_map(enc, &maps.wuk, d_in[8], 4096, 512, 32, 2);
    encode_slice_map(enc, &maps.wuv, d_in[9], 4096, 512, 32, 128);
    encode_slice_map(enc, &maps.woB, d_in[10], 512, 4096, 16, 256);
    encode_slice_map(enc, &maps.woA, d_in[4], 512, 4096, 16, 256);
    encode_slice_map(enc, &maps.endB, d_in[10], 512, 4096, 16, 64);
    encode_slice_map(enc, &maps.endA, d_in[4], 512, 4096, 16, 64);
    encode_map(enc, &maps.ckv, d_in[6], 512, 16384, 8, 8);
    fused_decode_kernel<<<NCTA, NTHR, SM_END>>>((const __nv_bfloat16*)d_in[0], (const __nv_bfloat16*)d_in[5],
                                                (const __nv_bfloat16*)d_in[7], (const __nv_bfloat16*)d_in[3],
                                                (const __nv_bfloat16*)d_in[1] + 3072 * 128, (const __nv_bfloat16*)d_in[2] + 3072 * 128,
                                                (__nv_bfloat16*)d_out, gs, maps);
}
```

```cpp
#include <cuda_runtime.h>
#include <cuda_bf16.h>
#include <cuda.h>
#include <stdint.h>

namespace {

constexpr int NCTA   = 128;
constexpr int NSLOT  = 13;
constexpr int SLOT   = 16384;
constexpr int NITEM  = 56;
constexpr int NTHR   = 384;

constexpr int INFLIGHT = 4;
constexpr int PACE     = 644;
constexpr int LEAD     = 530;
constexpr int TAPER    = 260;
constexpr int OS0      = -60;
constexpr int OS1      = 241;
constexpr int OF0      = -200;
constexpr int OF1      = 480;
constexpr int OF2      = 1690;
constexpr int OF3      = 160;
constexpr int XS       = 1340;
constexpr int XF       = 1640;
constexpr int OB       = 50;
constexpr int XB       = 90;
constexpr int OPGAP    = 250;
constexpr int NWIN     = 4;
__device__ constexpr int win_pos(int k)  { return k == 0 ? 10 : k == 1 ? 20 : k == 2 ? 31 : 38; }
__device__ constexpr int win_late(int k) { return k == 0 ? 1810 : k == 1 ? 1845 : k == 2 ? 1845 : 1735; }
constexpr int GAIN     = 11;

constexpr int IT_WQB = 0, IT_WQA = 2, IT_WUK = 4, IT_K0 = 6, IT_Q = 14, IT_C = 16, IT_K1 = 24, IT_V0 = 32,
              IT_OP = 40, IT_V1 = 42, IT_WUV = 50, IT_WO = 52;
constexpr int IT_X = 56;
constexpr int BAR_LAT = 55;

constexpr int SM_FULL  = NSLOT * SLOT;
constexpr int SM_EMPTY = SM_FULL + 512;
constexpr int SM_IN0   = SM_EMPTY + 512;
constexpr int SM_IN1   = SM_IN0 + 1088;
constexpr int SM_SC    = SM_IN1 + 1088;
constexpr int SM_PA    = SM_SC + 4096;
constexpr int SM_PF    = SM_PA + 2048;
constexpr int SM_MX    = SM_PF + 8192;
constexpr int SM_ML    = SM_MX + 1024;
constexpr int SM_LAST  = SM_ML + 128;
constexpr int SM_CNT   = SM_LAST + 128;
constexpr int SM_RCV   = SM_CNT + 128;
constexpr int SM_PACE  = SM_RCV + 256;
constexpr int SM_END   = SM_PACE + 32;
constexpr int SM_LAT   = SM_PF + 4096;
constexpr int SM_FIN   = SM_SC;
constexpr int SM_SUM   = SM_IN0;
static_assert(SM_END <= 232448, "smem");

struct Maps { CUtensorMap wuk, wuv, woA, woB, ckv, endA, endB; };

struct Scratch {
    uint64_t late[16];
    unsigned cnt[NCTA][32];
    float    part[2][NCTA][512];
    uint32_t x[2][32][256];
    uint32_t lat[32][4][256];
    uint4    q[4][2048];
    uint4    op[NCTA][2048];
    float2   stat[32][128];
};
__device__ __align__(128) Scratch g_scratch;

constexpr int SPIN_LIMIT = 1 << 22;

__device__ __forceinline__ uint32_t smem_u32(const void* p) { return (uint32_t)__cvta_generic_to_shared(p); }
__device__ __forceinline__ void mbar_init(uint32_t bar, uint32_t cnt) {
    asm volatile("mbarrier.init.shared::cta.b64 [%0], %1;" ::"r"(bar), "r"(cnt) : "memory");
}
__device__ __forceinline__ void mbar_expect_tx(uint32_t bar, uint32_t bytes) {
    asm volatile("mbarrier.arrive.expect_tx.shared::cta.b64 _, [%0], %1;" ::"r"(bar), "r"(bytes) : "memory");
}
__device__ __forceinline__ void mbar_arrive(uint32_t bar) {
    asm volatile("mbarrier.arrive.shared::cta.b64 _, [%0];" ::"r"(bar) : "memory");
}
__device__ __forceinline__ void mbar_arrive8(uint32_t bar) {
    asm volatile("mbarrier.arrive.shared::cta.b64 _, [%0], 8;" ::"r"(bar) : "memory");
}
__device__ __forceinline__ void mbar_wait(uint32_t bar) {
    uint32_t done;
    int it = 0;
    do {
        asm volatile("{\n.reg .pred p;\nmbarrier.try_wait.parity.shared::cta.b64 p, [%1], 0;\nselp.u32 %0, 1, 0, p;\n}"
                     : "=r"(done) : "r"(bar) : "memory");
        if (++it > SPIN_LIMIT) __trap();
    } while (!done);
}
__device__ __forceinline__ uint32_t map_cta(uint32_t a, uint32_t rank) {
    uint32_t r; asm("mapa.shared::cluster.u32 %0, %1, %2;" : "=r"(r) : "r"(a), "r"(rank)); return r;
}
__device__ __forceinline__ void st_async64_if(uint32_t a, float x, float y, uint32_t bar, bool on) {
    asm volatile("{\n.reg .pred p;\nsetp.ne.u32 p, %4, 0;\n@p st.async.shared::cluster.mbarrier::complete_tx::bytes.v2.f32 [%0], {%1,%2}, [%3];\n}"
                 ::"r"(a), "f"(x), "f"(y), "r"(bar), "r"((uint32_t)on) : "memory");
}
__device__ __forceinline__ uint64_t evict_first() {
    uint64_t pol; asm volatile("createpolicy.fractional.L2::evict_first.b64 %0, 1.0;" : "=l"(pol)); return pol;
}
#define ELECT "{\n.reg .pred p;\nelect.sync _|p, 0xffffffff;\n@p "
__device__ __forceinline__ void bulk_load(uint32_t dst, const void* src, uint32_t bytes, uint32_t bar, uint64_t pol) {
    asm volatile(ELECT "cp.async.bulk.shared::cluster.global.mbarrier::complete_tx::bytes.L2::cache_hint [%0], [%1], %2, [%3], %4;\n}"
                 ::"r"(dst), "l"(src), "r"(bytes), "r"(bar), "l"(pol) : "memory");
}
__device__ __forceinline__ void bulk_load_nohint(uint32_t dst, const void* src, uint32_t bytes, uint32_t bar) {
    asm volatile("cp.async.bulk.shared::cluster.global.mbarrier::complete_tx::bytes [%0], [%1], %2, [%3];"
                 ::"r"(dst), "l"(src), "r"(bytes), "r"(bar) : "memory");
}
__device__ __forceinline__ void tma3d(uint32_t dst, const CUtensorMap* tm, int c0, int c1, int c2, uint32_t bar, uint64_t pol) {
    asm volatile(ELECT "cp.async.bulk.tensor.3d.shared::cluster.global.mbarrier::complete_tx::bytes.L2::cache_hint [%0], [%1, {%3, %4, %5}], [%2], %6;\n}"
                 ::"r"(dst), "l"(tm), "r"(bar), "r"(c0), "r"(c1), "r"(c2), "l"(pol) : "memory");
}
__device__ __forceinline__ void ldsm4(uint32_t a, uint32_t& r0, uint32_t& r1, uint32_t& r2, uint32_t& r3) {
    asm volatile("ldmatrix.sync.aligned.m8n8.x4.shared.b16 {%0,%1,%2,%3}, [%4];"
                 : "=r"(r0), "=r"(r1), "=r"(r2), "=r"(r3) : "r"(a) : "memory");
}
__device__ __forceinline__ void ldsm4t(uint32_t a, uint32_t& r0, uint32_t& r1, uint32_t& r2, uint32_t& r3) {
    asm volatile("ldmatrix.sync.aligned.m8n8.x4.trans.shared.b16 {%0,%1,%2,%3}, [%4];"
                 : "=r"(r0), "=r"(r1), "=r"(r2), "=r"(r3) : "r"(a) : "memory");
}
__device__ __forceinline__ void mma16816(float (&c)[4], uint32_t a0, uint32_t a1, uint32_t a2, uint32_t a3,
                                         uint32_t b0, uint32_t b1) {
    asm volatile("mma.sync.aligned.m16n8k16.row.col.f32.bf16.bf16.f32 {%0,%1,%2,%3}, {%4,%5,%6,%7}, {%8,%9}, {%0,%1,%2,%3};"
                 : "+f"(c[0]), "+f"(c[1]), "+f"(c[2]), "+f"(c[3])
                 : "r"(a0), "r"(a1), "r"(a2), "r"(a3), "r"(b0), "r"(b1));
}
__device__ __forceinline__ uint32_t lds32(uint32_t a) {
    uint32_t v; asm volatile("ld.shared.b32 %0, [%1];" : "=r"(v) : "r"(a) : "memory"); return v;
}
__device__ __forceinline__ float ldsf(uint32_t a) {
    float v; asm volatile("ld.shared.f32 %0, [%1];" : "=f"(v) : "r"(a) : "memory"); return v;
}
__device__ __forceinline__ float2 ldsf2(uint32_t a) {
    float2 v; asm volatile("ld.shared.v2.f32 {%0,%1}, [%2];" : "=f"(v.x), "=f"(v.y) : "r"(a) : "memory"); return v;
}
__device__ __forceinline__ float4 ldsf4(uint32_t a) {
    float4 v; asm volatile("ld.shared.v4.f32 {%0,%1,%2,%3}, [%4];" : "=f"(v.x), "=f"(v.y), "=f"(v.z), "=f"(v.w) : "r"(a) : "memory"); return v;
}
__device__ __forceinline__ uint4 lds128(uint32_t a) {
    uint4 v; asm volatile("ld.shared.v4.b32 {%0,%1,%2,%3}, [%4];" : "=r"(v.x), "=r"(v.y), "=r"(v.z), "=r"(v.w) : "r"(a) : "memory"); return v;
}
__device__ __forceinline__ float ldsf_if(uint32_t a, bool on) {
    float v = 0.f;
    asm volatile("{\n.reg .pred p;\nsetp.ne.u32 p, %2, 0;\n@p ld.shared.f32 %0, [%1];\n}" : "+f"(v) : "r"(a), "r"((uint32_t)on) : "memory");
    return v;
}
__device__ __forceinline__ float4 ldv4(uint32_t a) {
    float4 v; asm volatile("ld.volatile.shared.v4.f32 {%0,%1,%2,%3}, [%4];" : "=f"(v.x), "=f"(v.y), "=f"(v.z), "=f"(v.w) : "r"(a) : "memory"); return v;
}
__device__ __forceinline__ void stv(uint32_t a, float v) { asm volatile("st.volatile.shared.f32 [%0], %1;" ::"r"(a), "f"(v) : "memory"); }
__device__ __forceinline__ void sts16(uint32_t a, uint16_t v) { asm volatile("st.shared.b16 [%0], %1;" ::"r"(a), "h"(v) : "memory"); }
__device__ __forceinline__ void sts32(uint32_t a, uint32_t v) { asm volatile("st.shared.b32 [%0], %1;" ::"r"(a), "r"(v) : "memory"); }
__device__ __forceinline__ void stsf(uint32_t a, float v) { asm volatile("st.shared.f32 [%0], %1;" ::"r"(a), "f"(v) : "memory"); }
__device__ __forceinline__ void sts64(uint32_t a, uint32_t x, uint32_t y) {
    asm volatile("st.shared.v2.b32 [%0], {%1,%2};" ::"r"(a), "r"(x), "r"(y) : "memory");
}
__device__ __forceinline__ void sts128(uint32_t a, uint4 v) {
    asm volatile("st.shared.v4.b32 [%0], {%1,%2,%3,%4};" ::"r"(a), "r"(v.x), "r"(v.y), "r"(v.z), "r"(v.w) : "memory");
}
__device__ __forceinline__ uint32_t pack_bf16(float lo, float hi) {
    uint32_t r; asm("cvt.rn.bf16x2.f32 %0, %1, %2;" : "=r"(r) : "f"(hi), "f"(lo)); return r;
}
__device__ __forceinline__ float bf_lo(uint32_t v) { return __uint_as_float(v << 16); }
__device__ __forceinline__ float bf_hi(uint32_t v) { return __uint_as_float(v & 0xffff0000u); }
__device__ __forceinline__ float ex2(float x) { float y; asm("ex2.approx.ftz.f32 %0, %1;" : "=f"(y) : "f"(x)); return y; }
__device__ __forceinline__ uint32_t timer_ns() { uint32_t t; asm volatile("mov.u32 %0, %%globaltimer_lo;" : "=r"(t)); return t; }
__device__ __forceinline__ void bar_consumers() { asm volatile("bar.sync 1, 256;" ::: "memory"); }

__device__ __forceinline__ uint32_t tagf(float v, uint32_t tag) { return (__float_as_uint(v) & 0xffffff00u) | tag; }
__device__ __forceinline__ uint2 ld_rlx2(const void* p) {
    uint64_t v; asm volatile("ld.relaxed.gpu.global.b64 %0, [%1];" : "=l"(v) : "l"(p) : "memory");
    return make_uint2((uint32_t)v, (uint32_t)(v >> 32));
}
__device__ __forceinline__ float untag(uint32_t v) { return __uint_as_float(v & 0xffffff00u); }

__device__ __forceinline__ uint32_t slot_off(int item) { return (uint32_t)(item % NSLOT) * SLOT; }

template <bool TRANS, bool TMA = true>
__device__ __forceinline__ void tile_mma(uint32_t sb, int item, uint32_t in, int w, int lane, float (&acc)[2][2]) {
    const int g = lane >> 2, t = lane & 3;
    float c[4][4];
#pragma unroll
    for (int i = 0; i < 16; i++) (&c[0][0])[i] = 0.f;
    uint32_t a[16];
    const uint32_t ia = in + (g & 3) * 272 + t * 4;
#pragma unroll
    for (int i = 0; i < 16; i++) a[i] = lds32(ia + i * 16);
    const uint32_t s0 = sb + slot_off(item), s1 = sb + slot_off(item + 1);
    if (TRANS) {
        const int r = (lane & 7) + (lane & 8);
        const int ch = 2 * (w & 3) + (lane >> 4);
        const uint32_t off = (TMA ? (w >> 2) * 8192 + r * 128 : (w >> 2) * 128 + r * 256) + ((ch ^ (lane & 7)) << 4);
#pragma unroll
        for (int kk = 0; kk < 8; kk++) {
            if (TMA && (kk & 3) == 0) mbar_wait(sb + SM_FULL + (item + (kk >> 2)) * 8);
            uint32_t r0, r1, r2, r3;
            ldsm4t(((kk >> 2) ? s1 : s0) + off + (kk & 3) * (TMA ? 2048 : 4096), r0, r1, r2, r3);
            mma16816(c[2 * (kk & 1)],     a[2 * kk], 0u, a[2 * kk + 1], 0u, r0, r1);
            mma16816(c[2 * (kk & 1) + 1], a[2 * kk], 0u, a[2 * kk + 1], 0u, r2, r3);
        }
    } else {
        mbar_wait(sb + SM_FULL + (item + (w >> 2)) * 8);
        const int r = 16 * (w & 3) + (lane & 7) + ((lane >> 4) << 3);
        const uint32_t base = ((w >> 2) ? s1 : s0) + (r & 32) * 128 + r * 128 + ((((lane >> 3) & 1) ^ (lane & 7)) << 4);
#pragma unroll
        for (int kk = 0; kk < 8; kk++) {
            uint32_t r0, r1, r2, r3;
            ldsm4((base ^ ((kk & 3) << 5)) + (kk >> 2) * 4096, r0, r1, r2, r3);
            mma16816(c[2 * (kk & 1)],     a[2 * kk], 0u, a[2 * kk + 1], 0u, r0, r1);
            mma16816(c[2 * (kk & 1) + 1], a[2 * kk], 0u, a[2 * kk + 1], 0u, r2, r3);
        }
    }
    __syncwarp();
    if (lane == 0) {
        mbar_arrive(sb + SM_EMPTY + item * 8);
        mbar_arrive(sb + SM_EMPTY + (item + 1) * 8);
    }
    acc[0][0] = c[0][0] + c[2][0]; acc[0][1] = c[0][1] + c[2][1];
    acc[1][0] = c[1][0] + c[3][0]; acc[1][1] = c[1][1] + c[3][1];
}

__device__ __forceinline__ void publish(float* dst, int w, int lane, const float (&acc)[2][2], uint32_t tag) {
    if (lane < 16)
        asm volatile("st.relaxed.gpu.global.v4.b32 [%0], {%1,%2,%3,%4};" ::"l"(dst + w * 64 + lane * 4),
                     "r"(tagf(acc[0][0], tag)), "r"(tagf(acc[0][1], tag)), "r"(tagf(acc[1][0], tag)), "r"(tagf(acc[1][1], tag)) : "memory");
}

__device__ __forceinline__ void gather(const float* part, uint32_t in, int tid, uint32_t tag) {
    const float* p = part + tid * 2;
    uint2 v0, v1, v2, v3;
    int it = 0;
    while (true) {
        v0 = ld_rlx2(p); v1 = ld_rlx2(p + 512); v2 = ld_rlx2(p + 1024); v3 = ld_rlx2(p + 1536);
        uint32_t bad = ((v0.x ^ tag) | (v0.y ^ tag) | (v1.x ^ tag) | (v1.y ^ tag) |
                        (v2.x ^ tag) | (v2.y ^ tag) | (v3.x ^ tag) | (v3.y ^ tag)) & 0xffu;
        if (__all_sync(0xffffffffu, bad == 0)) break;
        if (++it > SPIN_LIMIT) __trap();
    }
    float x = (untag(v0.x) + untag(v1.x)) + (untag(v2.x) + untag(v3.x));
    float y = (untag(v0.y) + untag(v1.y)) + (untag(v2.y) + untag(v3.y));
    sts32(in + ((tid >> 3) & 3) * 272 + (tid >> 5) * 32 + (tid & 1) * 16 + (tid & 6) * 2, pack_bf16(x, y));
    bar_consumers();
}

constexpr uint32_t EMPTY = 0xffffffffu;
__device__ __forceinline__ void st_rlx(uint32_t* p, uint32_t v) {
    asm volatile("st.relaxed.gpu.global.b32 [%0], %1;" ::"l"(p), "r"(v) : "memory");
}
__device__ __forceinline__ void st_rlx_if(uint64_t p, uint32_t v, bool on) {
    asm volatile("{\n.reg .pred p;\nsetp.ne.u32 p, %2, 0;\n@p st.relaxed.gpu.global.b32 [%0], %1;\n}" ::"l"(p), "r"(v), "r"((uint32_t)on) : "memory");
}
__device__ __forceinline__ void st_if(uint64_t p, uint32_t v, bool on) {
    asm volatile("{\n.reg .pred p;\nsetp.ne.u32 p, %2, 0;\n@p st.global.b32 [%0], %1;\n}" ::"l"(p), "r"(v), "r"((uint32_t)on) : "memory");
}
__device__ __forceinline__ void st_rlx2(uint32_t* p, uint32_t v0, uint32_t v1) {
    asm volatile("st.relaxed.gpu.global.v2.b32 [%0], {%1,%2};" ::"l"(p), "r"(v0), "r"(v1) : "memory");
}
__device__ __forceinline__ void ld_rlx4_if(uint4& v, const void* p, bool need) {
    asm volatile("{\n.reg .pred p;\nsetp.ne.u32 p, %5, 0;\n@p ld.relaxed.gpu.global.v4.b32 {%0,%1,%2,%3}, [%4];\n}"
                 : "+r"(v.x), "+r"(v.y), "+r"(v.z), "+r"(v.w) : "l"(p), "r"((uint32_t)need) : "memory");
}

template <class F>
__device__ __forceinline__ bool refetch(uint4 (&x)[8], F addr) {
    uint32_t m[8], m0 = 0;
#pragma unroll
    for (int i = 0; i < 8; i++) {
        m[i] = max(max(x[i].x, x[i].y), max(x[i].z, x[i].w));
        m0 = max(m0, m[i]);
    }
    if (!__any_sync(0xffffffffu, m0 == EMPTY)) return false;
#pragma unroll
    for (int i = 0; i < 8; i++) ld_rlx4_if(x[i], addr(i), m[i] == EMPTY);
    return true;
}

__device__ __forceinline__ unsigned read_counter(const unsigned* cnt) {
    unsigned v;
    asm volatile("ld.relaxed.gpu.global.u32 %0, [%1];" : "=r"(v) : "l"(cnt) : "memory");
    return v;
}
__device__ __forceinline__ unsigned epoch_of(unsigned cnt) {
    asm volatile("" : "+r"(cnt) :: "memory");
    return cnt + 1;
}
__device__ __forceinline__ uint32_t epoch_tag(unsigned epoch) { return (epoch & 0x7fu) | 0x80u; }

__device__ __forceinline__ void signal_and_wait(unsigned* cnt, unsigned target, int lane) {
    if (lane == 0) asm volatile("red.release.gpu.global.add.u32 [%0], 1;" ::"l"(cnt) : "memory");
    int it = 0;
    while (true) {
        unsigned v;
        asm volatile("ld.acquire.gpu.global.u32 %0, [%1];" : "=r"(v) : "l"(cnt) : "memory");
        if (__all_sync(0xffffffffu, (int)(v - target) >= 0)) break;
        if (++it > SPIN_LIMIT) __trap();
    }
    asm volatile("fence.proxy.async.global;" ::: "memory");
}

__global__ void __cluster_dims__(2, 1, 1) __launch_bounds__(NTHR, 1)
fused_decode_kernel(const uint2 first, const __nv_bfloat16* __restrict__ xA, const __nv_bfloat16* __restrict__ xB,
                    const __nv_bfloat16* __restrict__ wqB, const __nv_bfloat16* __restrict__ wqA,
                    const __nv_bfloat16* __restrict__ Kc, const __nv_bfloat16* __restrict__ Vc,
                    __nv_bfloat16* __restrict__ out, Scratch* gs, const __grid_constant__ Maps maps) {
    extern __shared__ __align__(1024) unsigned char smem_raw[];
    const uint32_t sb = smem_u32(smem_raw);
    const int tid = threadIdx.x, lane = tid & 31;
    const int cta = blockIdx.x, h = cta >> 2, j = cta & 3;
    const size_t kv_off = (size_t)blockIdx.x * 4096 * 128;
    asm volatile("{\n.reg .b32 l;\n.reg .b64 a;\nmad.lo.u32 l, %2, 32, %0;\nmov.b64 a, {l, %1};\nprefetch.global.L2 [a];\n}"
                 ::"r"(first.x + blockIdx.x * (NTHR * 32)), "r"(first.y), "r"(threadIdx.x) : "memory");
    const uint32_t trow = threadIdx.x >> 4;
    const uint32_t tile_src = trow * (8192 - 256) + (threadIdx.x * 16 + ((blockIdx.x * 0x100040u) & 0x301f00u));
    const uint32_t tile_dst = sb + ((threadIdx.x ^ (trow & 7)) << 4);
    auto lsu_piece = [&](int k) {
#pragma unroll
        for (int q = 2 * k; q < 2 * k + 2; q++)
            asm volatile("cp.async.cg.shared.global [%0], [%1], 16;" ::"r"(tile_dst + q * 4096),
                         "l"(reinterpret_cast<const char*>((k < 4 ? wqB : wqA) + (q & 7) * 16 * 4096) + tile_src) : "memory");
        if ((k & 3) == 3) asm volatile("cp.async.commit_group;" ::: "memory");
    };
    if (tid < 256) {
#pragma unroll
        for (int k = 0; k < 4; k++) lsu_piece(k);
    }
    const uint32_t tz = timer_ns() - LEAD;
    unsigned cnt1;
    if (tid < 256) cnt1 = read_counter(gs->cnt[blockIdx.x]);
    uint4 xv;
    if (tid < 128) {
        const __nv_bfloat16* x = (tid < 64 ? xB : xA) + ((tid >> 4) & 3) * 512 + j * 128 + (tid & 15) * 8;
        xv = __ldg(reinterpret_cast<const uint4*>(x));
    }
    const int w = __shfl_sync(0xffffffffu, tid >> 5, 0);
    const int pr = cta >> 1;
    const int slice = pr < 4 ? pr : pr < 36 ? 4 + ((pr - 4) & 7) * 4 + ((pr - 4) >> 3) : 36 + (pr - 36) % 7 * 4 + (pr - 36) / 7;

    if (w >= 8) {
        if (lane == 0) {
            const uint32_t full = sb + SM_FULL + (IT_WUK + (w & 3) * 14) * 8, empty = sb + SM_EMPTY + (w & 3) * 13 * 8,
                           last = sb + SM_LAST + (w & 3) * 32;
#pragma unroll
            for (int i = 0; i < 14; i++) mbar_init(full + i * 8, 1);
#pragma unroll
            for (int i = 0; i < 13; i++) mbar_init(empty + i * 8, 8);
#pragma unroll
            for (int i = 0; i < 4; i++) mbar_init(last + i * 8, 1);
#pragma unroll
            for (int i = 0; i < 14; i++) {
                const int b = IT_WUK + 42 + i;
                mbar_expect_tx(full + i * 8, (w == 10 && b - 14 == IT_OP) ? SLOT + 1024 : (w == 11 && b == BAR_LAT) ? 4096 : SLOT);
            }
#pragma unroll
            for (int i = 0; i < 4; i++) mbar_expect_tx(last + i * 8, i == 1 && w == 8 && !(j & 1) ? 2048 + 256 : 2048);
            asm volatile("fence.mbarrier_init.release.cluster;" ::: "memory");
            if (w == 10) sts64(sb + SM_PACE, tz, PACE * 16);
        }
        asm volatile("bar.sync 2, 128;" ::: "memory");
        asm volatile("bar.arrive 4, 384;" ::: "memory");
    }
    if (w == 10) {
        if (lane == 0) {
            int slope = 0;
#pragma unroll
            for (int k = 0; k < NWIN; k++) {
                const int c = win_pos(k);
                uint32_t acc = 0;
#pragma unroll
                for (int p = c; p < c + 4; p++) {
                    mbar_wait(sb + SM_FULL + (p < IT_Q ? p : p < IT_OP - 2 ? p + 2 : p + 4) * 8);
                    acc += timer_ns() - tz - p * PACE - ((p * slope) >> 4);
                }
                if (k == 0) mbar_wait(sb + SM_FULL + IT_Q * 8);
                asm volatile("red.relaxed.gpu.global.add.u64 [%0], %1;" ::"l"(&gs->late[k]),
                             "l"((uint64_t)tz << 32 | (1u << 24) + min(acc >> 2, 65535u)) : "memory");
                uint2 v;
                int it = 0;
                do { v = ld_rlx2(&gs->late[k]); } while ((v.x >> 24) != NCTA && ++it < 1000);
                if (it == 1000) break;
                const int late = (v.x & 0xffffffu) / NCTA;
                slope = max(-320, min(320, slope + (late - win_late(k)) * (GAIN * 2) / (2 * c + 3)));
                sts64(sb + SM_PACE, k < NWIN - 1 ? tz : tz + (int)(v.y - tz * NCTA) / NCTA, PACE * 16 + slope);
            }
        }
        return;
    }
    if (w >= 8) {
        auto wait_due = [&](uint32_t p, uint32_t shift) {
            uint32_t a, b;
            do {
                asm volatile("ld.volatile.shared.v2.b32 {%0,%1}, [%2];" : "=r"(a), "=r"(b) : "r"(sb + SM_PACE) : "memory");
            } while (__all_sync(0xffffffffu, (int)(timer_ns() - (a + ((p * b) >> 4) + shift)) < 0));
        };
        if (w != 9) {
            const int half = w & 1;
            const uint64_t pol = evict_first();
            int slot = IT_WUK, tail = IT_WUK - INFLIGHT;
            uint32_t np = IT_WUK, shift = half ? PACE / 4 : -(PACE / 4);
#pragma unroll 1
            for (int i = IT_WUK; i < NITEM; i++) {
                const uint32_t dst = sb + slot * SLOT + half * (SLOT / 2), bar = sb + SM_FULL + i * 8;
                if (++slot == NSLOT) slot = 0;
                if ((i & ~1) == IT_Q || (i & ~1) == IT_OP) continue;
                const bool ckv = i >= IT_C && i < IT_K1, wo = i >= IT_WO;
                const bool tiled = ckv || i < IT_K0 || i >= IT_WUV;
                const CUtensorMap* tm = &maps.wuk + (i < IT_K0 ? 0 : ckv ? 4 : wo ? 2 + (slice >> 5) : 1);
                const int c0 = wo ? (slice & 31) * 16 : i >= IT_WUV ? cta * 32 : 0;
                const int c1 = i < IT_K0 ? j * 128 + (i & 1) * 64 + half * 32 : ckv ? cta * 128 + (i - IT_C) * 16 + half * 8 : wo ? 0 : half * 128;
                const int c2 = i < IT_K0 ? h * 2 : ckv ? 0 : wo ? (j & 1) * 8 + (i - IT_WO) * 2 + half : i & 1;
                const int c = i < IT_Q ? i - IT_K0 : i < IT_V0 ? i - IT_K1 + 8 : i < IT_OP ? i - IT_V0 : i - IT_V1 + 8;
                const __nv_bfloat16* src = (i < IT_V0 ? Kc : Vc) + kv_off + (size_t)((c ^ (j & 1) * 7) * 2 + half) * (SLOT / 4);
                if (i >= NSLOT) mbar_wait(sb + SM_EMPTY + (i - NSLOT) * 8);
                if (tail >= IT_WUK && !wo) mbar_wait(sb + SM_FULL + tail * 8);
                ++tail;
                if (tail == IT_Q || tail == IT_OP) tail += 2;
                if (wo) {
                    const int n = c2 & 7;
                    np = IT_WO - 4;
                    shift = TAPER + ((j & 1) ? OS0 + n * OS1 : n < 4 ? OF0 + n * OF1 : OF2 + (n - 4) * OF3) + (slice < 32 ? -OB : OB);
                }
                wait_due(np, shift);
                ++np;
                if (i == IT_WUV - 1) shift += TAPER;
                if (i >= NITEM - 2) {
#pragma unroll
                    for (int q = 0; q < 4; q++)
                        tma3d(dst + q * 2048, tm + 3, c0, q * 64, c2, sb + SM_LAST + half * 64 + q * 16 + (i & 1) * 8, pol);
                }
                else if (tiled) tma3d(dst, tm, c0, c1, c2, bar, pol);
                else bulk_load(dst, src, SLOT / 2, bar, pol);
            }
        } else {
            if (lane < sizeof(Maps) / 128) asm volatile("prefetch.tensormap [%0];" ::"l"(&maps.wuk + lane) : "memory");
            cnt1 = read_counter(gs->cnt[blockIdx.x]);
            asm volatile("bar.sync 3, 288;" ::: "memory");
            const unsigned epoch = epoch_of(cnt1);
            if (lane == 0) st_rlx(gs->cnt[cta], epoch);
            signal_and_wait(&gs->cnt[0][1], epoch * NCTA, lane);
            if (lane == 0) {
                const uint4* q = gs->q[cta >> 5];
                bulk_load_nohint(sb + slot_off(IT_Q), q, SLOT, sb + SM_FULL + IT_Q * 8);
                bulk_load_nohint(sb + slot_off(IT_Q + 1), q + 1024, SLOT, sb + SM_FULL + (IT_Q + 1) * 8);
            }
            asm volatile("bar.sync 3, 288;" ::: "memory");
            signal_and_wait(&gs->cnt[0][2], epoch * NCTA, lane);
            mbar_wait(sb + SM_EMPTY + (IT_OP - NSLOT) * 8);
            mbar_wait(sb + SM_EMPTY + (IT_OP + 1 - NSLOT) * 8);
            if (lane == 0) {
                const uint4* op = gs->op[cta];
                bulk_load_nohint(sb + SM_MX, gs->stat[h], 1024, sb + SM_FULL + IT_OP * 8);
                uint32_t t1 = timer_ns();
#pragma unroll 1
                for (int i = 0; i < 8; i++) {
                    while ((int)(timer_ns() - t1) < 0) {}
                    t1 += OPGAP;
                    bulk_load_nohint(sb + slot_off(IT_OP) + i * 4096, op + i * 256, 4096, sb + SM_FULL + (IT_OP + i / 4) * 8);
                }
            }
            mbar_wait(sb + SM_FULL + (IT_V1 + 4) * 8);
            if (lane == 0) bulk_load_nohint(sb + SM_LAT, gs->lat[h], 4096, sb + SM_FULL + BAR_LAT * 8);
            mbar_wait(sb + SM_EMPTY + (IT_X - NSLOT) * 8);
            mbar_wait(sb + SM_FULL + (IT_WUV + 1) * 8);
            wait_due(IT_WO - 4, TAPER + ((j & 1) ? XS : XF) + (slice < 32 ? -XB : XB));
            if (lane == 0) bulk_load_nohint(sb + slot_off(IT_X), gs->x[slice >> 5][(j & 1) * 16], SLOT, sb + SM_FULL + IT_X * 8);
        }
        return;
    }

    const int g = lane >> 2, t = lane & 3;
    const uint32_t in0 = sb + SM_IN0, in1 = sb + SM_IN1;
    const int ba = cta >> 5, ha = cta & 31;
    uint32_t* const ctx_dst = &gs->x[1][h][(j * 4 + (w & 3)) * 16 + ((g ^ (w & 2)) & 3) * 4 + ((t - w) & 3)];
    uint32_t* const o_dst = &gs->x[0][ha][ba * 64 + ((tid & 60) ^ ((ba & 1) * 16)) + ((t - g) & 3)];
    uint32_t* const lat_dst = &gs->lat[h][g & 3][j * 64 + ((w >> 1) ^ (g & 1)) * 16 + t * 4 + ((w * 2 ^ t) & 2)];
    {
#pragma unroll
        for (int k = 4; k < 8; k++) {
            while (__all_sync(0xffffffffu, (int)(timer_ns() - (tz + (2 * k - 1) * (PACE / 4))) < 0)) {}
            lsu_piece(k);
        }
        if (lane < 16) st_rlx2(lat_dst, EMPTY, EMPTY);
        if (lane >= 16 && w < 4) st_rlx(ctx_dst, EMPTY);
        if (w >= 6) st_rlx(o_dst, EMPTY);
        if (cta == 0 && w == 5) st_rlx((uint32_t*)gs->late + lane, 0u);
        if (tid < 128) sts128((tid < 64 ? in0 : in1) + ((tid >> 4) & 3) * 272 + (tid & 15) * 16, xv);
        asm volatile("cp.async.wait_group 1;" ::: "memory");
    }
    asm volatile("bar.sync 4, 384;" ::: "memory");
    const uint32_t tag = epoch_tag(epoch_of(cnt1));

    float acc[2][2];
    tile_mma<true, false>(sb, IT_WQB, in0, w, lane, acc);
    publish(gs->part[0][cta], w, lane, acc, tag);
    asm volatile("cp.async.wait_group 0;" ::: "memory");
    bar_consumers();
    tile_mma<true, false>(sb, IT_WQA, in1, w, lane, acc);
    publish(gs->part[1][cta], w, lane, acc, tag);
    bar_consumers();

    const float SC = 0.08838834764831845f * 1.4426950408889634f;
    gather(gs->part[0][h * 4], in0, tid, tag);
    tile_mma<false>(sb, IT_WUK, in0, w, lane, acc);
    if (lane < 16) {
        uint32_t* q = reinterpret_cast<uint32_t*>(gs->q[g]) + (2 * j + (w >> 2)) * 1024 + h * 32 + t;
        const int ch = 2 * (w & 3);
        q[((ch) ^ (h & 7)) * 4]     = pack_bf16(acc[0][0] * SC, acc[0][1] * SC);
        q[((ch + 1) ^ (h & 7)) * 4] = pack_bf16(acc[1][0] * SC, acc[1][1] * SC);
    }
    __syncwarp();
    asm volatile("bar.arrive 3, 288;" ::: "memory");
    gather(gs->part[1][ha * 4], in1, tid, tag);

    uint32_t qf[16];
#pragma unroll
    for (int c = 0; c < 8; c++) {
        qf[2 * c]     = lds32(in1 + ba * 272 + ((c ^ g) << 4) + t * 4);
        qf[2 * c + 1] = lds32(in1 + ba * 272 + 128 + ((c ^ g) << 4) + t * 4);
    }
    const uint32_t sc_w = sb + SM_SC + w * 512;
    auto k_item = [&](int item, uint32_t sc) {
        mbar_wait(sb + SM_FULL + item * 8);
        const uint32_t base = sb + slot_off(item) + ((lane & 7) + (lane & 8)) * 256 + ((lane >> 4) << 7);
        float s[4][4];
#pragma unroll
        for (int T = 0; T < 4; T++) { s[T][0] = s[T][1] = s[T][2] = s[T][3] = 0.f; }
#pragma unroll
        for (int c = 0; c < 8; c++) {
            const uint32_t a = base + ((c ^ (lane & 7)) << 4);
#pragma unroll
            for (int T = 0; T < 4; T++) {
                uint32_t r0, r1, r2, r3;
                ldsm4(a + T * 4096, r0, r1, r2, r3);
                mma16816(s[T], r0, r1, r2, r3, qf[2 * c], qf[2 * c + 1]);
            }
        }
        __syncwarp();
        if (lane == 0) mbar_arrive8(sb + SM_EMPTY + item * 8);
        if (t == (g >> 1)) {
#pragma unroll
            for (int T = 0; T < 4; T++) {
                stsf(sc + (16 * T + g) * 4,     (g & 1) ? s[T][1] : s[T][0]);
                stsf(sc + (16 * T + g + 8) * 4, (g & 1) ? s[T][3] : s[T][2]);
            }
        }
    };
    k_item(IT_K0 + w, sc_w);

    {
        float s[2][2][4];
#pragma unroll
        for (int i = 0; i < 16; i++) (&s[0][0][0])[i] = 0.f;
        mbar_wait(sb + SM_FULL + IT_Q * 8);
        mbar_wait(sb + SM_FULL + (IT_Q + 1) * 8);
        mbar_wait(sb + SM_FULL + (IT_C + w) * 8);
        const uint32_t cb0 = sb + slot_off(IT_C + w) + (lane & 7) * 128 + (lane >> 4) * 8192;
        const uint32_t cx = (((lane >> 3) & 1) ^ (lane & 7)) << 4;
        const uint32_t qr = ((lane & 7) + (lane & 8)) * 128;
        const uint32_t qx = ((lane >> 4) ^ (lane & 7)) << 4;
#pragma unroll
        for (int cb = 0; cb < 8; cb++) {
            const uint32_t qb = sb + slot_off(IT_Q + (cb >> 2)) + (cb & 3) * 4096 + qr;
#pragma unroll
            for (int k4 = 0; k4 < 4; k4++) {
                uint32_t b0, b1, b2, b3, a0, a1, a2, a3;
                ldsm4(cb0 + cb * 1024 + (cx ^ (k4 << 5)), b0, b1, b2, b3);
                ldsm4(qb + (qx ^ (k4 << 5)), a0, a1, a2, a3);
                mma16816(s[0][0], a0, a1, a2, a3, b0, b1);
                mma16816(s[0][1], a0, a1, a2, a3, b2, b3);
                ldsm4(qb + 2048 + (qx ^ (k4 << 5)), a0, a1, a2, a3);
                mma16816(s[1][0], a0, a1, a2, a3, b0, b1);
                mma16816(s[1][1], a0, a1, a2, a3, b2, b3);
            }
        }
        __syncwarp();
        if (lane == 0) { mbar_arrive(sb + SM_EMPTY + IT_Q * 8); mbar_arrive(sb + SM_EMPTY + (IT_Q + 1) * 8); }
#pragma unroll
        for (int r = 0; r < 4; r++) {
            const int mt = r >> 1, hi = (r & 1) * 2;
            float m = fmaxf(fmaxf(s[mt][0][hi], s[mt][0][hi + 1]), fmaxf(s[mt][1][hi], s[mt][1][hi + 1]));
            m = fmaxf(m, __shfl_xor_sync(0xffffffffu, m, 1));
            m = fmaxf(m, __shfl_xor_sync(0xffffffffu, m, 2));
            if (t == 0) stsf(sb + SM_MX + (8 * r + g) * 32 + w * 4, m);
        }
        bar_consumers();
        uint32_t pf[2][4];
#pragma unroll
        for (int r = 0; r < 4; r++) {
            const int mt = r >> 1, hi = r & 1;
            const float4 m0 = ldsf4(sb + SM_MX + (8 * r + g) * 32), m1 = ldsf4(sb + SM_MX + (8 * r + g) * 32 + 16);
            const float m = fmaxf(fmaxf(fmaxf(m0.x, m0.y), fmaxf(m0.z, m0.w)), fmaxf(fmaxf(m1.x, m1.y), fmaxf(m1.z, m1.w)));
            const uint32_t p0 = pack_bf16(ex2(s[mt][0][2 * hi] - m), ex2(s[mt][0][2 * hi + 1] - m));
            const uint32_t p1 = pack_bf16(ex2(s[mt][1][2 * hi] - m), ex2(s[mt][1][2 * hi + 1] - m));
            pf[mt][hi] = p0; pf[mt][2 + hi] = p1;
            float l = (bf_lo(p0) + bf_hi(p0)) + (bf_lo(p1) + bf_hi(p1));
            l += __shfl_xor_sync(0xffffffffu, l, 1);
            l += __shfl_xor_sync(0xffffffffu, l, 2);
            if (t == 0) stsf(sb + SM_SUM + (8 * r + g) * 32 + w * 4, l);
        }
        sts128(sb + SM_PF + (w * 2 + 0) * 512 + lane * 16, make_uint4(pf[0][0], pf[0][1], pf[0][2], pf[0][3]));
        sts128(sb + SM_PF + (w * 2 + 1) * 512 + lane * 16, make_uint4(pf[1][0], pf[1][1], pf[1][2], pf[1][3]));
        bar_consumers();
        if (w == 0) {
            const float4 m0 = ldsf4(sb + SM_MX + lane * 32), m1 = ldsf4(sb + SM_MX + lane * 32 + 16);
            const float4 l0 = ldsf4(sb + SM_SUM + lane * 32), l1 = ldsf4(sb + SM_SUM + lane * 32 + 16);
            const float m = fmaxf(fmaxf(fmaxf(m0.x, m0.y), fmaxf(m0.z, m0.w)), fmaxf(fmaxf(m1.x, m1.y), fmaxf(m1.z, m1.w)));
            const float l = ((l0.x + l0.y) + (l0.z + l0.w)) + ((l1.x + l1.y) + (l1.z + l1.w));
            gs->stat[lane][cta] = make_float2(m, l);
        }
        float o[2][8][4];
#pragma unroll
        for (int i = 0; i < 64; i++) (&o[0][0][0])[i] = 0.f;
        const uint32_t vr = w * 1024 + (lane & 7) * 128 + (lane & 8) * 1024;
        const uint32_t vx = ((lane >> 4) ^ (lane & 7)) << 4;
#pragma unroll
        for (int ks = 0; ks < 8; ks++) {
            const uint4 p0 = lds128(sb + SM_PF + (ks * 2 + 0) * 512 + lane * 16);
            const uint4 p1 = lds128(sb + SM_PF + (ks * 2 + 1) * 512 + lane * 16);
            const uint32_t vb = sb + slot_off(IT_C + ks) + vr;
#pragma unroll
            for (int n2 = 0; n2 < 4; n2++) {
                uint32_t b0, b1, b2, b3;
                ldsm4t(vb + (vx ^ (n2 << 5)), b0, b1, b2, b3);
                mma16816(o[0][2 * n2],     p0.x, p0.y, p0.z, p0.w, b0, b1);
                mma16816(o[0][2 * n2 + 1], p0.x, p0.y, p0.z, p0.w, b2, b3);
                mma16816(o[1][2 * n2],     p1.x, p1.y, p1.z, p1.w, b0, b1);
                mma16816(o[1][2 * n2 + 1], p1.x, p1.y, p1.z, p1.w, b2, b3);
            }
            __syncwarp();
            if (lane == 0) mbar_arrive(sb + SM_EMPTY + (IT_C + ks) * 8);
        }
        mbar_wait(sb + SM_FULL + (IT_K1 + 1 + (w * 3 >> 2)) * 8);
#pragma unroll
        for (int r = 0; r < 4; r++) {
            const int mt = r >> 1, hi = (r & 1) * 2;
            uint4* dst = gs->op[(8 * r + g) * 4 + (w >> 1)] + (cta >> 6) * 1024 + (w & 1) * 512 + (cta & 63) * 8;
#pragma unroll
            for (int u = 0; u < 2; u++) {
                uint4 v;
                v.x = pack_bf16(o[mt][4 * u][hi],     o[mt][4 * u][hi + 1]);
                v.y = pack_bf16(o[mt][4 * u + 1][hi], o[mt][4 * u + 1][hi + 1]);
                v.z = pack_bf16(o[mt][4 * u + 2][hi], o[mt][4 * u + 2][hi + 1]);
                v.w = pack_bf16(o[mt][4 * u + 3][hi], o[mt][4 * u + 3][hi + 1]);
                dst[(t + 4 * u) ^ (cta & 7)] = v;
            }
        }
        asm volatile("bar.arrive 3, 288;" ::: "memory");
    }

    k_item(IT_K1 + w, sc_w + 256);
    __syncwarp();
    {
        const float4 s = ldsf4(sc_w + lane * 16);
        float m = fmaxf(fmaxf(s.x, s.y), fmaxf(s.z, s.w));
#pragma unroll
        for (int d = 1; d < 32; d <<= 1) m = fmaxf(m, __shfl_xor_sync(0xffffffffu, m, d));
        if (lane == 0) stsf(sb + SM_ML + w * 4, m);
        bar_consumers();
        const float4 m0 = ldsf4(sb + SM_ML), m1 = ldsf4(sb + SM_ML + 16);
        m = fmaxf(fmaxf(fmaxf(m0.x, m0.y), fmaxf(m0.z, m0.w)), fmaxf(fmaxf(m1.x, m1.y), fmaxf(m1.z, m1.w))) * SC;
        const uint32_t p0 = pack_bf16(ex2(fmaf(s.x, SC, -m)), ex2(fmaf(s.y, SC, -m)));
        const uint32_t p1 = pack_bf16(ex2(fmaf(s.z, SC, -m)), ex2(fmaf(s.w, SC, -m)));
        float l = (bf_lo(p0) + bf_hi(p0)) + (bf_lo(p1) + bf_hi(p1));
#pragma unroll
        for (int d = 1; d < 32; d <<= 1) l += __shfl_xor_sync(0xffffffffu, l, d);
        if (lane == 0) stsf(sb + SM_ML + 32 + w * 4, l);
        sts64(sb + SM_PA + w * 256 + lane * 8, p0, p1);
        __syncwarp();
    }

    float oa[4][4];
#pragma unroll
    for (int i = 0; i < 16; i++) (&oa[0][0])[i] = 0.f;
    auto v_item = [&](int item, uint32_t pa) {
        uint32_t p[8];
#pragma unroll
        for (int i = 0; i < 8; i++) p[i] = lds32(pa + i * 16 + t * 4);
        mbar_wait(sb + SM_FULL + item * 8);
        const uint32_t base = sb + slot_off(item) + ((lane & 7) + ((lane >> 4) << 3)) * 256 + ((lane & 8) << 4);
#pragma unroll
        for (int c = 0; c < 8; c++) {
            const uint32_t a = base + ((c ^ (lane & 7)) << 4);
            const uint32_t mask = ((c == (g ^ (2 * t))) ? 0x0000ffffu : 0u) | ((c == (g ^ (2 * t + 1))) ? 0xffff0000u : 0u);
#pragma unroll
            for (int T = 0; T < 4; T++) {
                uint32_t r0, r1, r2, r3;
                ldsm4t(a + T * 4096, r0, r1, r2, r3);
                mma16816(oa[T], r0, r1, r2, r3, p[2 * T] & mask, p[2 * T + 1] & mask);
            }
        }
        __syncwarp();
        if (lane == 0) mbar_arrive8(sb + SM_EMPTY + item * 8);
    };
    sts64(sb + SM_FIN + tid * 8, EMPTY, EMPTY);
    if (w == 0) sts32(sb + SM_CNT + lane * 4, 0u);
    v_item(IT_V0 + w, sb + SM_PA + w * 256);

    mbar_wait(sb + SM_FULL + IT_OP * 8);
    if (w < 4) {
        const float2 st = ldsf2(sb + SM_MX + tid * 8);
        float m = st.x;
#pragma unroll
        for (int d = 1; d < 32; d <<= 1) m = fmaxf(m, __shfl_xor_sync(0xffffffffu, m, d));
        const uint32_t wb = pack_bf16(ex2(st.x - m), 0.f);
        float l = bf_lo(wb) * st.y;
#pragma unroll
        for (int d = 1; d < 32; d <<= 1) l += __shfl_xor_sync(0xffffffffu, l, d);
#pragma unroll
        for (int bb = 0; bb < 4; bb++) sts16(in0 + bb * 272 + tid * 2, bb == w ? (uint16_t)wb : (uint16_t)0);
        if (lane == 0) stsf(sb + SM_ML + 64 + w * 4, 1.f / l);
    }
    bar_consumers();
    tile_mma<true>(sb, IT_OP, in0, w, lane, acc);
    if (lane < 16) {
        const float inv = ldsf(sb + SM_ML + 64 + g * 4);
        const uint32_t v0 = pack_bf16(acc[0][0] * inv, acc[0][1] * inv), v1 = pack_bf16(acc[1][0] * inv, acc[1][1] * inv);
        st_rlx2(lat_dst, (t & 1) ? v1 : v0, (t & 1) ? v0 : v1);
    }

    {
        const float4 l0 = ldsf4(sb + SM_ML + 32), l1 = ldsf4(sb + SM_ML + 48);
        const float inv = 1.f / (((l0.x + l0.y) + (l0.z + l0.w)) + ((l1.x + l1.y) + (l1.z + l1.w)));
        v_item(IT_V1 + w, sb + SM_PA + w * 256 + 128);
        const uint32_t so = sb + SM_PF + w * 512 + (16 * t + g) * 4;
        stsf(so,       (oa[0][0] + oa[1][0]) + (oa[2][0] + oa[3][0]));
        stsf(so + 32,  (oa[0][1] + oa[1][1]) + (oa[2][1] + oa[3][1]));
        stsf(so + 256, (oa[0][2] + oa[1][2]) + (oa[2][2] + oa[3][2]));
        stsf(so + 288, (oa[0][3] + oa[1][3]) + (oa[2][3] + oa[3][3]));
        if (w < 6) {
            asm volatile("bar.arrive 1, 256;" ::: "memory");
        } else {
            bar_consumers();
            float x = 0.f, y = 0.f;
#pragma unroll
            for (int i = 0; i < 8; i++) {
                const float2 v = ldsf2(sb + SM_PF + i * 512 + (tid & 63) * 8);
                x += v.x; y += v.y;
            }
            st_rlx(o_dst, pack_bf16(x * inv, y * inv));
        }
    }

    if (w < 4) {
        const uint32_t lo = (g & 3) * 1024 + (g >> 2) * 512 + (g & 1) * 64 + t * 16;
        const int wd = ((lane >> 2 & 2) + (lane >> 4)) ^ (lane >> 1 & 3);
        const uint32_t base = sb + ((lane & 6) * 4 + wd * 2 + (lane & 1)) * 64 + (((w ^ wd) & 3) << 4);
        const uint64_t dst = __shfl_sync(0xffffffffu, (unsigned long long)ctx_dst, lane);
        mbar_wait(sb + SM_FULL + BAR_LAT * 8);
        uint4 a[8];
#pragma unroll
        for (int i = 0; i < 8; i++) a[i] = lds128(sb + SM_LAT + (lo ^ (i * 64)));
        int it = 0;
        while (refetch(a, [&](int i) { return (const char*)gs->lat[h] + (lo ^ (i * 64)); }))
            if (++it > SPIN_LIMIT) __trap();
        float v0 = 0.f, v1 = 0.f;
#pragma unroll
        for (int i = 0; i < 2; i++) {
            float c[4][4];
#pragma unroll
            for (int k = 0; k < 16; k++) (&c[0][0])[k] = 0.f;
            c[0][0] = v0; c[0][1] = v1;
            mbar_wait(sb + SM_FULL + (IT_WUV + i) * 8);
#pragma unroll
            for (int kk = 0; kk < 8; kk++) {
                uint32_t r0, r1, r2, r3;
                ldsm4t(base + slot_off(IT_WUV + i) + kk * 2048, r0, r1, r2, r3);
                mma16816(c[2 * (kk & 1)],     a[kk].x, a[kk].y, a[kk].z, a[kk].w, r0, r1);
                mma16816(c[2 * (kk & 1) + 1], a[kk].x, a[kk].y, a[kk].z, a[kk].w, r2, r3);
            }
            v0 = (c[0][0] + c[1][2]) + (c[2][0] + c[3][2]);
            v1 = (c[0][1] + c[1][3]) + (c[2][1] + c[3][3]);
            if (i == 0) { v0 = __shfl_xor_sync(0xffffffffu, v0, 16); v1 = __shfl_xor_sync(0xffffffffu, v1, 16); }
        }
        st_rlx_if(dst, pack_bf16(v0, v1), lane >= 16);
    }

    {
        const bool isB = slice >= 32;
        const int r = j & 1;
        const uint32_t cs = isB ? 256 : 64;
        const uint32_t xl = (isB ? t * 64 + (((g >> 1) ^ (t & 2)) << 4) : (g >> 1) * 256 + ((g & 2) * 2 + t) * 16) + (w >> 1) * 1024 + (w & 1) * 2 * cs;
        auto xoff = [&](int i) { return (i >> 1) * 4096 + (xl ^ ((i & 1) * cs)); };
        const char* src = (const char*)gs->x[slice >> 5][r * 16];
        uint32_t off[2];
#pragma unroll
        for (int u = 0; u < 2; u++) {
            const int tt = (lane & 7) >> 1, row = 8 * tt + 2 * ((2 * u + (lane >> 4) + tt) & 3) + (lane & 1);
            off[u] = sb + w * 2048 + row * 32 + ((((lane >> 3) ^ (row >> 2)) & 1) << 4);
        }
        uint32_t fin[2], rcv[2];
#pragma unroll
        for (int e = 0; e < 2; e++) {
            const uint32_t o = t * 16 + (e ^ (t >> 1)) * 8 + g;
            fin[e] = __shfl_sync(0xffffffffu, sb + SM_FIN + (w >> 1) * 512 + o * 8 + ((w ^ t) & 1) * 4, lane);
            rcv[e] = __shfl_sync(0xffffffffu, sb + SM_RCV + o * 4, lane);
        }
        const uint32_t cnt = __shfl_sync(0xffffffffu, sb + SM_CNT + lane * 4, lane), sum = __shfl_sync(0xffffffffu, sb + SM_FIN + lane * 16, lane);
        const uint32_t inc = __shfl_sync(0xffffffffu, lane, 1 + r), last = __shfl_sync(0xffffffffu, lane, 7 + 7 * r);
        const uint32_t snd = __shfl_sync(0xffffffffu, map_cta(sb + SM_RCV + lane * 8, 0), lane),
                       sbar = __shfl_sync(0xffffffffu, map_cta(sb + SM_LAST + 8 + (lane & 16), 0), lane & 15);
        const uint64_t dst = __shfl_sync(0xffffffffu, (unsigned long long)(out + (lane >> 3) * 1024 + slice * 16 + ((lane ^ (lane >> 2 & 4)) & 7) * 2), lane);
        uint32_t a[2][4][4];
        uint4 x[8];
        float c[4][4];
        auto load_w = [&](int i) {
            mbar_wait(i < 2 ? sb + SM_FULL + (IT_WO + i) * 8 : sb + SM_LAST + w * 16 + (i & 1) * 8);
#pragma unroll
            for (int q = 0; q < 4; q++)
                ldsm4t(slot_off(IT_WO + i) + off[q & 1] + (q >> 1) * 1024, a[i & 1][q][0], a[i & 1][q][1], a[i & 1][q][2], a[i & 1][q][3]);
        };
        auto mma_w = [&](int i) {
#pragma unroll
            for (int q = 0; q < 4; q++) {
                const uint4& b = x[2 * i + (q >> 1)];
                if (i == 0) c[q][0] = c[q][1] = c[q][2] = c[q][3] = 0.f;
                mma16816(c[q], a[i & 1][q][0], a[i & 1][q][1], a[i & 1][q][2], a[i & 1][q][3], (q & 1) ? b.z : b.x, (q & 1) ? b.w : b.y);
            }
        };
        load_w(0); load_w(1);
        mbar_wait(sb + SM_FULL + IT_X * 8);
#pragma unroll
        for (int i = 0; i < 8; i++) x[i] = lds128(sb + slot_off(IT_X) + xoff(i));
        int it = 0;
        while (true) {
            mma_w(0); mma_w(1);
            if (!refetch(x, [&](int i) { return src + xoff(i); })) break;
            if (++it > SPIN_LIMIT) __trap();
        }
        load_w(2);
        mma_w(2);
        load_w(3);
        uint32_t rank;
        const float pr[2] = {ldsf_if(rcv[0], w == 0 && r == 0), ldsf_if(rcv[1], w == 0 && r == 0)};
        mma_w(3);
#pragma unroll
        for (int e = 0; e < 2; e++) stv(fin[e], (((c[0][2 * e] + pr[e]) + c[1][2 * e]) + c[2][2 * e]) + c[3][2 * e]);
        float4 p[4];
        float s0, s1;
        auto add_up = [&]() {
#pragma unroll
            for (int k = 0; k < 4; k++) p[k] = ldv4(sum + k * 512);
            const float a0 = ((p[0].x + p[0].y) + (p[1].x + p[1].y)) + (p[2].x + p[2].y), b0 = p[3].x + p[3].y;
            const float a1 = ((p[0].z + p[0].w) + (p[1].z + p[1].w)) + (p[2].z + p[2].w), b1 = p[3].z + p[3].w;
            s0 = a0 + b0; s1 = a1 + b1;
            uint32_t nan;
            asm("{\n.reg .pred p;\nsetp.ne.u32 p, %5, 0;\nsetp.nan.or.f32 p, %1, %2, p;\nsetp.nan.or.f32 p, %3, %4, p;\nselp.u32 %0, 1, 0, p;\n}"
                : "=r"(nan) : "f"(a0), "f"(a1), "f"(b0), "f"(b1), "r"(r));
            return nan;
        };
        asm volatile("atom.relaxed.cta.shared.add.u32 %0, [%1], %2;" : "=r"(rank) : "r"(cnt), "r"(inc) : "memory");
        const uint32_t redo = add_up();
        st_if(dst, pack_bf16(s0, s1), rank == 7);
        if (!redo) return;
        const bool num = s0 == s0 && s1 == s1;
        st_async64_if(snd, s0, s1, sbar, rank == 14 && num);
        if (rank != last || num) return;
        auto mx = [](float4 q) { return max(max(__float_as_uint(q.x), __float_as_uint(q.y)), max(__float_as_uint(q.z), __float_as_uint(q.w))); };
        for (it = 0; max(max(mx(p[0]), mx(p[1])), max(mx(p[2]), mx(p[3]))) == EMPTY; it++) {
            add_up();
            if (it > SPIN_LIMIT) __trap();
        }
        if (r) st_async64_if(snd, s0, s1, sbar, true);
        else st_if(dst, pack_bf16(s0, s1), true);
    }
}

typedef CUresult (*EncodeTiledFn)(CUtensorMap*, CUtensorMapDataType, cuuint32_t, void*, const cuuint64_t*,
                                  const cuuint64_t*, const cuuint32_t*, const cuuint32_t*, CUtensorMapInterleave,
                                  CUtensorMapSwizzle, CUtensorMapL2promotion, CUtensorMapFloatOOBfill);

void encode_map(EncodeTiledFn enc, CUtensorMap* tm, const void* p, cuuint64_t cols, cuuint64_t rows,
                cuuint32_t brows, cuuint32_t bblk) {
    cuuint64_t dims[3] = {64, rows, cols / 64};
    cuuint64_t strides[2] = {cols * 2, 128};
    cuuint32_t box[3] = {64, brows, bblk};
    cuuint32_t es[3] = {1, 1, 1};
    enc(tm, CU_TENSOR_MAP_DATA_TYPE_BFLOAT16, 3, const_cast<void*>(p), dims, strides, box, es,
        CU_TENSOR_MAP_INTERLEAVE_NONE, CU_TENSOR_MAP_SWIZZLE_128B, CU_TENSOR_MAP_L2_PROMOTION_L2_256B,
        CU_TENSOR_MAP_FLOAT_OOB_FILL_NONE);
}

void encode_slice_map(EncodeTiledFn enc, CUtensorMap* tm, const void* p, cuuint64_t cols, cuuint64_t rows,
                      cuuint32_t bcols, cuuint32_t brows) {
    cuuint64_t dims[3] = {cols, 256, rows / 256};
    cuuint64_t strides[2] = {cols * 2, cols * 512};
    cuuint32_t box[3] = {bcols, brows, 1};
    cuuint32_t es[3] = {1, 1, 1};
    enc(tm, CU_TENSOR_MAP_DATA_TYPE_BFLOAT16, 3, const_cast<void*>(p), dims, strides, box, es, CU_TENSOR_MAP_INTERLEAVE_NONE,
        bcols == 16 ? CU_TENSOR_MAP_SWIZZLE_32B : CU_TENSOR_MAP_SWIZZLE_64B, CU_TENSOR_MAP_L2_PROMOTION_L2_128B,
        CU_TENSOR_MAP_FLOAT_OOB_FILL_NONE);
}

}

extern "C" void kernel_launch(void* const* d_in, const int* in_sizes, int n_in, void* d_out, int out_size) {
    (void)in_sizes; (void)n_in; (void)out_size;
    static EncodeTiledFn enc = nullptr;
    static Scratch* gs = nullptr;
    if (!enc) {
        cudaGetSymbolAddress((void**)&gs, g_scratch);
        void* fn = nullptr;
        cudaDriverEntryPointQueryResult qr;
        cudaGetDriverEntryPoint("cuTensorMapEncodeTiled", &fn, cudaEnableDefault, &qr);
        enc = (EncodeTiledFn)fn;
        cudaFuncSetAttribute(fused_decode_kernel, cudaFuncAttributeMaxDynamicSharedMemorySize, SM_END);
    }
    Maps maps;
    encode_map(enc, &maps.wuk, d_in[8], 4096, 512, 32, 2);
    encode_slice_map(enc, &maps.wuv, d_in[9], 4096, 512, 32, 128);
    encode_slice_map(enc, &maps.woB, d_in[10], 512, 4096, 16, 256);
    encode_slice_map(enc, &maps.woA, d_in[4], 512, 4096, 16, 256);
    encode_slice_map(enc, &maps.endB, d_in[10], 512, 4096, 16, 64);
    encode_slice_map(enc, &maps.endA, d_in[4], 512, 4096, 16, 64);
    encode_map(enc, &maps.ckv, d_in[6], 512, 16384, 8, 8);
    uint64_t first = (uint64_t)d_in[7];
    if ((uint32_t)first >= 0xffe00000u) first += 1 << 21;
    fused_decode_kernel<<<NCTA, NTHR, SM_END>>>(make_uint2((uint32_t)first, (uint32_t)(first >> 32)),
                                                (const __nv_bfloat16*)d_in[0], (const __nv_bfloat16*)d_in[5],
                                                (const __nv_bfloat16*)d_in[7], (const __nv_bfloat16*)d_in[3],
                                                (const __nv_bfloat16*)d_in[1] + 3072 * 128, (const __nv_bfloat16*)d_in[2] + 3072 * 128,
                                                (__nv_bfloat16*)d_out, gs, maps);
}
```

```cpp
#include <cuda_runtime.h>
#include <cuda_bf16.h>
#include <cuda.h>
#include <stdint.h>

namespace {

constexpr int NCTA   = 128;
constexpr int NSLOT  = 13;
constexpr int SLOT   = 16384;
constexpr int NITEM  = 56;
constexpr int NTHR   = 384;

constexpr int INFLIGHT = 4;
constexpr int PACE     = 644;
constexpr int LEAD     = 530;
constexpr int TAPER    = 260;
constexpr int OS0      = -60;
constexpr int OS1      = 241;
constexpr int OF0      = -200;
constexpr int OF1      = 480;
constexpr int OF2      = 1690;
constexpr int OF3      = 160;
constexpr int XS       = 1340;
constexpr int XF       = 1640;
constexpr int OB       = 50;
constexpr int XB       = 90;
constexpr uint32_t ROWS_EVEN = 0xfedc9630u, ROWS_ODD = 0xba875421u;
constexpr uint64_t PIECE_OF  = 0x7654fe3dc2ba1980ull;
constexpr int OPGAP    = 250;
constexpr int NWIN     = 4;
__device__ constexpr int win_pos(int k)  { return k == 0 ? 10 : k == 1 ? 20 : k == 2 ? 31 : 38; }
__device__ constexpr int win_late(int k) { return k == 0 ? 1810 : k == 1 ? 1845 : k == 2 ? 1845 : 1735; }
constexpr int GAIN     = 11;

constexpr int IT_WQB = 0, IT_WQA = 2, IT_WUK = 4, IT_K0 = 6, IT_Q = 14, IT_C = 16, IT_K1 = 24, IT_V0 = 32,
              IT_OP = 40, IT_V1 = 42, IT_WUV = 50, IT_WO = 52;
constexpr int IT_X = 56;
constexpr int BAR_LAT = 55;

constexpr int SM_FULL  = NSLOT * SLOT;
constexpr int SM_EMPTY = SM_FULL + 512;
constexpr int SM_IN0   = SM_EMPTY + 512;
constexpr int SM_IN1   = SM_IN0 + 1088;
constexpr int SM_SC    = SM_IN1 + 1088;
constexpr int SM_PA    = SM_SC + 4096;
constexpr int SM_PF    = SM_PA + 2048;
constexpr int SM_MX    = SM_PF + 8192;
constexpr int SM_ML    = SM_MX + 1024;
constexpr int SM_LAST  = SM_ML + 128;
constexpr int SM_CNT   = SM_LAST + 128;
constexpr int SM_RCV   = SM_CNT + 128;
constexpr int SM_PACE  = SM_RCV + 256;
constexpr int SM_END   = SM_PACE + 32;
constexpr int SM_LAT   = SM_PF + 4096;
constexpr int SM_FIN   = SM_SC;
constexpr int SM_SUM   = SM_IN0;
static_assert(SM_END <= 232448, "smem");

struct Maps { CUtensorMap wuk, wuv, woA, woB, ckv, endA, endB; };

struct Scratch {
    uint64_t late[16];
    unsigned cnt[NCTA][32];
    float    part[2][NCTA][512];
    uint32_t x[2][32][256];
    uint32_t lat[32][4][256];
    uint4    q[4][2048];
    uint4    op[NCTA][2048];
    float2   stat[32][128];
};
__device__ __align__(128) Scratch g_scratch;

constexpr int SPIN_LIMIT = 1 << 22;

__device__ __forceinline__ uint32_t smem_u32(const void* p) { return (uint32_t)__cvta_generic_to_shared(p); }
__device__ __forceinline__ void mbar_init(uint32_t bar, uint32_t cnt) {
    asm volatile("mbarrier.init.shared::cta.b64 [%0], %1;" ::"r"(bar), "r"(cnt) : "memory");
}
__device__ __forceinline__ void mbar_expect_tx(uint32_t bar, uint32_t bytes) {
    asm volatile("mbarrier.arrive.expect_tx.shared::cta.b64 _, [%0], %1;" ::"r"(bar), "r"(bytes) : "memory");
}
__device__ __forceinline__ void mbar_arrive(uint32_t bar) {
    asm volatile("mbarrier.arrive.shared::cta.b64 _, [%0];" ::"r"(bar) : "memory");
}
__device__ __forceinline__ void mbar_arrive8(uint32_t bar) {
    asm volatile("mbarrier.arrive.shared::cta.b64 _, [%0], 8;" ::"r"(bar) : "memory");
}
__device__ __forceinline__ void mbar_wait(uint32_t bar) {
    uint32_t done;
    int it = 0;
    do {
        asm volatile("{\n.reg .pred p;\nmbarrier.try_wait.parity.shared::cta.b64 p, [%1], 0;\nselp.u32 %0, 1, 0, p;\n}"
                     : "=r"(done) : "r"(bar) : "memory");
        if (++it > SPIN_LIMIT) __trap();
    } while (!done);
}
__device__ __forceinline__ uint32_t map_cta(uint32_t a, uint32_t rank) {
    uint32_t r; asm("mapa.shared::cluster.u32 %0, %1, %2;" : "=r"(r) : "r"(a), "r"(rank)); return r;
}
__device__ __forceinline__ void st_async64_if(uint32_t a, float x, float y, uint32_t bar, bool on) {
    asm volatile("{\n.reg .pred p;\nsetp.ne.u32 p, %4, 0;\n@p st.async.shared::cluster.mbarrier::complete_tx::bytes.v2.f32 [%0], {%1,%2}, [%3];\n}"
                 ::"r"(a), "f"(x), "f"(y), "r"(bar), "r"((uint32_t)on) : "memory");
}
__device__ __forceinline__ uint64_t evict_first() {
    uint64_t pol; asm volatile("createpolicy.fractional.L2::evict_first.b64 %0, 1.0;" : "=l"(pol)); return pol;
}
#define ELECT "{\n.reg .pred p;\nelect.sync _|p, 0xffffffff;\n@p "
__device__ __forceinline__ void bulk_load(uint32_t dst, const void* src, uint32_t bytes, uint32_t bar, uint64_t pol) {
    asm volatile(ELECT "cp.async.bulk.shared::cluster.global.mbarrier::complete_tx::bytes.L2::cache_hint [%0], [%1], %2, [%3], %4;\n}"
                 ::"r"(dst), "l"(src), "r"(bytes), "r"(bar), "l"(pol) : "memory");
}
__device__ __forceinline__ void bulk_load_nohint(uint32_t dst, const void* src, uint32_t bytes, uint32_t bar) {
    asm volatile("cp.async.bulk.shared::cluster.global.mbarrier::complete_tx::bytes [%0], [%1], %2, [%3];"
                 ::"r"(dst), "l"(src), "r"(bytes), "r"(bar) : "memory");
}
__device__ __forceinline__ void tma3d(uint32_t dst, const CUtensorMap* tm, int c0, int c1, int c2, uint32_t bar, uint64_t pol) {
    asm volatile(ELECT "cp.async.bulk.tensor.3d.shared::cluster.global.mbarrier::complete_tx::bytes.L2::cache_hint [%0], [%1, {%3, %4, %5}], [%2], %6;\n}"
                 ::"r"(dst), "l"(tm), "r"(bar), "r"(c0), "r"(c1), "r"(c2), "l"(pol) : "memory");
}
__device__ __forceinline__ void ldsm4(uint32_t a, uint32_t& r0, uint32_t& r1, uint32_t& r2, uint32_t& r3) {
    asm volatile("ldmatrix.sync.aligned.m8n8.x4.shared.b16 {%0,%1,%2,%3}, [%4];"
                 : "=r"(r0), "=r"(r1), "=r"(r2), "=r"(r3) : "r"(a) : "memory");
}
__device__ __forceinline__ void ldsm4t(uint32_t a, uint32_t& r0, uint32_t& r1, uint32_t& r2, uint32_t& r3) {
    asm volatile("ldmatrix.sync.aligned.m8n8.x4.trans.shared.b16 {%0,%1,%2,%3}, [%4];"
                 : "=r"(r0), "=r"(r1), "=r"(r2), "=r"(r3) : "r"(a) : "memory");
}
__device__ __forceinline__ void mma16816(float (&c)[4], uint32_t a0, uint32_t a1, uint32_t a2, uint32_t a3,
                                         uint32_t b0, uint32_t b1) {
    asm volatile("mma.sync.aligned.m16n8k16.row.col.f32.bf16.bf16.f32 {%0,%1,%2,%3}, {%4,%5,%6,%7}, {%8,%9}, {%0,%1,%2,%3};"
                 : "+f"(c[0]), "+f"(c[1]), "+f"(c[2]), "+f"(c[3])
                 : "r"(a0), "r"(a1), "r"(a2), "r"(a3), "r"(b0), "r"(b1));
}
__device__ __forceinline__ uint32_t lds32(uint32_t a) {
    uint32_t v; asm volatile("ld.shared.b32 %0, [%1];" : "=r"(v) : "r"(a) : "memory"); return v;
}
__device__ __forceinline__ float ldsf(uint32_t a) {
    float v; asm volatile("ld.shared.f32 %0, [%1];" : "=f"(v) : "r"(a) : "memory"); return v;
}
__device__ __forceinline__ float2 ldsf2(uint32_t a) {
    float2 v; asm volatile("ld.shared.v2.f32 {%0,%1}, [%2];" : "=f"(v.x), "=f"(v.y) : "r"(a) : "memory"); return v;
}
__device__ __forceinline__ float4 ldsf4(uint32_t a) {
    float4 v; asm volatile("ld.shared.v4.f32 {%0,%1,%2,%3}, [%4];" : "=f"(v.x), "=f"(v.y), "=f"(v.z), "=f"(v.w) : "r"(a) : "memory"); return v;
}
__device__ __forceinline__ uint4 lds128(uint32_t a) {
    uint4 v; asm volatile("ld.shared.v4.b32 {%0,%1,%2,%3}, [%4];" : "=r"(v.x), "=r"(v.y), "=r"(v.z), "=r"(v.w) : "r"(a) : "memory"); return v;
}
__device__ __forceinline__ float ldsf_if(uint32_t a, bool on) {
    float v = 0.f;
    asm volatile("{\n.reg .pred p;\nsetp.ne.u32 p, %2, 0;\n@p ld.shared.f32 %0, [%1];\n}" : "+f"(v) : "r"(a), "r"((uint32_t)on) : "memory");
    return v;
}
__device__ __forceinline__ float4 ldv4(uint32_t a) {
    float4 v; asm volatile("ld.volatile.shared.v4.f32 {%0,%1,%2,%3}, [%4];" : "=f"(v.x), "=f"(v.y), "=f"(v.z), "=f"(v.w) : "r"(a) : "memory"); return v;
}
__device__ __forceinline__ void stv(uint32_t a, float v) { asm volatile("st.volatile.shared.f32 [%0], %1;" ::"r"(a), "f"(v) : "memory"); }
__device__ __forceinline__ void sts16(uint32_t a, uint16_t v) { asm volatile("st.shared.b16 [%0], %1;" ::"r"(a), "h"(v) : "memory"); }
__device__ __forceinline__ void sts32(uint32_t a, uint32_t v) { asm volatile("st.shared.b32 [%0], %1;" ::"r"(a), "r"(v) : "memory"); }
__device__ __forceinline__ void stsf(uint32_t a, float v) { asm volatile("st.shared.f32 [%0], %1;" ::"r"(a), "f"(v) : "memory"); }
__device__ __forceinline__ void sts64(uint32_t a, uint32_t x, uint32_t y) {
    asm volatile("st.shared.v2.b32 [%0], {%1,%2};" ::"r"(a), "r"(x), "r"(y) : "memory");
}
__device__ __forceinline__ void sts128(uint32_t a, uint4 v) {
    asm volatile("st.shared.v4.b32 [%0], {%1,%2,%3,%4};" ::"r"(a), "r"(v.x), "r"(v.y), "r"(v.z), "r"(v.w) : "memory");
}
__device__ __forceinline__ uint32_t pack_bf16(float lo, float hi) {
    uint32_t r; asm("cvt.rn.bf16x2.f32 %0, %1, %2;" : "=r"(r) : "f"(hi), "f"(lo)); return r;
}
__device__ __forceinline__ float bf_lo(uint32_t v) { return __uint_as_float(v << 16); }
__device__ __forceinline__ float bf_hi(uint32_t v) { return __uint_as_float(v & 0xffff0000u); }
__device__ __forceinline__ float ex2(float x) { float y; asm("ex2.approx.ftz.f32 %0, %1;" : "=f"(y) : "f"(x)); return y; }
__device__ __forceinline__ uint32_t timer_ns() { uint32_t t; asm volatile("mov.u32 %0, %%globaltimer_lo;" : "=r"(t)); return t; }
__device__ __forceinline__ void bar_consumers() { asm volatile("bar.sync 1, 256;" ::: "memory"); }

__device__ __forceinline__ uint32_t tagf(float v, uint32_t tag) { return (__float_as_uint(v) & 0xffffff00u) | tag; }
__device__ __forceinline__ uint2 ld_rlx2(const void* p) {
    uint64_t v; asm volatile("ld.relaxed.gpu.global.b64 %0, [%1];" : "=l"(v) : "l"(p) : "memory");
    return make_uint2((uint32_t)v, (uint32_t)(v >> 32));
}
__device__ __forceinline__ float untag(uint32_t v) { return __uint_as_float(v & 0xffffff00u); }

__device__ __forceinline__ uint32_t slot_off(int item) { return (uint32_t)(item % NSLOT) * SLOT; }

template <bool TRANS, bool TMA = true>
__device__ __forceinline__ void tile_mma(uint32_t sb, int item, uint32_t in, int w, int lane, float (&acc)[2][2]) {
    const int g = lane >> 2, t = lane & 3;
    float c[4][4];
#pragma unroll
    for (int i = 0; i < 16; i++) (&c[0][0])[i] = 0.f;
    uint32_t a[16];
    const uint32_t ia = in + (g & 3) * 272 + t * 4;
#pragma unroll
    for (int i = 0; i < 16; i++) a[i] = lds32(ia + i * 16);
    const uint32_t s0 = sb + slot_off(item), s1 = sb + slot_off(item + 1);
    if (TRANS) {
        const int r = (lane & 7) + (lane & 8);
        const int ch = 2 * (w & 3) + (lane >> 4);
        const uint32_t off = (TMA ? (w >> 2) * 8192 + r * 128 : (w >> 2) * 128 + r * 256) + ((ch ^ (lane & 7)) << 4);
#pragma unroll
        for (int kk = 0; kk < 8; kk++) {
            if (TMA && (kk & 3) == 0) mbar_wait(sb + SM_FULL + (item + (kk >> 2)) * 8);
            uint32_t r0, r1, r2, r3;
            ldsm4t(((kk >> 2) ? s1 : s0) + off + (kk & 3) * (TMA ? 2048 : 4096), r0, r1, r2, r3);
            mma16816(c[2 * (kk & 1)],     a[2 * kk], 0u, a[2 * kk + 1], 0u, r0, r1);
            mma16816(c[2 * (kk & 1) + 1], a[2 * kk], 0u, a[2 * kk + 1], 0u, r2, r3);
        }
    } else {
        mbar_wait(sb + SM_FULL + (item + (w >> 2)) * 8);
        const int r = 16 * (w & 3) + (lane & 7) + ((lane >> 4) << 3);
        const uint32_t base = ((w >> 2) ? s1 : s0) + (r & 32) * 128 + r * 128 + ((((lane >> 3) & 1) ^ (lane & 7)) << 4);
#pragma unroll
        for (int kk = 0; kk < 8; kk++) {
            uint32_t r0, r1, r2, r3;
            ldsm4((base ^ ((kk & 3) << 5)) + (kk >> 2) * 4096, r0, r1, r2, r3);
            mma16816(c[2 * (kk & 1)],     a[2 * kk], 0u, a[2 * kk + 1], 0u, r0, r1);
            mma16816(c[2 * (kk & 1) + 1], a[2 * kk], 0u, a[2 * kk + 1], 0u, r2, r3);
        }
    }
    __syncwarp();
    if (lane == 0) {
        mbar_arrive(sb + SM_EMPTY + item * 8);
        mbar_arrive(sb + SM_EMPTY + (item + 1) * 8);
    }
    acc[0][0] = c[0][0] + c[2][0]; acc[0][1] = c[0][1] + c[2][1];
    acc[1][0] = c[1][0] + c[3][0]; acc[1][1] = c[1][1] + c[3][1];
}

__device__ __forceinline__ void publish(float* dst, int w, int lane, const float (&acc)[2][2], uint32_t tag) {
    if (lane < 16)
        asm volatile("st.relaxed.gpu.global.v4.b32 [%0], {%1,%2,%3,%4};" ::"l"(dst + w * 64 + lane * 4),
                     "r"(tagf(acc[0][0], tag)), "r"(tagf(acc[0][1], tag)), "r"(tagf(acc[1][0], tag)), "r"(tagf(acc[1][1], tag)) : "memory");
}

__device__ __forceinline__ void gather(const float* part, uint32_t in, int tid, uint32_t tag) {
    const float* p = part + tid * 2;
    uint2 v0, v1, v2, v3;
    int it = 0;
    while (true) {
        v0 = ld_rlx2(p); v1 = ld_rlx2(p + 512); v2 = ld_rlx2(p + 1024); v3 = ld_rlx2(p + 1536);
        uint32_t bad = ((v0.x ^ tag) | (v0.y ^ tag) | (v1.x ^ tag) | (v1.y ^ tag) |
                        (v2.x ^ tag) | (v2.y ^ tag) | (v3.x ^ tag) | (v3.y ^ tag)) & 0xffu;
        if (__all_sync(0xffffffffu, bad == 0)) break;
        if (++it > SPIN_LIMIT) __trap();
    }
    float x = (untag(v0.x) + untag(v1.x)) + (untag(v2.x) + untag(v3.x));
    float y = (untag(v0.y) + untag(v1.y)) + (untag(v2.y) + untag(v3.y));
    sts32(in + ((tid >> 3) & 3) * 272 + (tid >> 5) * 32 + (tid & 1) * 16 + (tid & 6) * 2, pack_bf16(x, y));
    bar_consumers();
}

constexpr uint32_t EMPTY = 0xffffffffu;
__device__ __forceinline__ void st_rlx(uint32_t* p, uint32_t v) {
    asm volatile("st.relaxed.gpu.global.b32 [%0], %1;" ::"l"(p), "r"(v) : "memory");
}
__device__ __forceinline__ void st_rlx_if(uint64_t p, uint32_t v, bool on) {
    asm volatile("{\n.reg .pred p;\nsetp.ne.u32 p, %2, 0;\n@p st.relaxed.gpu.global.b32 [%0], %1;\n}" ::"l"(p), "r"(v), "r"((uint32_t)on) : "memory");
}
__device__ __forceinline__ void st_if(uint64_t p, uint32_t v, bool on) {
    asm volatile("{\n.reg .pred p;\nsetp.ne.u32 p, %2, 0;\n@p st.global.b32 [%0], %1;\n}" ::"l"(p), "r"(v), "r"((uint32_t)on) : "memory");
}
__device__ __forceinline__ void st_rlx2(uint32_t* p, uint32_t v0, uint32_t v1) {
    asm volatile("st.relaxed.gpu.global.v2.b32 [%0], {%1,%2};" ::"l"(p), "r"(v0), "r"(v1) : "memory");
}
__device__ __forceinline__ void ld_rlx4_if(uint4& v, const void* p, bool need) {
    asm volatile("{\n.reg .pred p;\nsetp.ne.u32 p, %5, 0;\n@p ld.relaxed.gpu.global.v4.b32 {%0,%1,%2,%3}, [%4];\n}"
                 : "+r"(v.x), "+r"(v.y), "+r"(v.z), "+r"(v.w) : "l"(p), "r"((uint32_t)need) : "memory");
}

template <class F>
__device__ __forceinline__ bool refetch(uint4 (&x)[8], F addr) {
    uint32_t m[8], m0 = 0;
#pragma unroll
    for (int i = 0; i < 8; i++) {
        m[i] = max(max(x[i].x, x[i].y), max(x[i].z, x[i].w));
        m0 = max(m0, m[i]);
    }
    if (!__any_sync(0xffffffffu, m0 == EMPTY)) return false;
#pragma unroll
    for (int i = 0; i < 8; i++) ld_rlx4_if(x[i], addr(i), m[i] == EMPTY);
    return true;
}

__device__ __forceinline__ unsigned read_counter(const unsigned* cnt) {
    unsigned v;
    asm volatile("ld.relaxed.gpu.global.u32 %0, [%1];" : "=r"(v) : "l"(cnt) : "memory");
    return v;
}
__device__ __forceinline__ unsigned epoch_of(unsigned cnt) {
    asm volatile("" : "+r"(cnt) :: "memory");
    return cnt + 1;
}
__device__ __forceinline__ uint32_t epoch_tag(unsigned epoch) { return (epoch & 0x7fu) | 0x80u; }

__device__ __forceinline__ void signal_and_wait(unsigned* cnt, unsigned target, int lane) {
    if (lane == 0) asm volatile("red.release.gpu.global.add.u32 [%0], 1;" ::"l"(cnt) : "memory");
    int it = 0;
    while (true) {
        unsigned v;
        asm volatile("ld.acquire.gpu.global.u32 %0, [%1];" : "=r"(v) : "l"(cnt) : "memory");
        if (__all_sync(0xffffffffu, (int)(v - target) >= 0)) break;
        if (++it > SPIN_LIMIT) __trap();
    }
    asm volatile("fence.proxy.async.global;" ::: "memory");
}

__global__ void __cluster_dims__(2, 1, 1) __launch_bounds__(NTHR, 1)
fused_decode_kernel(const uint2 first, const __nv_bfloat16* __restrict__ xA, const __nv_bfloat16* __restrict__ xB,
                    const __nv_bfloat16* __restrict__ wqB, const __nv_bfloat16* __restrict__ wqA,
                    const __nv_bfloat16* __restrict__ Kc, const __nv_bfloat16* __restrict__ Vc,
                    __nv_bfloat16* __restrict__ out, Scratch* gs, const __grid_constant__ Maps maps) {
    extern __shared__ __align__(1024) unsigned char smem_raw[];
    const uint32_t sb = smem_u32(smem_raw);
    const int tid = threadIdx.x, lane = tid & 31;
    const int cta = blockIdx.x, h = cta >> 2, j = cta & 3;
    const size_t kv_off = (size_t)blockIdx.x * 4096 * 128;
    asm volatile("{\n.reg .b32 l;\n.reg .b64 a;\nmad.lo.u32 l, %2, 32, %0;\nmov.b64 a, {l, %1};\nprefetch.global.L2 [a];\n}"
                 ::"r"(first.x + blockIdx.x * (NTHR * 32)), "r"(first.y), "r"(threadIdx.x) : "memory");
    const uint32_t trow = threadIdx.x >> 4;
    const uint32_t tile_src = trow * (8192 - 256) + (threadIdx.x * 16 + ((blockIdx.x * 0x100040u) & 0x301f00u));
    const uint32_t tile_dst = sb + ((threadIdx.x ^ (trow & 7)) << 4);
    auto lsu_piece = [&](int k) {
#pragma unroll
        for (int q = 2 * k; q < 2 * k + 2; q++)
            asm volatile("cp.async.cg.shared.global [%0], [%1], 16;" ::"r"(tile_dst + q * 4096),
                         "l"(reinterpret_cast<const char*>((k < 4 ? wqB : wqA) + (q & 7) * 16 * 4096) + tile_src) : "memory");
        if ((k & 3) == 3) asm volatile("cp.async.commit_group;" ::: "memory");
    };
    if (tid < 256) {
#pragma unroll
        for (int k = 0; k < 4; k++) lsu_piece(k);
    }
    const uint32_t tz = timer_ns() - LEAD;
    unsigned cnt1;
    if (tid < 256) cnt1 = read_counter(gs->cnt[blockIdx.x]);
    uint4 xv;
    if (tid < 128) {
        const __nv_bfloat16* x = (tid < 64 ? xB : xA) + ((tid >> 4) & 3) * 512 + j * 128 + (tid & 15) * 8;
        xv = __ldg(reinterpret_cast<const uint4*>(x));
    }
    const int w = __shfl_sync(0xffffffffu, tid >> 5, 0);
    const int pr = cta >> 1;
    const int slice = pr < 4 ? pr : pr < 36 ? 4 + ((pr - 4) & 7) * 4 + ((pr - 4) >> 3) : 36 + (pr - 36) % 7 * 4 + (pr - 36) / 7;

    if (w >= 8) {
        if (lane == 0) {
            const uint32_t full = sb + SM_FULL + (IT_WUK + (w & 3) * 14) * 8, empty = sb + SM_EMPTY + (w & 3) * 13 * 8,
                           last = sb + SM_LAST + (w & 3) * 32;
#pragma unroll
            for (int i = 0; i < 14; i++) mbar_init(full + i * 8, 1);
#pragma unroll
            for (int i = 0; i < 13; i++) mbar_init(empty + i * 8, 8);
#pragma unroll
            for (int i = 0; i < 4; i++) mbar_init(last + i * 8, 1);
#pragma unroll
            for (int i = 0; i < 14; i++) {
                const int b = IT_WUK + 42 + i;
                mbar_expect_tx(full + i * 8, (w == 10 && b - 14 == IT_OP) ? SLOT + 1024 : (w == 11 && b == BAR_LAT) ? 4096 : SLOT);
            }
#pragma unroll
            for (int i = 0; i < 4; i++) mbar_expect_tx(last + i * 8, i == 1 && w == 8 && !(j & 1) ? 2048 + 256 : 2048);
            asm volatile("fence.mbarrier_init.release.cluster;" ::: "memory");
            if (w == 10) sts64(sb + SM_PACE, tz, PACE * 16);
        }
        asm volatile("bar.sync 2, 128;" ::: "memory");
        asm volatile("bar.arrive 4, 384;" ::: "memory");
    }
    if (w == 10) {
        if (lane == 0) {
            int slope = 0;
#pragma unroll
            for (int k = 0; k < NWIN; k++) {
                const int c = win_pos(k);
                uint32_t acc = 0;
#pragma unroll
                for (int p = c; p < c + 4; p++) {
                    mbar_wait(sb + SM_FULL + (p < IT_Q ? p : p < IT_OP - 2 ? p + 2 : p + 4) * 8);
                    acc += timer_ns() - tz - p * PACE - ((p * slope) >> 4);
                }
                if (k == 0) mbar_wait(sb + SM_FULL + IT_Q * 8);
                asm volatile("red.relaxed.gpu.global.add.u64 [%0], %1;" ::"l"(&gs->late[k]),
                             "l"((uint64_t)tz << 32 | (1u << 24) + min(acc >> 2, 65535u)) : "memory");
                uint2 v;
                int it = 0;
                do { v = ld_rlx2(&gs->late[k]); } while ((v.x >> 24) != NCTA && ++it < 1000);
                if (it == 1000) break;
                const int late = (v.x & 0xffffffu) / NCTA;
                slope = max(-320, min(320, slope + (late - win_late(k)) * (GAIN * 2) / (2 * c + 3)));
                sts64(sb + SM_PACE, k < NWIN - 1 ? tz : tz + (int)(v.y - tz * NCTA) / NCTA, PACE * 16 + slope);
            }
        }
        return;
    }
    if (w >= 8) {
        auto wait_due = [&](uint32_t p, uint32_t shift) {
            uint32_t a, b;
            do {
                asm volatile("ld.volatile.shared.v2.b32 {%0,%1}, [%2];" : "=r"(a), "=r"(b) : "r"(sb + SM_PACE) : "memory");
            } while (__all_sync(0xffffffffu, (int)(timer_ns() - (a + ((p * b) >> 4) + shift)) < 0));
        };
        if (w != 9) {
            const int half = w & 1;
            const uint64_t pol = evict_first();
            const uint32_t rows = ((j & 1) ? ROWS_ODD : ROWS_EVEN) >> half * 4;
            int slot = IT_WUK, tail = IT_WUK - INFLIGHT;
            uint32_t np = IT_WUK, shift = half ? PACE / 4 : -(PACE / 4);
#pragma unroll 1
            for (int i = IT_WUK; i < NITEM; i++) {
                const uint32_t dst = sb + slot * SLOT + half * (SLOT / 2), bar = sb + SM_FULL + i * 8;
                if (++slot == NSLOT) slot = 0;
                if ((i & ~1) == IT_Q || (i & ~1) == IT_OP) continue;
                const bool ckv = i >= IT_C && i < IT_K1, wo = i >= IT_WO;
                const bool tiled = ckv || i < IT_K0 || i >= IT_WUV;
                const CUtensorMap* tm = &maps.wuk + (i < IT_K0 ? 0 : ckv ? 4 : wo ? 2 + (slice >> 5) : 1);
                const int c0 = wo ? (slice & 31) * 16 : i >= IT_WUV ? cta * 32 : 0;
                const int c1 = i < IT_K0 ? j * 128 + (i & 1) * 64 + half * 32 : ckv ? cta * 128 + (i - IT_C) * 16 + half * 8 : wo ? 0 : half * 128;
                const int c2 = i < IT_K0 ? h * 2 : ckv ? 0 : wo ? rows >> (i - IT_WO) * 8 & 15 : i & 1;
                const int c = i < IT_Q ? i - IT_K0 : i < IT_V0 ? i - IT_K1 + 8 : i < IT_OP ? i - IT_V0 : i - IT_V1 + 8;
                const __nv_bfloat16* src = (i < IT_V0 ? Kc : Vc) + kv_off + (size_t)((c ^ (j & 1) * 7) * 2 + half) * (SLOT / 4);
                if (i >= NSLOT) mbar_wait(sb + SM_EMPTY + (i - NSLOT) * 8);
                if (tail >= IT_WUK && !wo) mbar_wait(sb + SM_FULL + tail * 8);
                ++tail;
                if (tail == IT_Q || tail == IT_OP) tail += 2;
                if (wo) {
                    const int n = (i - IT_WO) * 2 + half;
                    np = IT_WO - 4;
                    shift = TAPER + ((j & 1) ? OS0 + n * OS1 : n < 4 ? OF0 + n * OF1 : OF2 + (n - 4) * OF3) + (slice < 32 ? -OB : OB);
                }
                wait_due(np, shift);
                ++np;
                if (i == IT_WUV - 1) shift += TAPER;
                if (i >= NITEM - 2) {
#pragma unroll
                    for (int q = 0; q < 4; q++)
                        tma3d(dst + q * 2048, tm + 3, c0, q * 64, c2, sb + SM_LAST + half * 64 + q * 16 + (i & 1) * 8, pol);
                }
                else if (tiled) tma3d(dst, tm, c0, c1, c2, bar, pol);
                else bulk_load(dst, src, SLOT / 2, bar, pol);
            }
        } else {
            if (lane < sizeof(Maps) / 128) asm volatile("prefetch.tensormap [%0];" ::"l"(&maps.wuk + lane) : "memory");
            cnt1 = read_counter(gs->cnt[blockIdx.x]);
            asm volatile("bar.sync 3, 288;" ::: "memory");
            const unsigned epoch = epoch_of(cnt1);
            if (lane == 0) st_rlx(gs->cnt[cta], epoch);
            signal_and_wait(&gs->cnt[0][1], epoch * NCTA, lane);
            if (lane == 0) {
                const uint4* q = gs->q[cta >> 5];
                bulk_load_nohint(sb + slot_off(IT_Q), q, SLOT, sb + SM_FULL + IT_Q * 8);
                bulk_load_nohint(sb + slot_off(IT_Q + 1), q + 1024, SLOT, sb + SM_FULL + (IT_Q + 1) * 8);
            }
            asm volatile("bar.sync 3, 288;" ::: "memory");
            signal_and_wait(&gs->cnt[0][2], epoch * NCTA, lane);
            mbar_wait(sb + SM_EMPTY + (IT_OP - NSLOT) * 8);
            mbar_wait(sb + SM_EMPTY + (IT_OP + 1 - NSLOT) * 8);
            if (lane == 0) {
                const uint4* op = gs->op[cta];
                bulk_load_nohint(sb + SM_MX, gs->stat[h], 1024, sb + SM_FULL + IT_OP * 8);
                uint32_t t1 = timer_ns();
#pragma unroll 1
                for (int i = 0; i < 8; i++) {
                    while ((int)(timer_ns() - t1) < 0) {}
                    t1 += OPGAP;
                    bulk_load_nohint(sb + slot_off(IT_OP) + i * 4096, op + i * 256, 4096, sb + SM_FULL + (IT_OP + i / 4) * 8);
                }
            }
            mbar_wait(sb + SM_FULL + (IT_V1 + 4) * 8);
            if (lane == 0) bulk_load_nohint(sb + SM_LAT, gs->lat[h], 4096, sb + SM_FULL + BAR_LAT * 8);
            mbar_wait(sb + SM_EMPTY + (IT_X - NSLOT) * 8);
            mbar_wait(sb + SM_FULL + (IT_WUV + 1) * 8);
            wait_due(IT_WO - 4, TAPER + ((j & 1) ? XS : XF) + (slice < 32 ? -XB : XB));
            if (lane == 0) bulk_load_nohint(sb + slot_off(IT_X), gs->x[slice >> 5][(j & 1) * 16], SLOT, sb + SM_FULL + IT_X * 8);
        }
        return;
    }

    const int g = lane >> 2, t = lane & 3;
    const uint32_t in0 = sb + SM_IN0, in1 = sb + SM_IN1;
    const int ba = cta >> 5, ha = cta & 31;
    auto xpos = [](int head) { return (int)(PIECE_OF >> (head >> 1) * 4 & 15) * 2 + (head & 1); };
    uint32_t* const ctx_dst = &gs->x[1][xpos(h)][(j * 4 + (w & 3)) * 16 + ((g ^ (w & 2)) & 3) * 4 + ((t - w) & 3)];
    uint32_t* const o_dst = &gs->x[0][xpos(ha)][ba * 64 + ((tid & 60) ^ ((ba & 1) * 16)) + ((t - g) & 3)];
    uint32_t* const lat_dst = &gs->lat[h][g & 3][j * 64 + ((w >> 1) ^ (g & 1)) * 16 + t * 4 + ((w * 2 ^ t) & 2)];
    {
#pragma unroll
        for (int k = 4; k < 8; k++) {
            while (__all_sync(0xffffffffu, (int)(timer_ns() - (tz + (2 * k - 1) * (PACE / 4))) < 0)) {}
            lsu_piece(k);
        }
        if (lane < 16) st_rlx2(lat_dst, EMPTY, EMPTY);
        if (lane >= 16 && w < 4) st_rlx(ctx_dst, EMPTY);
        if (w >= 6) st_rlx(o_dst, EMPTY);
        if (cta == 0 && w == 5) st_rlx((uint32_t*)gs->late + lane, 0u);
        if (tid < 128) sts128((tid < 64 ? in0 : in1) + ((tid >> 4) & 3) * 272 + (tid & 15) * 16, xv);
        asm volatile("cp.async.wait_group 1;" ::: "memory");
    }
    asm volatile("bar.sync 4, 384;" ::: "memory");
    const uint32_t tag = epoch_tag(epoch_of(cnt1));

    float acc[2][2];
    tile_mma<true, false>(sb, IT_WQB, in0, w, lane, acc);
    publish(gs->part[0][cta], w, lane, acc, tag);
    asm volatile("cp.async.wait_group 0;" ::: "memory");
    bar_consumers();
    tile_mma<true, false>(sb, IT_WQA, in1, w, lane, acc);
    publish(gs->part[1][cta], w, lane, acc, tag);
    bar_consumers();

    const float SC = 0.08838834764831845f * 1.4426950408889634f;
    gather(gs->part[0][h * 4], in0, tid, tag);
    tile_mma<false>(sb, IT_WUK, in0, w, lane, acc);
    if (lane < 16) {
        uint32_t* q = reinterpret_cast<uint32_t*>(gs->q[g]) + (2 * j + (w >> 2)) * 1024 + h * 32 + t;
        const int ch = 2 * (w & 3);
        q[((ch) ^ (h & 7)) * 4]     = pack_bf16(acc[0][0] * SC, acc[0][1] * SC);
        q[((ch + 1) ^ (h & 7)) * 4] = pack_bf16(acc[1][0] * SC, acc[1][1] * SC);
    }
    __syncwarp();
    asm volatile("bar.arrive 3, 288;" ::: "memory");
    gather(gs->part[1][ha * 4], in1, tid, tag);

    uint32_t qf[16];
#pragma unroll
    for (int c = 0; c < 8; c++) {
        qf[2 * c]     = lds32(in1 + ba * 272 + ((c ^ g) << 4) + t * 4);
        qf[2 * c + 1] = lds32(in1 + ba * 272 + 128 + ((c ^ g) << 4) + t * 4);
    }
    const uint32_t sc_w = sb + SM_SC + w * 512;
    auto k_item = [&](int item, uint32_t sc) {
        mbar_wait(sb + SM_FULL + item * 8);
        const uint32_t base = sb + slot_off(item) + ((lane & 7) + (lane & 8)) * 256 + ((lane >> 4) << 7);
        float s[4][4];
#pragma unroll
        for (int T = 0; T < 4; T++) { s[T][0] = s[T][1] = s[T][2] = s[T][3] = 0.f; }
#pragma unroll
        for (int c = 0; c < 8; c++) {
            const uint32_t a = base + ((c ^ (lane & 7)) << 4);
#pragma unroll
            for (int T = 0; T < 4; T++) {
                uint32_t r0, r1, r2, r3;
                ldsm4(a + T * 4096, r0, r1, r2, r3);
                mma16816(s[T], r0, r1, r2, r3, qf[2 * c], qf[2 * c + 1]);
            }
        }
        __syncwarp();
        if (lane == 0) mbar_arrive8(sb + SM_EMPTY + item * 8);
        if (t == (g >> 1)) {
#pragma unroll
            for (int T = 0; T < 4; T++) {
                stsf(sc + (16 * T + g) * 4,     (g & 1) ? s[T][1] : s[T][0]);
                stsf(sc + (16 * T + g + 8) * 4, (g & 1) ? s[T][3] : s[T][2]);
            }
        }
    };
    k_item(IT_K0 + w, sc_w);

    {
        float s[2][2][4];
#pragma unroll
        for (int i = 0; i < 16; i++) (&s[0][0][0])[i] = 0.f;
        mbar_wait(sb + SM_FULL + IT_Q * 8);
        mbar_wait(sb + SM_FULL + (IT_Q + 1) * 8);
        mbar_wait(sb + SM_FULL + (IT_C + w) * 8);
        const uint32_t cb0 = sb + slot_off(IT_C + w) + (lane & 7) * 128 + (lane >> 4) * 8192;
        const uint32_t cx = (((lane >> 3) & 1) ^ (lane & 7)) << 4;
        const uint32_t qr = ((lane & 7) + (lane & 8)) * 128;
        const uint32_t qx = ((lane >> 4) ^ (lane & 7)) << 4;
#pragma unroll
        for (int cb = 0; cb < 8; cb++) {
            const uint32_t qb = sb + slot_off(IT_Q + (cb >> 2)) + (cb & 3) * 4096 + qr;
#pragma unroll
            for (int k4 = 0; k4 < 4; k4++) {
                uint32_t b0, b1, b2, b3, a0, a1, a2, a3;
                ldsm4(cb0 + cb * 1024 + (cx ^ (k4 << 5)), b0, b1, b2, b3);
                ldsm4(qb + (qx ^ (k4 << 5)), a0, a1, a2, a3);
                mma16816(s[0][0], a0, a1, a2, a3, b0, b1);
                mma16816(s[0][1], a0, a1, a2, a3, b2, b3);
                ldsm4(qb + 2048 + (qx ^ (k4 << 5)), a0, a1, a2, a3);
                mma16816(s[1][0], a0, a1, a2, a3, b0, b1);
                mma16816(s[1][1], a0, a1, a2, a3, b2, b3);
            }
        }
        __syncwarp();
        if (lane == 0) { mbar_arrive(sb + SM_EMPTY + IT_Q * 8); mbar_arrive(sb + SM_EMPTY + (IT_Q + 1) * 8); }
#pragma unroll
        for (int r = 0; r < 4; r++) {
            const int mt = r >> 1, hi = (r & 1) * 2;
            float m = fmaxf(fmaxf(s[mt][0][hi], s[mt][0][hi + 1]), fmaxf(s[mt][1][hi], s[mt][1][hi + 1]));
            m = fmaxf(m, __shfl_xor_sync(0xffffffffu, m, 1));
            m = fmaxf(m, __shfl_xor_sync(0xffffffffu, m, 2));
            if (t == 0) stsf(sb + SM_MX + (8 * r + g) * 32 + w * 4, m);
        }
        bar_consumers();
        uint32_t pf[2][4];
#pragma unroll
        for (int r = 0; r < 4; r++) {
            const int mt = r >> 1, hi = r & 1;
            const float4 m0 = ldsf4(sb + SM_MX + (8 * r + g) * 32), m1 = ldsf4(sb + SM_MX + (8 * r + g) * 32 + 16);
            const float m = fmaxf(fmaxf(fmaxf(m0.x, m0.y), fmaxf(m0.z, m0.w)), fmaxf(fmaxf(m1.x, m1.y), fmaxf(m1.z, m1.w)));
            const uint32_t p0 = pack_bf16(ex2(s[mt][0][2 * hi] - m), ex2(s[mt][0][2 * hi + 1] - m));
            const uint32_t p1 = pack_bf16(ex2(s[mt][1][2 * hi] - m), ex2(s[mt][1][2 * hi + 1] - m));
            pf[mt][hi] = p0; pf[mt][2 + hi] = p1;
            float l = (bf_lo(p0) + bf_hi(p0)) + (bf_lo(p1) + bf_hi(p1));
            l += __shfl_xor_sync(0xffffffffu, l, 1);
            l += __shfl_xor_sync(0xffffffffu, l, 2);
            if (t == 0) stsf(sb + SM_SUM + (8 * r + g) * 32 + w * 4, l);
        }
        sts128(sb + SM_PF + (w * 2 + 0) * 512 + lane * 16, make_uint4(pf[0][0], pf[0][1], pf[0][2], pf[0][3]));
        sts128(sb + SM_PF + (w * 2 + 1) * 512 + lane * 16, make_uint4(pf[1][0], pf[1][1], pf[1][2], pf[1][3]));
        bar_consumers();
        if (w == 0) {
            const float4 m0 = ldsf4(sb + SM_MX + lane * 32), m1 = ldsf4(sb + SM_MX + lane * 32 + 16);
            const float4 l0 = ldsf4(sb + SM_SUM + lane * 32), l1 = ldsf4(sb + SM_SUM + lane * 32 + 16);
            const float m = fmaxf(fmaxf(fmaxf(m0.x, m0.y), fmaxf(m0.z, m0.w)), fmaxf(fmaxf(m1.x, m1.y), fmaxf(m1.z, m1.w)));
            const float l = ((l0.x + l0.y) + (l0.z + l0.w)) + ((l1.x + l1.y) + (l1.z + l1.w));
            gs->stat[lane][cta] = make_float2(m, l);
        }
        float o[2][8][4];
#pragma unroll
        for (int i = 0; i < 64; i++) (&o[0][0][0])[i] = 0.f;
        const uint32_t vr = w * 1024 + (lane & 7) * 128 + (lane & 8) * 1024;
        const uint32_t vx = ((lane >> 4) ^ (lane & 7)) << 4;
#pragma unroll
        for (int ks = 0; ks < 8; ks++) {
            const uint4 p0 = lds128(sb + SM_PF + (ks * 2 + 0) * 512 + lane * 16);
            const uint4 p1 = lds128(sb + SM_PF + (ks * 2 + 1) * 512 + lane * 16);
            const uint32_t vb = sb + slot_off(IT_C + ks) + vr;
#pragma unroll
            for (int n2 = 0; n2 < 4; n2++) {
                uint32_t b0, b1, b2, b3;
                ldsm4t(vb + (vx ^ (n2 << 5)), b0, b1, b2, b3);
                mma16816(o[0][2 * n2],     p0.x, p0.y, p0.z, p0.w, b0, b1);
                mma16816(o[0][2 * n2 + 1], p0.x, p0.y, p0.z, p0.w, b2, b3);
                mma16816(o[1][2 * n2],     p1.x, p1.y, p1.z, p1.w, b0, b1);
                mma16816(o[1][2 * n2 + 1], p1.x, p1.y, p1.z, p1.w, b2, b3);
            }
            __syncwarp();
            if (lane == 0) mbar_arrive(sb + SM_EMPTY + (IT_C + ks) * 8);
        }
        mbar_wait(sb + SM_FULL + (IT_K1 + 1 + (w * 3 >> 2)) * 8);
#pragma unroll
        for (int r = 0; r < 4; r++) {
            const int mt = r >> 1, hi = (r & 1) * 2;
            uint4* dst = gs->op[(8 * r + g) * 4 + (w >> 1)] + (cta >> 6) * 1024 + (w & 1) * 512 + (cta & 63) * 8;
#pragma unroll
            for (int u = 0; u < 2; u++) {
                uint4 v;
                v.x = pack_bf16(o[mt][4 * u][hi],     o[mt][4 * u][hi + 1]);
                v.y = pack_bf16(o[mt][4 * u + 1][hi], o[mt][4 * u + 1][hi + 1]);
                v.z = pack_bf16(o[mt][4 * u + 2][hi], o[mt][4 * u + 2][hi + 1]);
                v.w = pack_bf16(o[mt][4 * u + 3][hi], o[mt][4 * u + 3][hi + 1]);
                dst[(t + 4 * u) ^ (cta & 7)] = v;
            }
        }
        asm volatile("bar.arrive 3, 288;" ::: "memory");
    }

    k_item(IT_K1 + w, sc_w + 256);
    __syncwarp();
    {
        const float4 s = ldsf4(sc_w + lane * 16);
        float m = fmaxf(fmaxf(s.x, s.y), fmaxf(s.z, s.w));
#pragma unroll
        for (int d = 1; d < 32; d <<= 1) m = fmaxf(m, __shfl_xor_sync(0xffffffffu, m, d));
        if (lane == 0) stsf(sb + SM_ML + w * 4, m);
        bar_consumers();
        const float4 m0 = ldsf4(sb + SM_ML), m1 = ldsf4(sb + SM_ML + 16);
        m = fmaxf(fmaxf(fmaxf(m0.x, m0.y), fmaxf(m0.z, m0.w)), fmaxf(fmaxf(m1.x, m1.y), fmaxf(m1.z, m1.w))) * SC;
        const uint32_t p0 = pack_bf16(ex2(fmaf(s.x, SC, -m)), ex2(fmaf(s.y, SC, -m)));
        const uint32_t p1 = pack_bf16(ex2(fmaf(s.z, SC, -m)), ex2(fmaf(s.w, SC, -m)));
        float l = (bf_lo(p0) + bf_hi(p0)) + (bf_lo(p1) + bf_hi(p1));
#pragma unroll
        for (int d = 1; d < 32; d <<= 1) l += __shfl_xor_sync(0xffffffffu, l, d);
        if (lane == 0) stsf(sb + SM_ML + 32 + w * 4, l);
        sts64(sb + SM_PA + w * 256 + lane * 8, p0, p1);
        __syncwarp();
    }

    float oa[4][4];
#pragma unroll
    for (int i = 0; i < 16; i++) (&oa[0][0])[i] = 0.f;
    auto v_item = [&](int item, uint32_t pa) {
        uint32_t p[8];
#pragma unroll
        for (int i = 0; i < 8; i++) p[i] = lds32(pa + i * 16 + t * 4);
        mbar_wait(sb + SM_FULL + item * 8);
        const uint32_t base = sb + slot_off(item) + ((lane & 7) + ((lane >> 4) << 3)) * 256 + ((lane & 8) << 4);
#pragma unroll
        for (int c = 0; c < 8; c++) {
            const uint32_t a = base + ((c ^ (lane & 7)) << 4);
            const uint32_t mask = ((c == (g ^ (2 * t))) ? 0x0000ffffu : 0u) | ((c == (g ^ (2 * t + 1))) ? 0xffff0000u : 0u);
#pragma unroll
            for (int T = 0; T < 4; T++) {
                uint32_t r0, r1, r2, r3;
                ldsm4t(a + T * 4096, r0, r1, r2, r3);
                mma16816(oa[T], r0, r1, r2, r3, p[2 * T] & mask, p[2 * T + 1] & mask);
            }
        }
        __syncwarp();
        if (lane == 0) mbar_arrive8(sb + SM_EMPTY + item * 8);
    };
    sts64(sb + SM_FIN + tid * 8, EMPTY, EMPTY);
    if (w == 0) sts32(sb + SM_CNT + lane * 4, 0u);
    v_item(IT_V0 + w, sb + SM_PA + w * 256);

    mbar_wait(sb + SM_FULL + IT_OP * 8);
    if (w < 4) {
        const float2 st = ldsf2(sb + SM_MX + tid * 8);
        float m = st.x;
#pragma unroll
        for (int d = 1; d < 32; d <<= 1) m = fmaxf(m, __shfl_xor_sync(0xffffffffu, m, d));
        const uint32_t wb = pack_bf16(ex2(st.x - m), 0.f);
        float l = bf_lo(wb) * st.y;
#pragma unroll
        for (int d = 1; d < 32; d <<= 1) l += __shfl_xor_sync(0xffffffffu, l, d);
#pragma unroll
        for (int bb = 0; bb < 4; bb++) sts16(in0 + bb * 272 + tid * 2, bb == w ? (uint16_t)wb : (uint16_t)0);
        if (lane == 0) stsf(sb + SM_ML + 64 + w * 4, 1.f / l);
    }
    bar_consumers();
    tile_mma<true>(sb, IT_OP, in0, w, lane, acc);
    if (lane < 16) {
        const float inv = ldsf(sb + SM_ML + 64 + g * 4);
        const uint32_t v0 = pack_bf16(acc[0][0] * inv, acc[0][1] * inv), v1 = pack_bf16(acc[1][0] * inv, acc[1][1] * inv);
        st_rlx2(lat_dst, (t & 1) ? v1 : v0, (t & 1) ? v0 : v1);
    }

    {
        const float4 l0 = ldsf4(sb + SM_ML + 32), l1 = ldsf4(sb + SM_ML + 48);
        const float inv = 1.f / (((l0.x + l0.y) + (l0.z + l0.w)) + ((l1.x + l1.y) + (l1.z + l1.w)));
        v_item(IT_V1 + w, sb + SM_PA + w * 256 + 128);
        const uint32_t so = sb + SM_PF + w * 512 + (16 * t + g) * 4;
        stsf(so,       (oa[0][0] + oa[1][0]) + (oa[2][0] + oa[3][0]));
        stsf(so + 32,  (oa[0][1] + oa[1][1]) + (oa[2][1] + oa[3][1]));
        stsf(so + 256, (oa[0][2] + oa[1][2]) + (oa[2][2] + oa[3][2]));
        stsf(so + 288, (oa[0][3] + oa[1][3]) + (oa[2][3] + oa[3][3]));
        if (w < 6) {
            asm volatile("bar.arrive 1, 256;" ::: "memory");
        } else {
            bar_consumers();
            float x = 0.f, y = 0.f;
#pragma unroll
            for (int i = 0; i < 8; i++) {
                const float2 v = ldsf2(sb + SM_PF + i * 512 + (tid & 63) * 8);
                x += v.x; y += v.y;
            }
            st_rlx(o_dst, pack_bf16(x * inv, y * inv));
        }
    }

    if (w < 4) {
        const uint32_t lo = (g & 3) * 1024 + (g >> 2) * 512 + (g & 1) * 64 + t * 16;
        const int wd = ((lane >> 2 & 2) + (lane >> 4)) ^ (lane >> 1 & 3);
        const uint32_t base = sb + ((lane & 6) * 4 + wd * 2 + (lane & 1)) * 64 + (((w ^ wd) & 3) << 4);
        const uint64_t dst = __shfl_sync(0xffffffffu, (unsigned long long)ctx_dst, lane);
        mbar_wait(sb + SM_FULL + BAR_LAT * 8);
        uint4 a[8];
#pragma unroll
        for (int i = 0; i < 8; i++) a[i] = lds128(sb + SM_LAT + (lo ^ (i * 64)));
        int it = 0;
        while (refetch(a, [&](int i) { return (const char*)gs->lat[h] + (lo ^ (i * 64)); }))
            if (++it > SPIN_LIMIT) __trap();
        float v0 = 0.f, v1 = 0.f;
#pragma unroll
        for (int i = 0; i < 2; i++) {
            float c[4][4];
#pragma unroll
            for (int k = 0; k < 16; k++) (&c[0][0])[k] = 0.f;
            c[0][0] = v0; c[0][1] = v1;
            mbar_wait(sb + SM_FULL + (IT_WUV + i) * 8);
#pragma unroll
            for (int kk = 0; kk < 8; kk++) {
                uint32_t r0, r1, r2, r3;
                ldsm4t(base + slot_off(IT_WUV + i) + kk * 2048, r0, r1, r2, r3);
                mma16816(c[2 * (kk & 1)],     a[kk].x, a[kk].y, a[kk].z, a[kk].w, r0, r1);
                mma16816(c[2 * (kk & 1) + 1], a[kk].x, a[kk].y, a[kk].z, a[kk].w, r2, r3);
            }
            v0 = (c[0][0] + c[1][2]) + (c[2][0] + c[3][2]);
            v1 = (c[0][1] + c[1][3]) + (c[2][1] + c[3][3]);
            if (i == 0) { v0 = __shfl_xor_sync(0xffffffffu, v0, 16); v1 = __shfl_xor_sync(0xffffffffu, v1, 16); }
        }
        st_rlx_if(dst, pack_bf16(v0, v1), lane >= 16);
    }

    {
        const bool isB = slice >= 32;
        const int r = j & 1;
        const uint32_t cs = isB ? 256 : 64;
        const uint32_t xl = (isB ? t * 64 + (((g >> 1) ^ (t & 2)) << 4) : (g >> 1) * 256 + ((g & 2) * 2 + t) * 16) + (w >> 1) * 1024 + (w & 1) * 2 * cs;
        auto xoff = [&](int i) { return (i >> 1) * 4096 + (xl ^ ((i & 1) * cs)); };
        const char* src = (const char*)gs->x[slice >> 5][r * 16];
        uint32_t off[2];
#pragma unroll
        for (int u = 0; u < 2; u++) {
            const int tt = (lane & 7) >> 1, row = 8 * tt + 2 * ((2 * u + (lane >> 4) + tt) & 3) + (lane & 1);
            off[u] = sb + w * 2048 + row * 32 + ((((lane >> 3) ^ (row >> 2)) & 1) << 4);
        }
        uint32_t fin[2], rcv[2];
#pragma unroll
        for (int e = 0; e < 2; e++) {
            const uint32_t o = t * 16 + (e ^ (t >> 1)) * 8 + g;
            fin[e] = __shfl_sync(0xffffffffu, sb + SM_FIN + (w >> 1) * 512 + o * 8 + ((w ^ t) & 1) * 4, lane);
            rcv[e] = __shfl_sync(0xffffffffu, sb + SM_RCV + o * 4, lane);
        }
        const uint32_t cnt = __shfl_sync(0xffffffffu, sb + SM_CNT + lane * 4, lane), sum = __shfl_sync(0xffffffffu, sb + SM_FIN + lane * 16, lane);
        const uint32_t inc = __shfl_sync(0xffffffffu, lane, 1 + r), last = __shfl_sync(0xffffffffu, lane, 7 + 7 * r);
        const uint32_t snd = __shfl_sync(0xffffffffu, map_cta(sb + SM_RCV + lane * 8, 0), lane),
                       sbar = __shfl_sync(0xffffffffu, map_cta(sb + SM_LAST + 8 + (lane & 16), 0), lane & 15);
        const uint64_t dst = __shfl_sync(0xffffffffu, (unsigned long long)(out + (lane >> 3) * 1024 + slice * 16 + ((lane ^ (lane >> 2 & 4)) & 7) * 2), lane);
        uint32_t a[2][4][4];
        uint4 x[8];
        float c[4][4];
        auto load_w = [&](int i) {
            mbar_wait(i < 2 ? sb + SM_FULL + (IT_WO + i) * 8 : sb + SM_LAST + w * 16 + (i & 1) * 8);
#pragma unroll
            for (int q = 0; q < 4; q++)
                ldsm4t(slot_off(IT_WO + i) + off[q & 1] + (q >> 1) * 1024, a[i & 1][q][0], a[i & 1][q][1], a[i & 1][q][2], a[i & 1][q][3]);
        };
        auto mma_w = [&](int i) {
#pragma unroll
            for (int q = 0; q < 4; q++) {
                const uint4& b = x[2 * i + (q >> 1)];
                if (i == 0) c[q][0] = c[q][1] = c[q][2] = c[q][3] = 0.f;
                mma16816(c[q], a[i & 1][q][0], a[i & 1][q][1], a[i & 1][q][2], a[i & 1][q][3], (q & 1) ? b.z : b.x, (q & 1) ? b.w : b.y);
            }
        };
        load_w(0); load_w(1);
        mbar_wait(sb + SM_FULL + IT_X * 8);
#pragma unroll
        for (int i = 0; i < 8; i++) x[i] = lds128(sb + slot_off(IT_X) + xoff(i));
        int it = 0;
        while (true) {
            mma_w(0); mma_w(1);
            if (!refetch(x, [&](int i) { return src + xoff(i); })) break;
            if (++it > SPIN_LIMIT) __trap();
        }
        load_w(2);
        mma_w(2);
        load_w(3);
        uint32_t rank;
        const float pr[2] = {ldsf_if(rcv[0], w == 0 && r == 0), ldsf_if(rcv[1], w == 0 && r == 0)};
        mma_w(3);
#pragma unroll
        for (int e = 0; e < 2; e++) stv(fin[e], (((c[0][2 * e] + pr[e]) + c[1][2 * e]) + c[2][2 * e]) + c[3][2 * e]);
        float4 p[4];
        float s0, s1;
        auto add_up = [&]() {
#pragma unroll
            for (int k = 0; k < 4; k++) p[k] = ldv4(sum + k * 512);
            const float a0 = ((p[0].x + p[0].y) + (p[1].x + p[1].y)) + (p[2].x + p[2].y), b0 = p[3].x + p[3].y;
            const float a1 = ((p[0].z + p[0].w) + (p[1].z + p[1].w)) + (p[2].z + p[2].w), b1 = p[3].z + p[3].w;
            s0 = a0 + b0; s1 = a1 + b1;
            uint32_t nan;
            asm("{\n.reg .pred p;\nsetp.ne.u32 p, %5, 0;\nsetp.nan.or.f32 p, %1, %2, p;\nsetp.nan.or.f32 p, %3, %4, p;\nselp.u32 %0, 1, 0, p;\n}"
                : "=r"(nan) : "f"(a0), "f"(a1), "f"(b0), "f"(b1), "r"(r));
            return nan;
        };
        asm volatile("atom.relaxed.cta.shared.add.u32 %0, [%1], %2;" : "=r"(rank) : "r"(cnt), "r"(inc) : "memory");
        const uint32_t redo = add_up();
        st_if(dst, pack_bf16(s0, s1), rank == 7);
        if (!redo) return;
        const bool num = s0 == s0 && s1 == s1;
        st_async64_if(snd, s0, s1, sbar, rank == 14 && num);
        if (rank != last || num) return;
        auto mx = [](float4 q) { return max(max(__float_as_uint(q.x), __float_as_uint(q.y)), max(__float_as_uint(q.z), __float_as_uint(q.w))); };
        for (it = 0; max(max(mx(p[0]), mx(p[1])), max(mx(p[2]), mx(p[3]))) == EMPTY; it++) {
            add_up();
            if (it > SPIN_LIMIT) __trap();
        }
        if (r) st_async64_if(snd, s0, s1, sbar, true);
        else st_if(dst, pack_bf16(s0, s1), true);
    }
}

typedef CUresult (*EncodeTiledFn)(CUtensorMap*, CUtensorMapDataType, cuuint32_t, void*, const cuuint64_t*,
                                  const cuuint64_t*, const cuuint32_t*, const cuuint32_t*, CUtensorMapInterleave,
                                  CUtensorMapSwizzle, CUtensorMapL2promotion, CUtensorMapFloatOOBfill);

void encode_map(EncodeTiledFn enc, CUtensorMap* tm, const void* p, cuuint64_t cols, cuuint64_t rows,
                cuuint32_t brows, cuuint32_t bblk) {
    cuuint64_t dims[3] = {64, rows, cols / 64};
    cuuint64_t strides[2] = {cols * 2, 128};
    cuuint32_t box[3] = {64, brows, bblk};
    cuuint32_t es[3] = {1, 1, 1};
    enc(tm, CU_TENSOR_MAP_DATA_TYPE_BFLOAT16, 3, const_cast<void*>(p), dims, strides, box, es,
        CU_TENSOR_MAP_INTERLEAVE_NONE, CU_TENSOR_MAP_SWIZZLE_128B, CU_TENSOR_MAP_L2_PROMOTION_L2_256B,
        CU_TENSOR_MAP_FLOAT_OOB_FILL_NONE);
}

void encode_slice_map(EncodeTiledFn enc, CUtensorMap* tm, const void* p, cuuint64_t cols, cuuint64_t rows,
                      cuuint32_t bcols, cuuint32_t brows) {
    cuuint64_t dims[3] = {cols, 256, rows / 256};
    cuuint64_t strides[2] = {cols * 2, cols * 512};
    cuuint32_t box[3] = {bcols, brows, 1};
    cuuint32_t es[3] = {1, 1, 1};
    enc(tm, CU_TENSOR_MAP_DATA_TYPE_BFLOAT16, 3, const_cast<void*>(p), dims, strides, box, es, CU_TENSOR_MAP_INTERLEAVE_NONE,
        bcols == 16 ? CU_TENSOR_MAP_SWIZZLE_32B : CU_TENSOR_MAP_SWIZZLE_64B, CU_TENSOR_MAP_L2_PROMOTION_L2_128B,
        CU_TENSOR_MAP_FLOAT_OOB_FILL_NONE);
}

}

extern "C" void kernel_launch(void* const* d_in, const int* in_sizes, int n_in, void* d_out, int out_size) {
    (void)in_sizes; (void)n_in; (void)out_size;
    static EncodeTiledFn enc = nullptr;
    static Scratch* gs = nullptr;
    if (!enc) {
        cudaGetSymbolAddress((void**)&gs, g_scratch);
        void* fn = nullptr;
        cudaDriverEntryPointQueryResult qr;
        cudaGetDriverEntryPoint("cuTensorMapEncodeTiled", &fn, cudaEnableDefault, &qr);
        enc = (EncodeTiledFn)fn;
        cudaFuncSetAttribute(fused_decode_kernel, cudaFuncAttributeMaxDynamicSharedMemorySize, SM_END);
    }
    Maps maps;
    encode_map(enc, &maps.wuk, d_in[8], 4096, 512, 32, 2);
    encode_slice_map(enc, &maps.wuv, d_in[9], 4096, 512, 32, 128);
    encode_slice_map(enc, &maps.woB, d_in[10], 512, 4096, 16, 256);
    encode_slice_map(enc, &maps.woA, d_in[4], 512, 4096, 16, 256);
    encode_slice_map(enc, &maps.endB, d_in[10], 512, 4096, 16, 64);
    encode_slice_map(enc, &maps.endA, d_in[4], 512, 4096, 16, 64);
    encode_map(enc, &maps.ckv, d_in[6], 512, 16384, 8, 8);
    uint64_t first = (uint64_t)d_in[7];
    if ((uint32_t)first >= 0xffe00000u) first += 1 << 21;
    fused_decode_kernel<<<NCTA, NTHR, SM_END>>>(make_uint2((uint32_t)first, (uint32_t)(first >> 32)),
                                                (const __nv_bfloat16*)d_in[0], (const __nv_bfloat16*)d_in[5],
                                                (const __nv_bfloat16*)d_in[7], (const __nv_bfloat16*)d_in[3],
                                                (const __nv_bfloat16*)d_in[1] + 3072 * 128, (const __nv_bfloat16*)d_in[2] + 3072 * 128,
                                                (__nv_bfloat16*)d_out, gs, maps);
}
```

```cpp
#include <cuda_runtime.h>
#include <cuda_bf16.h>
#include <cuda.h>
#include <stdint.h>

namespace {

constexpr int NCTA   = 128;
constexpr int NSLOT  = 13;
constexpr int SLOT   = 16384;
constexpr int NITEM  = 56;
constexpr int NTHR   = 384;

constexpr int INFLIGHT = 4;
constexpr int PACE     = 644;
constexpr int LEAD     = 530;
constexpr int TAPER    = 270;
constexpr int OS0      = -130;
constexpr int OS1      = 243;
constexpr int OF0      = -240;
constexpr int OF1      = 470;
constexpr int OF2      = 1665;
constexpr int OF3      = 165;
constexpr int XS       = 1300;
constexpr int XF       = 1590;
constexpr uint64_t ROWS_A = 0x170fdba954326ec8ull, ROWS_B = 0x7659fecb321048daull;
constexpr uint64_t inverse(uint64_t rows) {
    uint64_t r = 0;
    for (uint64_t n = 0; n < 16; n++) r |= n << (rows >> n * 4 & 15) * 4;
    return r;
}
constexpr uint64_t PIECE_A = inverse(ROWS_A), PIECE_B = inverse(ROWS_B);
constexpr int OPGAP    = 250;
constexpr int NWIN     = 4;
__device__ constexpr int win_pos(int k)  { return k == 0 ? 10 : k == 1 ? 20 : k == 2 ? 31 : 38; }
__device__ constexpr int win_late(int k) { return k == 0 ? 1790 : k == 1 ? 1825 : k == 2 ? 1825 : 1715; }
constexpr int GAIN     = 11;

constexpr int IT_WQB = 0, IT_WQA = 2, IT_WUK = 4, IT_K0 = 6, IT_Q = 14, IT_C = 16, IT_K1 = 24, IT_V0 = 32,
              IT_OP = 40, IT_V1 = 42, IT_WUV = 50, IT_WO = 52;
constexpr int IT_X = 56;
constexpr int BAR_LAT = 55;

constexpr int SM_FULL  = NSLOT * SLOT;
constexpr int SM_EMPTY = SM_FULL + 512;
constexpr int SM_IN0   = SM_EMPTY + 512;
constexpr int SM_IN1   = SM_IN0 + 1088;
constexpr int SM_SC    = SM_IN1 + 1088;
constexpr int SM_PA    = SM_SC + 4096;
constexpr int SM_PF    = SM_PA + 2048;
constexpr int SM_MX    = SM_PF + 8192;
constexpr int SM_ML    = SM_MX + 1024;
constexpr int SM_LAST  = SM_ML + 128;
constexpr int SM_CNT   = SM_LAST + 128;
constexpr int SM_RCV   = SM_CNT + 128;
constexpr int SM_PACE  = SM_RCV + 256;
constexpr int SM_END   = SM_PACE + 32;
constexpr int SM_LAT   = SM_PF + 4096;
constexpr int SM_FIN   = SM_SC;
constexpr int SM_SUM   = SM_IN0;
static_assert(SM_END <= 232448, "smem");

struct Maps { CUtensorMap wuk, wuv, woA, woB, ckv, endA, endB; };

struct Scratch {
    uint64_t late[16];
    unsigned cnt[NCTA][32];
    float    part[2][NCTA][512];
    uint32_t x[2][32][256];
    uint32_t lat[32][4][256];
    uint4    q[4][2048];
    uint4    op[NCTA][2048];
    float2   stat[32][128];
};
__device__ __align__(128) Scratch g_scratch;

constexpr int SPIN_LIMIT = 1 << 22;

__device__ __forceinline__ uint32_t smem_u32(const void* p) { return (uint32_t)__cvta_generic_to_shared(p); }
__device__ __forceinline__ void mbar_init(uint32_t bar, uint32_t cnt) {
    asm volatile("mbarrier.init.shared::cta.b64 [%0], %1;" ::"r"(bar), "r"(cnt) : "memory");
}
__device__ __forceinline__ void mbar_expect_tx(uint32_t bar, uint32_t bytes) {
    asm volatile("mbarrier.arrive.expect_tx.shared::cta.b64 _, [%0], %1;" ::"r"(bar), "r"(bytes) : "memory");
}
__device__ __forceinline__ void mbar_arrive(uint32_t bar) {
    asm volatile("mbarrier.arrive.shared::cta.b64 _, [%0];" ::"r"(bar) : "memory");
}
__device__ __forceinline__ void mbar_arrive8(uint32_t bar) {
    asm volatile("mbarrier.arrive.shared::cta.b64 _, [%0], 8;" ::"r"(bar) : "memory");
}
__device__ __forceinline__ void mbar_wait(uint32_t bar) {
    uint32_t done;
    int it = 0;
    do {
        asm volatile("{\n.reg .pred p;\nmbarrier.try_wait.parity.shared::cta.b64 p, [%1], 0;\nselp.u32 %0, 1, 0, p;\n}"
                     : "=r"(done) : "r"(bar) : "memory");
        if (++it > SPIN_LIMIT) __trap();
    } while (!done);
}
__device__ __forceinline__ uint32_t map_cta(uint32_t a, uint32_t rank) {
    uint32_t r; asm("mapa.shared::cluster.u32 %0, %1, %2;" : "=r"(r) : "r"(a), "r"(rank)); return r;
}
__device__ __forceinline__ void st_async64_if(uint32_t a, float x, float y, uint32_t bar, bool on) {
    asm volatile("{\n.reg .pred p;\nsetp.ne.u32 p, %4, 0;\n@p st.async.shared::cluster.mbarrier::complete_tx::bytes.v2.f32 [%0], {%1,%2}, [%3];\n}"
                 ::"r"(a), "f"(x), "f"(y), "r"(bar), "r"((uint32_t)on) : "memory");
}
__device__ __forceinline__ uint64_t evict_first() {
    uint64_t pol; asm volatile("createpolicy.fractional.L2::evict_first.b64 %0, 1.0;" : "=l"(pol)); return pol;
}
#define ELECT "{\n.reg .pred p;\nelect.sync _|p, 0xffffffff;\n@p "
__device__ __forceinline__ void bulk_load(uint32_t dst, const void* src, uint32_t bytes, uint32_t bar, uint64_t pol) {
    asm volatile(ELECT "cp.async.bulk.shared::cluster.global.mbarrier::complete_tx::bytes.L2::cache_hint [%0], [%1], %2, [%3], %4;\n}"
                 ::"r"(dst), "l"(src), "r"(bytes), "r"(bar), "l"(pol) : "memory");
}
__device__ __forceinline__ void bulk_load_nohint(uint32_t dst, const void* src, uint32_t bytes, uint32_t bar) {
    asm volatile("cp.async.bulk.shared::cluster.global.mbarrier::complete_tx::bytes [%0], [%1], %2, [%3];"
                 ::"r"(dst), "l"(src), "r"(bytes), "r"(bar) : "memory");
}
__device__ __forceinline__ void tma3d(uint32_t dst, const CUtensorMap* tm, int c0, int c1, int c2, uint32_t bar, uint64_t pol) {
    asm volatile(ELECT "cp.async.bulk.tensor.3d.shared::cluster.global.mbarrier::complete_tx::bytes.L2::cache_hint [%0], [%1, {%3, %4, %5}], [%2], %6;\n}"
                 ::"r"(dst), "l"(tm), "r"(bar), "r"(c0), "r"(c1), "r"(c2), "l"(pol) : "memory");
}
__device__ __forceinline__ void ldsm4(uint32_t a, uint32_t& r0, uint32_t& r1, uint32_t& r2, uint32_t& r3) {
    asm volatile("ldmatrix.sync.aligned.m8n8.x4.shared.b16 {%0,%1,%2,%3}, [%4];"
                 : "=r"(r0), "=r"(r1), "=r"(r2), "=r"(r3) : "r"(a) : "memory");
}
__device__ __forceinline__ void ldsm4t(uint32_t a, uint32_t& r0, uint32_t& r1, uint32_t& r2, uint32_t& r3) {
    asm volatile("ldmatrix.sync.aligned.m8n8.x4.trans.shared.b16 {%0,%1,%2,%3}, [%4];"
                 : "=r"(r0), "=r"(r1), "=r"(r2), "=r"(r3) : "r"(a) : "memory");
}
__device__ __forceinline__ void mma16816(float (&c)[4], uint32_t a0, uint32_t a1, uint32_t a2, uint32_t a3,
                                         uint32_t b0, uint32_t b1) {
    asm volatile("mma.sync.aligned.m16n8k16.row.col.f32.bf16.bf16.f32 {%0,%1,%2,%3}, {%4,%5,%6,%7}, {%8,%9}, {%0,%1,%2,%3};"
                 : "+f"(c[0]), "+f"(c[1]), "+f"(c[2]), "+f"(c[3])
                 : "r"(a0), "r"(a1), "r"(a2), "r"(a3), "r"(b0), "r"(b1));
}
__device__ __forceinline__ uint32_t lds32(uint32_t a) {
    uint32_t v; asm volatile("ld.shared.b32 %0, [%1];" : "=r"(v) : "r"(a) : "memory"); return v;
}
__device__ __forceinline__ float ldsf(uint32_t a) {
    float v; asm volatile("ld.shared.f32 %0, [%1];" : "=f"(v) : "r"(a) : "memory"); return v;
}
__device__ __forceinline__ float2 ldsf2(uint32_t a) {
    float2 v; asm volatile("ld.shared.v2.f32 {%0,%1}, [%2];" : "=f"(v.x), "=f"(v.y) : "r"(a) : "memory"); return v;
}
__device__ __forceinline__ float4 ldsf4(uint32_t a) {
    float4 v; asm volatile("ld.shared.v4.f32 {%0,%1,%2,%3}, [%4];" : "=f"(v.x), "=f"(v.y), "=f"(v.z), "=f"(v.w) : "r"(a) : "memory"); return v;
}
__device__ __forceinline__ uint4 lds128(uint32_t a) {
    uint4 v; asm volatile("ld.shared.v4.b32 {%0,%1,%2,%3}, [%4];" : "=r"(v.x), "=r"(v.y), "=r"(v.z), "=r"(v.w) : "r"(a) : "memory"); return v;
}
__device__ __forceinline__ float ldsf_if(uint32_t a, bool on) {
    float v = 0.f;
    asm volatile("{\n.reg .pred p;\nsetp.ne.u32 p, %2, 0;\n@p ld.shared.f32 %0, [%1];\n}" : "+f"(v) : "r"(a), "r"((uint32_t)on) : "memory");
    return v;
}
__device__ __forceinline__ float4 ldv4(uint32_t a) {
    float4 v; asm volatile("ld.volatile.shared.v4.f32 {%0,%1,%2,%3}, [%4];" : "=f"(v.x), "=f"(v.y), "=f"(v.z), "=f"(v.w) : "r"(a) : "memory"); return v;
}
__device__ __forceinline__ void stv(uint32_t a, float v) { asm volatile("st.volatile.shared.f32 [%0], %1;" ::"r"(a), "f"(v) : "memory"); }
__device__ __forceinline__ void sts16(uint32_t a, uint16_t v) { asm volatile("st.shared.b16 [%0], %1;" ::"r"(a), "h"(v) : "memory"); }
__device__ __forceinline__ void sts32(uint32_t a, uint32_t v) { asm volatile("st.shared.b32 [%0], %1;" ::"r"(a), "r"(v) : "memory"); }
__device__ __forceinline__ void stsf(uint32_t a, float v) { asm volatile("st.shared.f32 [%0], %1;" ::"r"(a), "f"(v) : "memory"); }
__device__ __forceinline__ void sts64(uint32_t a, uint32_t x, uint32_t y) {
    asm volatile("st.shared.v2.b32 [%0], {%1,%2};" ::"r"(a), "r"(x), "r"(y) : "memory");
}
__device__ __forceinline__ void sts128(uint32_t a, uint4 v) {
    asm volatile("st.shared.v4.b32 [%0], {%1,%2,%3,%4};" ::"r"(a), "r"(v.x), "r"(v.y), "r"(v.z), "r"(v.w) : "memory");
}
__device__ __forceinline__ uint32_t pack_bf16(float lo, float hi) {
    uint32_t r; asm("cvt.rn.bf16x2.f32 %0, %1, %2;" : "=r"(r) : "f"(hi), "f"(lo)); return r;
}
__device__ __forceinline__ float bf_lo(uint32_t v) { return __uint_as_float(v << 16); }
__device__ __forceinline__ float bf_hi(uint32_t v) { return __uint_as_float(v & 0xffff0000u); }
__device__ __forceinline__ float ex2(float x) { float y; asm("ex2.approx.ftz.f32 %0, %1;" : "=f"(y) : "f"(x)); return y; }
__device__ __forceinline__ uint32_t timer_ns() { uint32_t t; asm volatile("mov.u32 %0, %%globaltimer_lo;" : "=r"(t)); return t; }
__device__ __forceinline__ void bar_consumers() { asm volatile("bar.sync 1, 256;" ::: "memory"); }

__device__ __forceinline__ uint32_t tagf(float v, uint32_t tag) { return (__float_as_uint(v) & 0xffffff00u) | tag; }
__device__ __forceinline__ uint2 ld_rlx2(const void* p) {
    uint64_t v; asm volatile("ld.relaxed.gpu.global.b64 %0, [%1];" : "=l"(v) : "l"(p) : "memory");
    return make_uint2((uint32_t)v, (uint32_t)(v >> 32));
}
__device__ __forceinline__ float untag(uint32_t v) { return __uint_as_float(v & 0xffffff00u); }

__device__ __forceinline__ uint32_t slot_off(int item) { return (uint32_t)(item % NSLOT) * SLOT; }

template <bool TRANS, bool TMA = true>
__device__ __forceinline__ void tile_mma(uint32_t sb, int item, uint32_t in, int w, int lane, float (&acc)[2][2]) {
    const int g = lane >> 2, t = lane & 3;
    float c[4][4];
#pragma unroll
    for (int i = 0; i < 16; i++) (&c[0][0])[i] = 0.f;
    uint32_t a[16];
    const uint32_t ia = in + (g & 3) * 272 + t * 4;
#pragma unroll
    for (int i = 0; i < 16; i++) a[i] = lds32(ia + i * 16);
    const uint32_t s0 = sb + slot_off(item), s1 = sb + slot_off(item + 1);
    if (TRANS) {
        const int r = (lane & 7) + (lane & 8);
        const int ch = 2 * (w & 3) + (lane >> 4);
        const uint32_t off = (TMA ? (w >> 2) * 8192 + r * 128 : (w >> 2) * 128 + r * 256) + ((ch ^ (lane & 7)) << 4);
#pragma unroll
        for (int kk = 0; kk < 8; kk++) {
            if (TMA && (kk & 3) == 0) mbar_wait(sb + SM_FULL + (item + (kk >> 2)) * 8);
            uint32_t r0, r1, r2, r3;
            ldsm4t(((kk >> 2) ? s1 : s0) + off + (kk & 3) * (TMA ? 2048 : 4096), r0, r1, r2, r3);
            mma16816(c[2 * (kk & 1)],     a[2 * kk], 0u, a[2 * kk + 1], 0u, r0, r1);
            mma16816(c[2 * (kk & 1) + 1], a[2 * kk], 0u, a[2 * kk + 1], 0u, r2, r3);
        }
    } else {
        mbar_wait(sb + SM_FULL + (item + (w >> 2)) * 8);
        const int r = 16 * (w & 3) + (lane & 7) + ((lane >> 4) << 3);
        const uint32_t base = ((w >> 2) ? s1 : s0) + (r & 32) * 128 + r * 128 + ((((lane >> 3) & 1) ^ (lane & 7)) << 4);
#pragma unroll
        for (int kk = 0; kk < 8; kk++) {
            uint32_t r0, r1, r2, r3;
            ldsm4((base ^ ((kk & 3) << 5)) + (kk >> 2) * 4096, r0, r1, r2, r3);
            mma16816(c[2 * (kk & 1)],     a[2 * kk], 0u, a[2 * kk + 1], 0u, r0, r1);
            mma16816(c[2 * (kk & 1) + 1], a[2 * kk], 0u, a[2 * kk + 1], 0u, r2, r3);
        }
    }
    __syncwarp();
    if (lane == 0) {
        mbar_arrive(sb + SM_EMPTY + item * 8);
        mbar_arrive(sb + SM_EMPTY + (item + 1) * 8);
    }
    acc[0][0] = c[0][0] + c[2][0]; acc[0][1] = c[0][1] + c[2][1];
    acc[1][0] = c[1][0] + c[3][0]; acc[1][1] = c[1][1] + c[3][1];
}

__device__ __forceinline__ void publish(float* dst, int w, int lane, const float (&acc)[2][2], uint32_t tag) {
    if (lane < 16)
        asm volatile("st.relaxed.gpu.global.v4.b32 [%0], {%1,%2,%3,%4};" ::"l"(dst + w * 64 + lane * 4),
                     "r"(tagf(acc[0][0], tag)), "r"(tagf(acc[0][1], tag)), "r"(tagf(acc[1][0], tag)), "r"(tagf(acc[1][1], tag)) : "memory");
}

__device__ __forceinline__ void gather(const float* part, uint32_t in, int tid, uint32_t tag) {
    const float* p = part + tid * 2;
    uint2 v0, v1, v2, v3;
    int it = 0;
    while (true) {
        v0 = ld_rlx2(p); v1 = ld_rlx2(p + 512); v2 = ld_rlx2(p + 1024); v3 = ld_rlx2(p + 1536);
        uint32_t bad = ((v0.x ^ tag) | (v0.y ^ tag) | (v1.x ^ tag) | (v1.y ^ tag) |
                        (v2.x ^ tag) | (v2.y ^ tag) | (v3.x ^ tag) | (v3.y ^ tag)) & 0xffu;
        if (__all_sync(0xffffffffu, bad == 0)) break;
        if (++it > SPIN_LIMIT) __trap();
    }
    float x = (untag(v0.x) + untag(v1.x)) + (untag(v2.x) + untag(v3.x));
    float y = (untag(v0.y) + untag(v1.y)) + (untag(v2.y) + untag(v3.y));
    sts32(in + ((tid >> 3) & 3) * 272 + (tid >> 5) * 32 + (tid & 1) * 16 + (tid & 6) * 2, pack_bf16(x, y));
    bar_consumers();
}

constexpr uint32_t EMPTY = 0xffffffffu;
__device__ __forceinline__ void st_rlx(uint32_t* p, uint32_t v) {
    asm volatile("st.relaxed.gpu.global.b32 [%0], %1;" ::"l"(p), "r"(v) : "memory");
}
__device__ __forceinline__ void st_rlx_if(uint64_t p, uint32_t v, bool on) {
    asm volatile("{\n.reg .pred p;\nsetp.ne.u32 p, %2, 0;\n@p st.relaxed.gpu.global.b32 [%0], %1;\n}" ::"l"(p), "r"(v), "r"((uint32_t)on) : "memory");
}
__device__ __forceinline__ void st_if(uint64_t p, uint32_t v, bool on) {
    asm volatile("{\n.reg .pred p;\nsetp.ne.u32 p, %2, 0;\n@p st.global.b32 [%0], %1;\n}" ::"l"(p), "r"(v), "r"((uint32_t)on) : "memory");
}
__device__ __forceinline__ void st_rlx2(uint32_t* p, uint32_t v0, uint32_t v1) {
    asm volatile("st.relaxed.gpu.global.v2.b32 [%0], {%1,%2};" ::"l"(p), "r"(v0), "r"(v1) : "memory");
}
__device__ __forceinline__ void ld_rlx4_if(uint4& v, const void* p, bool need) {
    asm volatile("{\n.reg .pred p;\nsetp.ne.u32 p, %5, 0;\n@p ld.relaxed.gpu.global.v4.b32 {%0,%1,%2,%3}, [%4];\n}"
                 : "+r"(v.x), "+r"(v.y), "+r"(v.z), "+r"(v.w) : "l"(p), "r"((uint32_t)need) : "memory");
}

template <class F>
__device__ __forceinline__ bool refetch(uint4 (&x)[8], F addr) {
    uint32_t m[8], m0 = 0;
#pragma unroll
    for (int i = 0; i < 8; i++) {
        m[i] = max(max(x[i].x, x[i].y), max(x[i].z, x[i].w));
        m0 = max(m0, m[i]);
    }
    if (!__any_sync(0xffffffffu, m0 == EMPTY)) return false;
#pragma unroll
    for (int i = 0; i < 8; i++) ld_rlx4_if(x[i], addr(i), m[i] == EMPTY);
    return true;
}

__device__ __forceinline__ unsigned read_counter(const unsigned* cnt) {
    unsigned v;
    asm volatile("ld.relaxed.gpu.global.u32 %0, [%1];" : "=r"(v) : "l"(cnt) : "memory");
    return v;
}
__device__ __forceinline__ unsigned epoch_of(unsigned cnt) {
    asm volatile("" : "+r"(cnt) :: "memory");
    return cnt + 1;
}
__device__ __forceinline__ uint32_t epoch_tag(unsigned epoch) { return (epoch & 0x7fu) | 0x80u; }

__device__ __forceinline__ void signal_and_wait(unsigned* cnt, unsigned target, int lane) {
    if (lane == 0) asm volatile("red.release.gpu.global.add.u32 [%0], 1;" ::"l"(cnt) : "memory");
    int it = 0;
    while (true) {
        unsigned v;
        asm volatile("ld.acquire.gpu.global.u32 %0, [%1];" : "=r"(v) : "l"(cnt) : "memory");
        if (__all_sync(0xffffffffu, (int)(v - target) >= 0)) break;
        if (++it > SPIN_LIMIT) __trap();
    }
    asm volatile("fence.proxy.async.global;" ::: "memory");
}

__global__ void __cluster_dims__(2, 1, 1) __launch_bounds__(NTHR, 1)
fused_decode_kernel(const uint2 first, const __nv_bfloat16* __restrict__ xA, const __nv_bfloat16* __restrict__ xB,
                    const __nv_bfloat16* __restrict__ wqB, const __nv_bfloat16* __restrict__ wqA,
                    const __nv_bfloat16* __restrict__ Kc, const __nv_bfloat16* __restrict__ Vc,
                    __nv_bfloat16* __restrict__ out, Scratch* gs, const __grid_constant__ Maps maps) {
    extern __shared__ __align__(1024) unsigned char smem_raw[];
    const uint32_t sb = smem_u32(smem_raw);
    const int tid = threadIdx.x, lane = tid & 31;
    const int cta = blockIdx.x, h = cta >> 2, j = cta & 3;
    const size_t kv_off = (size_t)blockIdx.x * 4096 * 128;
    asm volatile("{\n.reg .b32 l;\n.reg .b64 a;\nmad.lo.u32 l, %2, 32, %0;\nmov.b64 a, {l, %1};\nprefetch.global.L2 [a];\n}"
                 ::"r"(first.x + blockIdx.x * (NTHR * 32)), "r"(first.y), "r"(threadIdx.x) : "memory");
    const uint32_t trow = threadIdx.x >> 4;
    const uint32_t tile_src = trow * (8192 - 256) + (threadIdx.x * 16 + ((blockIdx.x * 0x100040u) & 0x301f00u));
    const uint32_t tile_dst = sb + ((threadIdx.x ^ (trow & 7)) << 4);
    auto lsu_piece = [&](int k) {
#pragma unroll
        for (int q = 2 * k; q < 2 * k + 2; q++)
            asm volatile("cp.async.cg.shared.global [%0], [%1], 16;" ::"r"(tile_dst + q * 4096),
                         "l"(reinterpret_cast<const char*>((k < 4 ? wqB : wqA) + (q & 7) * 16 * 4096) + tile_src) : "memory");
        if ((k & 3) == 3) asm volatile("cp.async.commit_group;" ::: "memory");
    };
    if (tid < 256) {
#pragma unroll
        for (int k = 0; k < 4; k++) lsu_piece(k);
    }
    const uint32_t tz = timer_ns() - LEAD;
    unsigned cnt1;
    if (tid < 256) cnt1 = read_counter(gs->cnt[blockIdx.x]);
    uint4 xv;
    if (tid < 128) {
        const __nv_bfloat16* x = (tid < 64 ? xB : xA) + ((tid >> 4) & 3) * 512 + j * 128 + (tid & 15) * 8;
        xv = __ldg(reinterpret_cast<const uint4*>(x));
    }
    const int w = __shfl_sync(0xffffffffu, tid >> 5, 0);
    const int pr = cta >> 1;
    const int slice = pr < 4 ? pr : pr < 36 ? 4 + ((pr - 4) & 7) * 4 + ((pr - 4) >> 3) : 36 + (pr - 36) % 7 * 4 + (pr - 36) / 7;

    if (w >= 8) {
        if (lane == 0) {
            const uint32_t full = sb + SM_FULL + (IT_WUK + (w & 3) * 14) * 8, empty = sb + SM_EMPTY + (w & 3) * 13 * 8,
                           last = sb + SM_LAST + (w & 3) * 32;
#pragma unroll
            for (int i = 0; i < 14; i++) mbar_init(full + i * 8, 1);
#pragma unroll
            for (int i = 0; i < 13; i++) mbar_init(empty + i * 8, 8);
#pragma unroll
            for (int i = 0; i < 4; i++) mbar_init(last + i * 8, 1);
#pragma unroll
            for (int i = 0; i < 14; i++) {
                const int b = IT_WUK + 42 + i;
                mbar_expect_tx(full + i * 8, (w == 10 && b - 14 == IT_OP) ? SLOT + 1024 : (w == 11 && b == BAR_LAT) ? 4096 : SLOT);
            }
#pragma unroll
            for (int i = 0; i < 4; i++) mbar_expect_tx(last + i * 8, i == 1 && w == 8 && !(j & 1) ? 2048 + 256 : 2048);
            asm volatile("fence.mbarrier_init.release.cluster;" ::: "memory");
            if (w == 10) sts64(sb + SM_PACE, tz, PACE * 16);
        }
        asm volatile("bar.sync 2, 128;" ::: "memory");
        asm volatile("bar.arrive 4, 384;" ::: "memory");
    }
    if (w == 10) {
        if (lane == 0) {
            int slope = 0;
#pragma unroll
            for (int k = 0; k < NWIN; k++) {
                const int c = win_pos(k);
                uint32_t acc = 0;
#pragma unroll
                for (int p = c; p < c + 4; p++) {
                    mbar_wait(sb + SM_FULL + (p < IT_Q ? p : p < IT_OP - 2 ? p + 2 : p + 4) * 8);
                    acc += timer_ns() - tz - p * PACE - ((p * slope) >> 4);
                }
                if (k == 0) mbar_wait(sb + SM_FULL + IT_Q * 8);
                asm volatile("red.relaxed.gpu.global.add.u64 [%0], %1;" ::"l"(&gs->late[k]),
                             "l"((uint64_t)tz << 32 | (1u << 24) + min(acc >> 2, 65535u)) : "memory");
                uint2 v;
                int it = 0;
                do { v = ld_rlx2(&gs->late[k]); } while ((v.x >> 24) != NCTA && ++it < 1000);
                if (it == 1000) break;
                const int late = (v.x & 0xffffffu) / NCTA;
                slope = max(-320, min(320, slope + (late - win_late(k)) * (GAIN * 2) / (2 * c + 3)));
                sts64(sb + SM_PACE, k < NWIN - 1 ? tz : tz + (int)(v.y - tz * NCTA) / NCTA, PACE * 16 + slope);
            }
        }
        return;
    }
    if (w >= 8) {
        auto wait_due = [&](uint32_t p, uint32_t shift) {
            uint32_t a, b;
            do {
                asm volatile("ld.volatile.shared.v2.b32 {%0,%1}, [%2];" : "=r"(a), "=r"(b) : "r"(sb + SM_PACE) : "memory");
            } while (__all_sync(0xffffffffu, (int)(timer_ns() - (a + ((p * b) >> 4) + shift)) < 0));
        };
        if (w != 9) {
            const int half = w & 1;
            const uint64_t pol = evict_first();
            const uint32_t rows = (slice < 32 ? ROWS_A : ROWS_B) >> ((j & 1) * 32 + half * 4);
            int slot = IT_WUK, tail = IT_WUK - INFLIGHT;
            uint32_t np = IT_WUK, shift = half ? PACE / 4 : -(PACE / 4);
#pragma unroll 1
            for (int i = IT_WUK; i < NITEM; i++) {
                const uint32_t dst = sb + slot * SLOT + half * (SLOT / 2), bar = sb + SM_FULL + i * 8;
                if (++slot == NSLOT) slot = 0;
                if ((i & ~1) == IT_Q || (i & ~1) == IT_OP) continue;
                const bool ckv = i >= IT_C && i < IT_K1, wo = i >= IT_WO;
                const bool tiled = ckv || i < IT_K0 || i >= IT_WUV;
                const CUtensorMap* tm = &maps.wuk + (i < IT_K0 ? 0 : ckv ? 4 : wo ? 2 + (slice >> 5) : 1);
                const int c0 = wo ? (slice & 31) * 16 : i >= IT_WUV ? cta * 32 : 0;
                const int c1 = i < IT_K0 ? j * 128 + (i & 1) * 64 + half * 32 : ckv ? cta * 128 + (i - IT_C) * 16 + half * 8 : wo ? 0 : half * 128;
                const int c2 = i < IT_K0 ? h * 2 : ckv ? 0 : wo ? rows >> (i - IT_WO) * 8 & 15 : i & 1;
                const int c = i < IT_Q ? i - IT_K0 : i < IT_V0 ? i - IT_K1 + 8 : i < IT_OP ? i - IT_V0 : i - IT_V1 + 8;
                const __nv_bfloat16* src = (i < IT_V0 ? Kc : Vc) + kv_off + (size_t)((c ^ (j & 1) * 7) * 2 + half) * (SLOT / 4);
                if (i >= NSLOT) mbar_wait(sb + SM_EMPTY + (i - NSLOT) * 8);
                if (tail >= IT_WUK && !wo) mbar_wait(sb + SM_FULL + tail * 8);
                ++tail;
                if (tail == IT_Q || tail == IT_OP) tail += 2;
                if (wo) {
                    const int n = (i - IT_WO) * 2 + half;
                    np = IT_WO - 4;
                    shift = TAPER + ((j & 1) ? OS0 + n * OS1 : n < 4 ? OF0 + n * OF1 : OF2 + (n - 4) * OF3);
                }
                wait_due(np, shift);
                ++np;
                if (i == IT_WUV - 1) shift += TAPER;
                if (i >= NITEM - 2) {
#pragma unroll
                    for (int q = 0; q < 4; q++)
                        tma3d(dst + q * 2048, tm + 3, c0, q * 64, c2, sb + SM_LAST + half * 64 + q * 16 + (i & 1) * 8, pol);
                }
                else if (tiled) tma3d(dst, tm, c0, c1, c2, bar, pol);
                else bulk_load(dst, src, SLOT / 2, bar, pol);
            }
        } else {
            if (lane < sizeof(Maps) / 128) asm volatile("prefetch.tensormap [%0];" ::"l"(&maps.wuk + lane) : "memory");
            cnt1 = read_counter(gs->cnt[blockIdx.x]);
            asm volatile("bar.sync 3, 288;" ::: "memory");
            const unsigned epoch = epoch_of(cnt1);
            if (lane == 0) st_rlx(gs->cnt[cta], epoch);
            signal_and_wait(&gs->cnt[0][1], epoch * NCTA, lane);
            if (lane == 0) {
                const uint4* q = gs->q[cta >> 5];
                bulk_load_nohint(sb + slot_off(IT_Q), q, SLOT, sb + SM_FULL + IT_Q * 8);
                bulk_load_nohint(sb + slot_off(IT_Q + 1), q + 1024, SLOT, sb + SM_FULL + (IT_Q + 1) * 8);
            }
            asm volatile("bar.sync 3, 288;" ::: "memory");
            signal_and_wait(&gs->cnt[0][2], epoch * NCTA, lane);
            mbar_wait(sb + SM_EMPTY + (IT_OP - NSLOT) * 8);
            mbar_wait(sb + SM_EMPTY + (IT_OP + 1 - NSLOT) * 8);
            if (lane == 0) {
                const uint4* op = gs->op[cta];
                bulk_load_nohint(sb + SM_MX, gs->stat[h], 1024, sb + SM_FULL + IT_OP * 8);
                uint32_t t1 = timer_ns();
#pragma unroll 1
                for (int i = 0; i < 8; i++) {
                    while ((int)(timer_ns() - t1) < 0) {}
                    t1 += OPGAP;
                    bulk_load_nohint(sb + slot_off(IT_OP) + i * 4096, op + i * 256, 4096, sb + SM_FULL + (IT_OP + i / 4) * 8);
                }
            }
            mbar_wait(sb + SM_FULL + (IT_V1 + 4) * 8);
            if (lane == 0) bulk_load_nohint(sb + SM_LAT, gs->lat[h], 4096, sb + SM_FULL + BAR_LAT * 8);
            mbar_wait(sb + SM_EMPTY + (IT_X - NSLOT) * 8);
            mbar_wait(sb + SM_FULL + (IT_WUV + 1) * 8);
            wait_due(IT_WO - 4, TAPER + ((j & 1) ? XS : XF));
            if (lane == 0) bulk_load_nohint(sb + slot_off(IT_X), gs->x[slice >> 5][(j & 1) * 16], SLOT, sb + SM_FULL + IT_X * 8);
        }
        return;
    }

    const int g = lane >> 2, t = lane & 3;
    const uint32_t in0 = sb + SM_IN0, in1 = sb + SM_IN1;
    const int ba = cta >> 5, ha = cta & 31;
    auto xpos = [](uint64_t piece, int head) { return (int)(piece >> (head >> 1) * 4 & 15) * 2 + (head & 1); };
    uint32_t* const ctx_dst = &gs->x[1][xpos(PIECE_B, h)][(j * 4 + (w & 3)) * 16 + ((g ^ (w & 2)) & 3) * 4 + ((t - w) & 3)];
    uint32_t* const o_dst = &gs->x[0][xpos(PIECE_A, ha)][ba * 64 + ((tid & 60) ^ ((ba & 1) * 16)) + ((t - g) & 3)];
    uint32_t* const lat_dst = &gs->lat[h][g & 3][j * 64 + ((w >> 1) ^ (g & 1)) * 16 + t * 4 + ((w * 2 ^ t) & 2)];
    {
#pragma unroll
        for (int k = 4; k < 8; k++) {
            while (__all_sync(0xffffffffu, (int)(timer_ns() - (tz + (2 * k - 1) * (PACE / 4))) < 0)) {}
            lsu_piece(k);
        }
        if (lane < 16) st_rlx2(lat_dst, EMPTY, EMPTY);
        if (lane >= 16 && w < 4) st_rlx(ctx_dst, EMPTY);
        if (w >= 6) st_rlx(o_dst, EMPTY);
        if (cta == 0 && w == 5) st_rlx((uint32_t*)gs->late + lane, 0u);
        if (tid < 128) sts128((tid < 64 ? in0 : in1) + ((tid >> 4) & 3) * 272 + (tid & 15) * 16, xv);
        asm volatile("cp.async.wait_group 1;" ::: "memory");
    }
    asm volatile("bar.sync 4, 384;" ::: "memory");
    const uint32_t tag = epoch_tag(epoch_of(cnt1));

    float acc[2][2];
    tile_mma<true, false>(sb, IT_WQB, in0, w, lane, acc);
    publish(gs->part[0][cta], w, lane, acc, tag);
    asm volatile("cp.async.wait_group 0;" ::: "memory");
    bar_consumers();
    tile_mma<true, false>(sb, IT_WQA, in1, w, lane, acc);
    publish(gs->part[1][cta], w, lane, acc, tag);
    bar_consumers();

    const float SC = 0.08838834764831845f * 1.4426950408889634f;
    gather(gs->part[0][h * 4], in0, tid, tag);
    tile_mma<false>(sb, IT_WUK, in0, w, lane, acc);
    if (lane < 16) {
        uint32_t* q = reinterpret_cast<uint32_t*>(gs->q[g]) + (2 * j + (w >> 2)) * 1024 + h * 32 + t;
        const int ch = 2 * (w & 3);
        q[((ch) ^ (h & 7)) * 4]     = pack_bf16(acc[0][0] * SC, acc[0][1] * SC);
        q[((ch + 1) ^ (h & 7)) * 4] = pack_bf16(acc[1][0] * SC, acc[1][1] * SC);
    }
    __syncwarp();
    asm volatile("bar.arrive 3, 288;" ::: "memory");
    gather(gs->part[1][ha * 4], in1, tid, tag);

    uint32_t qf[16];
#pragma unroll
    for (int c = 0; c < 8; c++) {
        qf[2 * c]     = lds32(in1 + ba * 272 + ((c ^ g) << 4) + t * 4);
        qf[2 * c + 1] = lds32(in1 + ba * 272 + 128 + ((c ^ g) << 4) + t * 4);
    }
    const uint32_t sc_w = sb + SM_SC + w * 512;
    auto k_item = [&](int item, uint32_t sc) {
        mbar_wait(sb + SM_FULL + item * 8);
        const uint32_t base = sb + slot_off(item) + ((lane & 7) + (lane & 8)) * 256 + ((lane >> 4) << 7);
        float s[4][4];
#pragma unroll
        for (int T = 0; T < 4; T++) { s[T][0] = s[T][1] = s[T][2] = s[T][3] = 0.f; }
#pragma unroll
        for (int c = 0; c < 8; c++) {
            const uint32_t a = base + ((c ^ (lane & 7)) << 4);
#pragma unroll
            for (int T = 0; T < 4; T++) {
                uint32_t r0, r1, r2, r3;
                ldsm4(a + T * 4096, r0, r1, r2, r3);
                mma16816(s[T], r0, r1, r2, r3, qf[2 * c], qf[2 * c + 1]);
            }
        }
        __syncwarp();
        if (lane == 0) mbar_arrive8(sb + SM_EMPTY + item * 8);
        if (t == (g >> 1)) {
#pragma unroll
            for (int T = 0; T < 4; T++) {
                stsf(sc + (16 * T + g) * 4,     (g & 1) ? s[T][1] : s[T][0]);
                stsf(sc + (16 * T + g + 8) * 4, (g & 1) ? s[T][3] : s[T][2]);
            }
        }
    };
    k_item(IT_K0 + w, sc_w);

    {
        float s[2][2][4];
#pragma unroll
        for (int i = 0; i < 16; i++) (&s[0][0][0])[i] = 0.f;
        mbar_wait(sb + SM_FULL + IT_Q * 8);
        mbar_wait(sb + SM_FULL + (IT_Q + 1) * 8);
        mbar_wait(sb + SM_FULL + (IT_C + w) * 8);
        const uint32_t cb0 = sb + slot_off(IT_C + w) + (lane & 7) * 128 + (lane >> 4) * 8192;
        const uint32_t cx = (((lane >> 3) & 1) ^ (lane & 7)) << 4;
        const uint32_t qr = ((lane & 7) + (lane & 8)) * 128;
        const uint32_t qx = ((lane >> 4) ^ (lane & 7)) << 4;
#pragma unroll
        for (int cb = 0; cb < 8; cb++) {
            const uint32_t qb = sb + slot_off(IT_Q + (cb >> 2)) + (cb & 3) * 4096 + qr;
#pragma unroll
            for (int k4 = 0; k4 < 4; k4++) {
                uint32_t b0, b1, b2, b3, a0, a1, a2, a3;
                ldsm4(cb0 + cb * 1024 + (cx ^ (k4 << 5)), b0, b1, b2, b3);
                ldsm4(qb + (qx ^ (k4 << 5)), a0, a1, a2, a3);
                mma16816(s[0][0], a0, a1, a2, a3, b0, b1);
                mma16816(s[0][1], a0, a1, a2, a3, b2, b3);
                ldsm4(qb + 2048 + (qx ^ (k4 << 5)), a0, a1, a2, a3);
                mma16816(s[1][0], a0, a1, a2, a3, b0, b1);
                mma16816(s[1][1], a0, a1, a2, a3, b2, b3);
            }
        }
        __syncwarp();
        if (lane == 0) { mbar_arrive(sb + SM_EMPTY + IT_Q * 8); mbar_arrive(sb + SM_EMPTY + (IT_Q + 1) * 8); }
#pragma unroll
        for (int r = 0; r < 4; r++) {
            const int mt = r >> 1, hi = (r & 1) * 2;
            float m = fmaxf(fmaxf(s[mt][0][hi], s[mt][0][hi + 1]), fmaxf(s[mt][1][hi], s[mt][1][hi + 1]));
            m = fmaxf(m, __shfl_xor_sync(0xffffffffu, m, 1));
            m = fmaxf(m, __shfl_xor_sync(0xffffffffu, m, 2));
            if (t == 0) stsf(sb + SM_MX + (8 * r + g) * 32 + w * 4, m);
        }
        bar_consumers();
        uint32_t pf[2][4];
#pragma unroll
        for (int r = 0; r < 4; r++) {
            const int mt = r >> 1, hi = r & 1;
            const float4 m0 = ldsf4(sb + SM_MX + (8 * r + g) * 32), m1 = ldsf4(sb + SM_MX + (8 * r + g) * 32 + 16);
            const float m = fmaxf(fmaxf(fmaxf(m0.x, m0.y), fmaxf(m0.z, m0.w)), fmaxf(fmaxf(m1.x, m1.y), fmaxf(m1.z, m1.w)));
            const uint32_t p0 = pack_bf16(ex2(s[mt][0][2 * hi] - m), ex2(s[mt][0][2 * hi + 1] - m));
            const uint32_t p1 = pack_bf16(ex2(s[mt][1][2 * hi] - m), ex2(s[mt][1][2 * hi + 1] - m));
            pf[mt][hi] = p0; pf[mt][2 + hi] = p1;
            float l = (bf_lo(p0) + bf_hi(p0)) + (bf_lo(p1) + bf_hi(p1));
            l += __shfl_xor_sync(0xffffffffu, l, 1);
            l += __shfl_xor_sync(0xffffffffu, l, 2);
            if (t == 0) stsf(sb + SM_SUM + (8 * r + g) * 32 + w * 4, l);
        }
        sts128(sb + SM_PF + (w * 2 + 0) * 512 + lane * 16, make_uint4(pf[0][0], pf[0][1], pf[0][2], pf[0][3]));
        sts128(sb + SM_PF + (w * 2 + 1) * 512 + lane * 16, make_uint4(pf[1][0], pf[1][1], pf[1][2], pf[1][3]));
        bar_consumers();
        if (w == 0) {
            const float4 m0 = ldsf4(sb + SM_MX + lane * 32), m1 = ldsf4(sb + SM_MX + lane * 32 + 16);
            const float4 l0 = ldsf4(sb + SM_SUM + lane * 32), l1 = ldsf4(sb + SM_SUM + lane * 32 + 16);
            const float m = fmaxf(fmaxf(fmaxf(m0.x, m0.y), fmaxf(m0.z, m0.w)), fmaxf(fmaxf(m1.x, m1.y), fmaxf(m1.z, m1.w)));
            const float l = ((l0.x + l0.y) + (l0.z + l0.w)) + ((l1.x + l1.y) + (l1.z + l1.w));
            gs->stat[lane][cta] = make_float2(m, l);
        }
        float o[2][8][4];
#pragma unroll
        for (int i = 0; i < 64; i++) (&o[0][0][0])[i] = 0.f;
        const uint32_t vr = w * 1024 + (lane & 7) * 128 + (lane & 8) * 1024;
        const uint32_t vx = ((lane >> 4) ^ (lane & 7)) << 4;
#pragma unroll
        for (int ks = 0; ks < 8; ks++) {
            const uint4 p0 = lds128(sb + SM_PF + (ks * 2 + 0) * 512 + lane * 16);
            const uint4 p1 = lds128(sb + SM_PF + (ks * 2 + 1) * 512 + lane * 16);
            const uint32_t vb = sb + slot_off(IT_C + ks) + vr;
#pragma unroll
            for (int n2 = 0; n2 < 4; n2++) {
                uint32_t b0, b1, b2, b3;
                ldsm4t(vb + (vx ^ (n2 << 5)), b0, b1, b2, b3);
                mma16816(o[0][2 * n2],     p0.x, p0.y, p0.z, p0.w, b0, b1);
                mma16816(o[0][2 * n2 + 1], p0.x, p0.y, p0.z, p0.w, b2, b3);
                mma16816(o[1][2 * n2],     p1.x, p1.y, p1.z, p1.w, b0, b1);
                mma16816(o[1][2 * n2 + 1], p1.x, p1.y, p1.z, p1.w, b2, b3);
            }
            __syncwarp();
            if (lane == 0) mbar_arrive(sb + SM_EMPTY + (IT_C + ks) * 8);
        }
        mbar_wait(sb + SM_FULL + (IT_K1 + 1 + (w * 3 >> 2)) * 8);
#pragma unroll
        for (int r = 0; r < 4; r++) {
            const int mt = r >> 1, hi = (r & 1) * 2;
            uint4* dst = gs->op[(8 * r + g) * 4 + (w >> 1)] + (cta >> 6) * 1024 + (w & 1) * 512 + (cta & 63) * 8;
#pragma unroll
            for (int u = 0; u < 2; u++) {
                uint4 v;
                v.x = pack_bf16(o[mt][4 * u][hi],     o[mt][4 * u][hi + 1]);
                v.y = pack_bf16(o[mt][4 * u + 1][hi], o[mt][4 * u + 1][hi + 1]);
                v.z = pack_bf16(o[mt][4 * u + 2][hi], o[mt][4 * u + 2][hi + 1]);
                v.w = pack_bf16(o[mt][4 * u + 3][hi], o[mt][4 * u + 3][hi + 1]);
                dst[(t + 4 * u) ^ (cta & 7)] = v;
            }
        }
        asm volatile("bar.arrive 3, 288;" ::: "memory");
    }

    k_item(IT_K1 + w, sc_w + 256);
    __syncwarp();
    {
        const float4 s = ldsf4(sc_w + lane * 16);
        float m = fmaxf(fmaxf(s.x, s.y), fmaxf(s.z, s.w));
#pragma unroll
        for (int d = 1; d < 32; d <<= 1) m = fmaxf(m, __shfl_xor_sync(0xffffffffu, m, d));
        if (lane == 0) stsf(sb + SM_ML + w * 4, m);
        bar_consumers();
        const float4 m0 = ldsf4(sb + SM_ML), m1 = ldsf4(sb + SM_ML + 16);
        m = fmaxf(fmaxf(fmaxf(m0.x, m0.y), fmaxf(m0.z, m0.w)), fmaxf(fmaxf(m1.x, m1.y), fmaxf(m1.z, m1.w))) * SC;
        const uint32_t p0 = pack_bf16(ex2(fmaf(s.x, SC, -m)), ex2(fmaf(s.y, SC, -m)));
        const uint32_t p1 = pack_bf16(ex2(fmaf(s.z, SC, -m)), ex2(fmaf(s.w, SC, -m)));
        float l = (bf_lo(p0) + bf_hi(p0)) + (bf_lo(p1) + bf_hi(p1));
#pragma unroll
        for (int d = 1; d < 32; d <<= 1) l += __shfl_xor_sync(0xffffffffu, l, d);
        if (lane == 0) stsf(sb + SM_ML + 32 + w * 4, l);
        sts64(sb + SM_PA + w * 256 + lane * 8, p0, p1);
        __syncwarp();
    }

    float oa[4][4];
#pragma unroll
    for (int i = 0; i < 16; i++) (&oa[0][0])[i] = 0.f;
    auto v_item = [&](int item, uint32_t pa) {
        uint32_t p[8];
#pragma unroll
        for (int i = 0; i < 8; i++) p[i] = lds32(pa + i * 16 + t * 4);
        mbar_wait(sb + SM_FULL + item * 8);
        const uint32_t base = sb + slot_off(item) + ((lane & 7) + ((lane >> 4) << 3)) * 256 + ((lane & 8) << 4);
#pragma unroll
        for (int c = 0; c < 8; c++) {
            const uint32_t a = base + ((c ^ (lane & 7)) << 4);
            const uint32_t mask = ((c == (g ^ (2 * t))) ? 0x0000ffffu : 0u) | ((c == (g ^ (2 * t + 1))) ? 0xffff0000u : 0u);
#pragma unroll
            for (int T = 0; T < 4; T++) {
                uint32_t r0, r1, r2, r3;
                ldsm4t(a + T * 4096, r0, r1, r2, r3);
                mma16816(oa[T], r0, r1, r2, r3, p[2 * T] & mask, p[2 * T + 1] & mask);
            }
        }
        __syncwarp();
        if (lane == 0) mbar_arrive8(sb + SM_EMPTY + item * 8);
    };
    sts64(sb + SM_FIN + tid * 8, EMPTY, EMPTY);
    if (w == 0) sts32(sb + SM_CNT + lane * 4, 0u);
    v_item(IT_V0 + w, sb + SM_PA + w * 256);

    mbar_wait(sb + SM_FULL + IT_OP * 8);
    if (w < 4) {
        const float2 st = ldsf2(sb + SM_MX + tid * 8);
        float m = st.x;
#pragma unroll
        for (int d = 1; d < 32; d <<= 1) m = fmaxf(m, __shfl_xor_sync(0xffffffffu, m, d));
        const uint32_t wb = pack_bf16(ex2(st.x - m), 0.f);
        float l = bf_lo(wb) * st.y;
#pragma unroll
        for (int d = 1; d < 32; d <<= 1) l += __shfl_xor_sync(0xffffffffu, l, d);
#pragma unroll
        for (int bb = 0; bb < 4; bb++) sts16(in0 + bb * 272 + tid * 2, bb == w ? (uint16_t)wb : (uint16_t)0);
        if (lane == 0) stsf(sb + SM_ML + 64 + w * 4, 1.f / l);
    }
    bar_consumers();
    tile_mma<true>(sb, IT_OP, in0, w, lane, acc);
    if (lane < 16) {
        const float inv = ldsf(sb + SM_ML + 64 + g * 4);
        const uint32_t v0 = pack_bf16(acc[0][0] * inv, acc[0][1] * inv), v1 = pack_bf16(acc[1][0] * inv, acc[1][1] * inv);
        st_rlx2(lat_dst, (t & 1) ? v1 : v0, (t & 1) ? v0 : v1);
    }

    {
        const float4 l0 = ldsf4(sb + SM_ML + 32), l1 = ldsf4(sb + SM_ML + 48);
        const float inv = 1.f / (((l0.x + l0.y) + (l0.z + l0.w)) + ((l1.x + l1.y) + (l1.z + l1.w)));
        v_item(IT_V1 + w, sb + SM_PA + w * 256 + 128);
        const uint32_t so = sb + SM_PF + w * 512 + (16 * t + g) * 4;
        stsf(so,       (oa[0][0] + oa[1][0]) + (oa[2][0] + oa[3][0]));
        stsf(so + 32,  (oa[0][1] + oa[1][1]) + (oa[2][1] + oa[3][1]));
        stsf(so + 256, (oa[0][2] + oa[1][2]) + (oa[2][2] + oa[3][2]));
        stsf(so + 288, (oa[0][3] + oa[1][3]) + (oa[2][3] + oa[3][3]));
        if (w < 6) {
            asm volatile("bar.arrive 1, 256;" ::: "memory");
        } else {
            bar_consumers();
            float x = 0.f, y = 0.f;
#pragma unroll
            for (int i = 0; i < 8; i++) {
                const float2 v = ldsf2(sb + SM_PF + i * 512 + (tid & 63) * 8);
                x += v.x; y += v.y;
            }
            st_rlx(o_dst, pack_bf16(x * inv, y * inv));
        }
    }

    if (w < 4) {
        const uint32_t lo = (g & 3) * 1024 + (g >> 2) * 512 + (g & 1) * 64 + t * 16;
        const int wd = ((lane >> 2 & 2) + (lane >> 4)) ^ (lane >> 1 & 3);
        const uint32_t base = sb + ((lane & 6) * 4 + wd * 2 + (lane & 1)) * 64 + (((w ^ wd) & 3) << 4);
        const uint64_t dst = __shfl_sync(0xffffffffu, (unsigned long long)ctx_dst, lane);
        mbar_wait(sb + SM_FULL + BAR_LAT * 8);
        uint4 a[8];
#pragma unroll
        for (int i = 0; i < 8; i++) a[i] = lds128(sb + SM_LAT + (lo ^ (i * 64)));
        int it = 0;
        while (refetch(a, [&](int i) { return (const char*)gs->lat[h] + (lo ^ (i * 64)); }))
            if (++it > SPIN_LIMIT) __trap();
        float v0 = 0.f, v1 = 0.f;
#pragma unroll
        for (int i = 0; i < 2; i++) {
            float c[4][4];
#pragma unroll
            for (int k = 0; k < 16; k++) (&c[0][0])[k] = 0.f;
            c[0][0] = v0; c[0][1] = v1;
            mbar_wait(sb + SM_FULL + (IT_WUV + i) * 8);
#pragma unroll
            for (int kk = 0; kk < 8; kk++) {
                uint32_t r0, r1, r2, r3;
                ldsm4t(base + slot_off(IT_WUV + i) + kk * 2048, r0, r1, r2, r3);
                mma16816(c[2 * (kk & 1)],     a[kk].x, a[kk].y, a[kk].z, a[kk].w, r0, r1);
                mma16816(c[2 * (kk & 1) + 1], a[kk].x, a[kk].y, a[kk].z, a[kk].w, r2, r3);
            }
            v0 = (c[0][0] + c[1][2]) + (c[2][0] + c[3][2]);
            v1 = (c[0][1] + c[1][3]) + (c[2][1] + c[3][3]);
            if (i == 0) { v0 = __shfl_xor_sync(0xffffffffu, v0, 16); v1 = __shfl_xor_sync(0xffffffffu, v1, 16); }
        }
        st_rlx_if(dst, pack_bf16(v0, v1), lane >= 16);
    }

    {
        const bool isB = slice >= 32;
        const int r = j & 1;
        const uint32_t cs = isB ? 256 : 64;
        const uint32_t xl = (isB ? t * 64 + (((g >> 1) ^ (t & 2)) << 4) : (g >> 1) * 256 + ((g & 2) * 2 + t) * 16) + (w >> 1) * 1024 + (w & 1) * 2 * cs;
        auto xoff = [&](int i) { return (i >> 1) * 4096 + (xl ^ ((i & 1) * cs)); };
        const char* src = (const char*)gs->x[slice >> 5][r * 16];
        uint32_t off[2];
#pragma unroll
        for (int u = 0; u < 2; u++) {
            const int tt = (lane & 7) >> 1, row = 8 * tt + 2 * ((2 * u + (lane >> 4) + tt) & 3) + (lane & 1);
            off[u] = sb + w * 2048 + row * 32 + ((((lane >> 3) ^ (row >> 2)) & 1) << 4);
        }
        uint32_t fin[2], rcv[2];
#pragma unroll
        for (int e = 0; e < 2; e++) {
            const uint32_t o = t * 16 + (e ^ (t >> 1)) * 8 + g;
            fin[e] = __shfl_sync(0xffffffffu, sb + SM_FIN + (w >> 1) * 512 + o * 8 + ((w ^ t) & 1) * 4, lane);
            rcv[e] = __shfl_sync(0xffffffffu, sb + SM_RCV + o * 4, lane);
        }
        const uint32_t cnt = __shfl_sync(0xffffffffu, sb + SM_CNT + lane * 4, lane), sum = __shfl_sync(0xffffffffu, sb + SM_FIN + lane * 16, lane);
        const uint32_t inc = __shfl_sync(0xffffffffu, lane, 1 + r), last = __shfl_sync(0xffffffffu, lane, 7 + 7 * r);
        const uint32_t snd = __shfl_sync(0xffffffffu, map_cta(sb + SM_RCV + lane * 8, 0), lane),
                       sbar = __shfl_sync(0xffffffffu, map_cta(sb + SM_LAST + 8 + (lane & 16), 0), lane & 15);
        const uint64_t dst = __shfl_sync(0xffffffffu, (unsigned long long)(out + (lane >> 3) * 1024 + slice * 16 + ((lane ^ (lane >> 2 & 4)) & 7) * 2), lane);
        uint32_t a[2][4][4];
        uint4 x[8];
        float c[4][4];
        auto load_w = [&](int i) {
            mbar_wait(i < 2 ? sb + SM_FULL + (IT_WO + i) * 8 : sb + SM_LAST + w * 16 + (i & 1) * 8);
#pragma unroll
            for (int q = 0; q < 4; q++)
                ldsm4t(slot_off(IT_WO + i) + off[q & 1] + (q >> 1) * 1024, a[i & 1][q][0], a[i & 1][q][1], a[i & 1][q][2], a[i & 1][q][3]);
        };
        auto mma_w = [&](int i) {
#pragma unroll
            for (int q = 0; q < 4; q++) {
                const uint4& b = x[2 * i + (q >> 1)];
                if (i == 0) c[q][0] = c[q][1] = c[q][2] = c[q][3] = 0.f;
                mma16816(c[q], a[i & 1][q][0], a[i & 1][q][1], a[i & 1][q][2], a[i & 1][q][3], (q & 1) ? b.z : b.x, (q & 1) ? b.w : b.y);
            }
        };
        load_w(0); load_w(1);
        mbar_wait(sb + SM_FULL + IT_X * 8);
#pragma unroll
        for (int i = 0; i < 8; i++) x[i] = lds128(sb + slot_off(IT_X) + xoff(i));
        int it = 0;
        while (true) {
            mma_w(0); mma_w(1);
            if (!refetch(x, [&](int i) { return src + xoff(i); })) break;
            if (++it > SPIN_LIMIT) __trap();
        }
        load_w(2);
        mma_w(2);
        load_w(3);
        uint32_t rank;
        const float pr[2] = {ldsf_if(rcv[0], w == 0 && r == 0), ldsf_if(rcv[1], w == 0 && r == 0)};
        mma_w(3);
#pragma unroll
        for (int e = 0; e < 2; e++) stv(fin[e], (((c[0][2 * e] + pr[e]) + c[1][2 * e]) + c[2][2 * e]) + c[3][2 * e]);
        float4 p[4];
        float s0, s1;
        auto add_up = [&]() {
#pragma unroll
            for (int k = 0; k < 4; k++) p[k] = ldv4(sum + k * 512);
            const float a0 = ((p[0].x + p[0].y) + (p[1].x + p[1].y)) + (p[2].x + p[2].y), b0 = p[3].x + p[3].y;
            const float a1 = ((p[0].z + p[0].w) + (p[1].z + p[1].w)) + (p[2].z + p[2].w), b1 = p[3].z + p[3].w;
            s0 = a0 + b0; s1 = a1 + b1;
            uint32_t nan;
            asm("{\n.reg .pred p;\nsetp.ne.u32 p, %5, 0;\nsetp.nan.or.f32 p, %1, %2, p;\nsetp.nan.or.f32 p, %3, %4, p;\nselp.u32 %0, 1, 0, p;\n}"
                : "=r"(nan) : "f"(a0), "f"(a1), "f"(b0), "f"(b1), "r"(r));
            return nan;
        };
        asm volatile("atom.relaxed.cta.shared.add.u32 %0, [%1], %2;" : "=r"(rank) : "r"(cnt), "r"(inc) : "memory");
        const uint32_t redo = add_up();
        st_if(dst, pack_bf16(s0, s1), rank == 7);
        if (!redo) return;
        const bool num = s0 == s0 && s1 == s1;
        st_async64_if(snd, s0, s1, sbar, rank == 14 && num);
        if (rank != last || num) return;
        auto mx = [](float4 q) { return max(max(__float_as_uint(q.x), __float_as_uint(q.y)), max(__float_as_uint(q.z), __float_as_uint(q.w))); };
        for (it = 0; max(max(mx(p[0]), mx(p[1])), max(mx(p[2]), mx(p[3]))) == EMPTY; it++) {
            add_up();
            if (it > SPIN_LIMIT) __trap();
        }
        if (r) st_async64_if(snd, s0, s1, sbar, true);
        else st_if(dst, pack_bf16(s0, s1), true);
    }
}

typedef CUresult (*EncodeTiledFn)(CUtensorMap*, CUtensorMapDataType, cuuint32_t, void*, const cuuint64_t*,
                                  const cuuint64_t*, const cuuint32_t*, const cuuint32_t*, CUtensorMapInterleave,
                                  CUtensorMapSwizzle, CUtensorMapL2promotion, CUtensorMapFloatOOBfill);

void encode_map(EncodeTiledFn enc, CUtensorMap* tm, const void* p, cuuint64_t cols, cuuint64_t rows,
                cuuint32_t brows, cuuint32_t bblk) {
    cuuint64_t dims[3] = {64, rows, cols / 64};
    cuuint64_t strides[2] = {cols * 2, 128};
    cuuint32_t box[3] = {64, brows, bblk};
    cuuint32_t es[3] = {1, 1, 1};
    enc(tm, CU_TENSOR_MAP_DATA_TYPE_BFLOAT16, 3, const_cast<void*>(p), dims, strides, box, es,
        CU_TENSOR_MAP_INTERLEAVE_NONE, CU_TENSOR_MAP_SWIZZLE_128B, CU_TENSOR_MAP_L2_PROMOTION_L2_256B,
        CU_TENSOR_MAP_FLOAT_OOB_FILL_NONE);
}

void encode_slice_map(EncodeTiledFn enc, CUtensorMap* tm, const void* p, cuuint64_t cols, cuuint64_t rows,
                      cuuint32_t bcols, cuuint32_t brows) {
    cuuint64_t dims[3] = {cols, 256, rows / 256};
    cuuint64_t strides[2] = {cols * 2, cols * 512};
    cuuint32_t box[3] = {bcols, brows, 1};
    cuuint32_t es[3] = {1, 1, 1};
    enc(tm, CU_TENSOR_MAP_DATA_TYPE_BFLOAT16, 3, const_cast<void*>(p), dims, strides, box, es, CU_TENSOR_MAP_INTERLEAVE_NONE,
        bcols == 16 ? CU_TENSOR_MAP_SWIZZLE_32B : CU_TENSOR_MAP_SWIZZLE_64B, CU_TENSOR_MAP_L2_PROMOTION_L2_128B,
        CU_TENSOR_MAP_FLOAT_OOB_FILL_NONE);
}

}

extern "C" void kernel_launch(void* const* d_in, const int* in_sizes, int n_in, void* d_out, int out_size) {
    (void)in_sizes; (void)n_in; (void)out_size;
    static EncodeTiledFn enc = nullptr;
    static Scratch* gs = nullptr;
    if (!enc) {
        cudaGetSymbolAddress((void**)&gs, g_scratch);
        void* fn = nullptr;
        cudaDriverEntryPointQueryResult qr;
        cudaGetDriverEntryPoint("cuTensorMapEncodeTiled", &fn, cudaEnableDefault, &qr);
        enc = (EncodeTiledFn)fn;
        cudaFuncSetAttribute(fused_decode_kernel, cudaFuncAttributeMaxDynamicSharedMemorySize, SM_END);
    }
    Maps maps;
    encode_map(enc, &maps.wuk, d_in[8], 4096, 512, 32, 2);
    encode_slice_map(enc, &maps.wuv, d_in[9], 4096, 512, 32, 128);
    encode_slice_map(enc, &maps.woB, d_in[10], 512, 4096, 16, 256);
    encode_slice_map(enc, &maps.woA, d_in[4], 512, 4096, 16, 256);
    encode_slice_map(enc, &maps.endB, d_in[10], 512, 4096, 16, 64);
    encode_slice_map(enc, &maps.endA, d_in[4], 512, 4096, 16, 64);
    encode_map(enc, &maps.ckv, d_in[6], 512, 16384, 8, 8);
    uint64_t first = (uint64_t)d_in[7];
    if ((uint32_t)first >= 0xffe00000u) first += 1 << 21;
    fused_decode_kernel<<<NCTA, NTHR, SM_END>>>(make_uint2((uint32_t)first, (uint32_t)(first >> 32)),
                                                (const __nv_bfloat16*)d_in[0], (const __nv_bfloat16*)d_in[5],
                                                (const __nv_bfloat16*)d_in[7], (const __nv_bfloat16*)d_in[3],
                                                (const __nv_bfloat16*)d_in[1] + 3072 * 128, (const __nv_bfloat16*)d_in[2] + 3072 * 128,
                                                (__nv_bfloat16*)d_out, gs, maps);
}
```

```cpp
#include <cuda_runtime.h>
#include <cuda_bf16.h>
#include <cuda.h>
#include <stdint.h>

namespace {

constexpr int NCTA   = 128;
constexpr int NSLOT  = 13;
constexpr int SLOT   = 16384;
constexpr int NITEM  = 56;
constexpr int NTHR   = 384;

constexpr int INFLIGHT = 4;
constexpr int PACE     = 638;
constexpr int LEAD     = 580;
constexpr int SECOND   = 1205;
constexpr int TAPER    = 272;
constexpr int OS0      = -115;
constexpr int OS1      = 242;
constexpr int OF0      = -252;
constexpr int OF1      = 471;
constexpr int OF2      = 1660;
constexpr int OF3      = 168;
constexpr int OA       = 38;
constexpr int XS       = 1294;
constexpr int XF       = 1600;
constexpr uint64_t ROWS_A = 0x170fdba954326ec8ull, ROWS_B = 0x7659fecb321048daull;
constexpr uint64_t inverse(uint64_t rows) {
    uint64_t r = 0;
    for (uint64_t n = 0; n < 16; n++) r |= n << (rows >> n * 4 & 15) * 4;
    return r;
}
constexpr uint64_t PIECE_A = inverse(ROWS_A), PIECE_B = inverse(ROWS_B);
constexpr int OPGAP    = 256;
constexpr int NWIN     = 4;
__device__ constexpr int win_pos(int k)  { return k == 0 ? 10 : k == 1 ? 20 : k == 2 ? 31 : 38; }
__device__ constexpr int win_late(int k) { return k == 0 ? 1850 : k == 1 ? 1765 : k == 2 ? 1860 : 1715; }
constexpr int GAIN     = 11;

constexpr int IT_WQA = 0, IT_WQB = 2, IT_WUK = 4, IT_K0 = 6, IT_Q = 14, IT_C = 16, IT_K1 = 24, IT_V0 = 32,
              IT_OP = 40, IT_V1 = 42, IT_WUV = 50, IT_WO = 52;
constexpr int IT_X = 56;
constexpr int BAR_QA = 54, BAR_LAT = 55;
constexpr int ROT = 12;

constexpr int SM_FULL  = NSLOT * SLOT;
constexpr int SM_EMPTY = SM_FULL + 512;
constexpr int SM_IN0   = SM_EMPTY + 512;
constexpr int SM_IN1   = SM_IN0 + 1088;
constexpr int SM_SC    = SM_IN1 + 1088;
constexpr int SM_PA    = SM_SC + 4096;
constexpr int SM_PF    = SM_PA + 2048;
constexpr int SM_MX    = SM_PF + 8192;
constexpr int SM_ML    = SM_MX + 1024;
constexpr int SM_LAST  = SM_ML + 128;
constexpr int SM_CNT   = SM_LAST + 128;
constexpr int SM_RCV   = SM_CNT + 128;
constexpr int SM_PACE  = SM_RCV + 256;
constexpr int SM_END   = SM_PACE + 32;
constexpr int SM_LAT   = SM_PF + 4096;
constexpr int SM_FIN   = SM_PF;
constexpr int SM_SUM   = SM_IN0;
static_assert(SM_END <= 232448, "smem");

struct Maps { CUtensorMap wuk, wuv, woA, woB, ckv, endA, endB; };

struct Scratch {
    uint64_t late[16];
    unsigned cnt[NCTA][32];
    float    part[2][NCTA][512];
    uint32_t x[2][32][256];
    uint32_t lat[32][4][256];
    uint4    qa[4][32][16];
    uint2    sa[NCTA][32];
    uint2    oa[NCTA][32][32];
    uint4    q[4][2048];
    uint4    op[NCTA][2048];
    float2   stat[32][128];
};
__device__ __align__(128) Scratch g_scratch;

constexpr int SPIN_LIMIT = 1 << 22;

__device__ __forceinline__ uint32_t smem_u32(const void* p) { return (uint32_t)__cvta_generic_to_shared(p); }
__device__ __forceinline__ void mbar_init(uint32_t bar, uint32_t cnt) {
    asm volatile("mbarrier.init.shared::cta.b64 [%0], %1;" ::"r"(bar), "r"(cnt) : "memory");
}
__device__ __forceinline__ void mbar_expect_tx(uint32_t bar, uint32_t bytes) {
    asm volatile("mbarrier.arrive.expect_tx.shared::cta.b64 _, [%0], %1;" ::"r"(bar), "r"(bytes) : "memory");
}
__device__ __forceinline__ void mbar_arrive(uint32_t bar) {
    asm volatile("mbarrier.arrive.shared::cta.b64 _, [%0];" ::"r"(bar) : "memory");
}
__device__ __forceinline__ void mbar_arrive8(uint32_t bar) {
    asm volatile("mbarrier.arrive.shared::cta.b64 _, [%0], 8;" ::"r"(bar) : "memory");
}
__device__ __forceinline__ void mbar_wait(uint32_t bar) {
    uint32_t done;
    int it = 0;
    do {
        asm volatile("{\n.reg .pred p;\nmbarrier.try_wait.parity.shared::cta.b64 p, [%1], 0;\nselp.u32 %0, 1, 0, p;\n}"
                     : "=r"(done) : "r"(bar) : "memory");
        if (++it > SPIN_LIMIT) __trap();
    } while (!done);
}
__device__ __forceinline__ uint32_t map_cta(uint32_t a, uint32_t rank) {
    uint32_t r; asm("mapa.shared::cluster.u32 %0, %1, %2;" : "=r"(r) : "r"(a), "r"(rank)); return r;
}
__device__ __forceinline__ void st_async64_if(uint32_t a, float x, float y, uint32_t bar, bool on) {
    asm volatile("{\n.reg .pred p;\nsetp.ne.u32 p, %4, 0;\n@p st.async.shared::cluster.mbarrier::complete_tx::bytes.v2.f32 [%0], {%1,%2}, [%3];\n}"
                 ::"r"(a), "f"(x), "f"(y), "r"(bar), "r"((uint32_t)on) : "memory");
}
__device__ __forceinline__ uint64_t evict_first() {
    uint64_t pol; asm volatile("createpolicy.fractional.L2::evict_first.b64 %0, 1.0;" : "=l"(pol)); return pol;
}
#define ELECT "{\n.reg .pred p;\nelect.sync _|p, 0xffffffff;\n@p "
__device__ __forceinline__ void bulk_load(uint32_t dst, const void* src, uint32_t bytes, uint32_t bar, uint64_t pol) {
    asm volatile(ELECT "cp.async.bulk.shared::cluster.global.mbarrier::complete_tx::bytes.L2::cache_hint [%0], [%1], %2, [%3], %4;\n}"
                 ::"r"(dst), "l"(src), "r"(bytes), "r"(bar), "l"(pol) : "memory");
}
__device__ __forceinline__ void bulk_load_nohint(uint32_t dst, const void* src, uint32_t bytes, uint32_t bar) {
    asm volatile("cp.async.bulk.shared::cluster.global.mbarrier::complete_tx::bytes [%0], [%1], %2, [%3];"
                 ::"r"(dst), "l"(src), "r"(bytes), "r"(bar) : "memory");
}
__device__ __forceinline__ void tma3d(uint32_t dst, const CUtensorMap* tm, int c0, int c1, int c2, uint32_t bar, uint64_t pol) {
    asm volatile(ELECT "cp.async.bulk.tensor.3d.shared::cluster.global.mbarrier::complete_tx::bytes.L2::cache_hint [%0], [%1, {%3, %4, %5}], [%2], %6;\n}"
                 ::"r"(dst), "l"(tm), "r"(bar), "r"(c0), "r"(c1), "r"(c2), "l"(pol) : "memory");
}
__device__ __forceinline__ void ldsm4(uint32_t a, uint32_t& r0, uint32_t& r1, uint32_t& r2, uint32_t& r3) {
    asm volatile("ldmatrix.sync.aligned.m8n8.x4.shared.b16 {%0,%1,%2,%3}, [%4];"
                 : "=r"(r0), "=r"(r1), "=r"(r2), "=r"(r3) : "r"(a) : "memory");
}
__device__ __forceinline__ void ldsm4t(uint32_t a, uint32_t& r0, uint32_t& r1, uint32_t& r2, uint32_t& r3) {
    asm volatile("ldmatrix.sync.aligned.m8n8.x4.trans.shared.b16 {%0,%1,%2,%3}, [%4];"
                 : "=r"(r0), "=r"(r1), "=r"(r2), "=r"(r3) : "r"(a) : "memory");
}
__device__ __forceinline__ void mma16816(float (&c)[4], uint32_t a0, uint32_t a1, uint32_t a2, uint32_t a3,
                                         uint32_t b0, uint32_t b1) {
    asm volatile("mma.sync.aligned.m16n8k16.row.col.f32.bf16.bf16.f32 {%0,%1,%2,%3}, {%4,%5,%6,%7}, {%8,%9}, {%0,%1,%2,%3};"
                 : "+f"(c[0]), "+f"(c[1]), "+f"(c[2]), "+f"(c[3])
                 : "r"(a0), "r"(a1), "r"(a2), "r"(a3), "r"(b0), "r"(b1));
}
__device__ __forceinline__ uint32_t lds32(uint32_t a) {
    uint32_t v; asm volatile("ld.shared.b32 %0, [%1];" : "=r"(v) : "r"(a) : "memory"); return v;
}
__device__ __forceinline__ float ldsf(uint32_t a) {
    float v; asm volatile("ld.shared.f32 %0, [%1];" : "=f"(v) : "r"(a) : "memory"); return v;
}
__device__ __forceinline__ float2 ldsf2(uint32_t a) {
    float2 v; asm volatile("ld.shared.v2.f32 {%0,%1}, [%2];" : "=f"(v.x), "=f"(v.y) : "r"(a) : "memory"); return v;
}
__device__ __forceinline__ float4 ldsf4(uint32_t a) {
    float4 v; asm volatile("ld.shared.v4.f32 {%0,%1,%2,%3}, [%4];" : "=f"(v.x), "=f"(v.y), "=f"(v.z), "=f"(v.w) : "r"(a) : "memory"); return v;
}
__device__ __forceinline__ uint4 lds128(uint32_t a) {
    uint4 v; asm volatile("ld.shared.v4.b32 {%0,%1,%2,%3}, [%4];" : "=r"(v.x), "=r"(v.y), "=r"(v.z), "=r"(v.w) : "r"(a) : "memory"); return v;
}
__device__ __forceinline__ float ldsf_if(uint32_t a, bool on) {
    float v = 0.f;
    asm volatile("{\n.reg .pred p;\nsetp.ne.u32 p, %2, 0;\n@p ld.shared.f32 %0, [%1];\n}" : "+f"(v) : "r"(a), "r"((uint32_t)on) : "memory");
    return v;
}
__device__ __forceinline__ float4 ldv4(uint32_t a) {
    float4 v; asm volatile("ld.volatile.shared.v4.f32 {%0,%1,%2,%3}, [%4];" : "=f"(v.x), "=f"(v.y), "=f"(v.z), "=f"(v.w) : "r"(a) : "memory"); return v;
}
__device__ __forceinline__ void stv(uint32_t a, float v) { asm volatile("st.volatile.shared.f32 [%0], %1;" ::"r"(a), "f"(v) : "memory"); }
__device__ __forceinline__ void sts16(uint32_t a, uint16_t v) { asm volatile("st.shared.b16 [%0], %1;" ::"r"(a), "h"(v) : "memory"); }
__device__ __forceinline__ void sts32(uint32_t a, uint32_t v) { asm volatile("st.shared.b32 [%0], %1;" ::"r"(a), "r"(v) : "memory"); }
__device__ __forceinline__ void stsf(uint32_t a, float v) { asm volatile("st.shared.f32 [%0], %1;" ::"r"(a), "f"(v) : "memory"); }
__device__ __forceinline__ void sts64(uint32_t a, uint32_t x, uint32_t y) {
    asm volatile("st.shared.v2.b32 [%0], {%1,%2};" ::"r"(a), "r"(x), "r"(y) : "memory");
}
__device__ __forceinline__ void sts128(uint32_t a, uint4 v) {
    asm volatile("st.shared.v4.b32 [%0], {%1,%2,%3,%4};" ::"r"(a), "r"(v.x), "r"(v.y), "r"(v.z), "r"(v.w) : "memory");
}
__device__ __forceinline__ uint32_t pack_bf16(float lo, float hi) {
    uint32_t r; asm("cvt.rn.bf16x2.f32 %0, %1, %2;" : "=r"(r) : "f"(hi), "f"(lo)); return r;
}
__device__ __forceinline__ float bf_lo(uint32_t v) { return __uint_as_float(v << 16); }
__device__ __forceinline__ float bf_hi(uint32_t v) { return __uint_as_float(v & 0xffff0000u); }
__device__ __forceinline__ float ex2(float x) { float y; asm("ex2.approx.ftz.f32 %0, %1;" : "=f"(y) : "f"(x)); return y; }
__device__ __forceinline__ uint32_t timer_ns() { uint32_t t; asm volatile("mov.u32 %0, %%globaltimer_lo;" : "=r"(t)); return t; }
__device__ __forceinline__ void bar_consumers() { asm volatile("bar.sync 1, 256;" ::: "memory"); }

__device__ __forceinline__ uint32_t tagf(float v, uint32_t tag) { return (__float_as_uint(v) & 0xffffff00u) | tag; }
__device__ __forceinline__ uint2 ld_rlx2(const void* p) {
    uint64_t v; asm volatile("ld.relaxed.gpu.global.b64 %0, [%1];" : "=l"(v) : "l"(p) : "memory");
    return make_uint2((uint32_t)v, (uint32_t)(v >> 32));
}
__device__ __forceinline__ float untag(uint32_t v) { return __uint_as_float(v & 0xffffff00u); }

__device__ __forceinline__ uint32_t slot_off(int item) { return (uint32_t)(item % NSLOT) * SLOT; }

template <bool TRANS, bool TMA = true>
__device__ __forceinline__ void tile_mma(uint32_t sb, int item, uint32_t in, int w, int lane, float (&acc)[2][2]) {
    const int g = lane >> 2, t = lane & 3;
    float c[4][4];
#pragma unroll
    for (int i = 0; i < 16; i++) (&c[0][0])[i] = 0.f;
    uint32_t a[16];
    const uint32_t ia = in + (g & 3) * 272 + t * 4;
#pragma unroll
    for (int i = 0; i < 16; i++) a[i] = lds32(ia + i * 16);
    const uint32_t s0 = sb + slot_off(item), s1 = sb + slot_off(item + 1);
    if (TRANS) {
        const int r = (lane & 7) + (lane & 8);
        const int ch = 2 * (w & 3) + (lane >> 4);
        const uint32_t off = (TMA ? (w >> 2) * 8192 + r * 128 : (w >> 2) * 128 + r * 256) + ((ch ^ (lane & 7)) << 4);
#pragma unroll
        for (int kk = 0; kk < 8; kk++) {
            if (TMA && (kk & 3) == 0) mbar_wait(sb + SM_FULL + (item + (kk >> 2)) * 8);
            uint32_t r0, r1, r2, r3;
            ldsm4t(((kk >> 2) ? s1 : s0) + off + (kk & 3) * (TMA ? 2048 : 4096), r0, r1, r2, r3);
            mma16816(c[2 * (kk & 1)],     a[2 * kk], 0u, a[2 * kk + 1], 0u, r0, r1);
            mma16816(c[2 * (kk & 1) + 1], a[2 * kk], 0u, a[2 * kk + 1], 0u, r2, r3);
        }
    } else {
        mbar_wait(sb + SM_FULL + (item + (w >> 2)) * 8);
        const int r = 16 * (w & 3) + (lane & 7) + ((lane >> 4) << 3);
        const uint32_t base = ((w >> 2) ? s1 : s0) + (r & 32) * 128 + r * 128 + ((((lane >> 3) & 1) ^ (lane & 7)) << 4);
#pragma unroll
        for (int kk = 0; kk < 8; kk++) {
            uint32_t r0, r1, r2, r3;
            ldsm4((base ^ ((kk & 3) << 5)) + (kk >> 2) * 4096, r0, r1, r2, r3);
            mma16816(c[2 * (kk & 1)],     a[2 * kk], 0u, a[2 * kk + 1], 0u, r0, r1);
            mma16816(c[2 * (kk & 1) + 1], a[2 * kk], 0u, a[2 * kk + 1], 0u, r2, r3);
        }
    }
    __syncwarp();
    if (lane == 0) {
        mbar_arrive(sb + SM_EMPTY + item * 8);
        mbar_arrive(sb + SM_EMPTY + (item + 1) * 8);
    }
    acc[0][0] = c[0][0] + c[2][0]; acc[0][1] = c[0][1] + c[2][1];
    acc[1][0] = c[1][0] + c[3][0]; acc[1][1] = c[1][1] + c[3][1];
}

__device__ __forceinline__ void publish(float* dst, int w, int lane, const float (&acc)[2][2], uint32_t tag) {
    if (lane < 16)
        asm volatile("st.relaxed.gpu.global.v4.b32 [%0], {%1,%2,%3,%4};" ::"l"(dst + w * 64 + lane * 4),
                     "r"(tagf(acc[0][0], tag)), "r"(tagf(acc[0][1], tag)), "r"(tagf(acc[1][0], tag)), "r"(tagf(acc[1][1], tag)) : "memory");
}

__device__ __forceinline__ void gather(const float* part, uint32_t in, int tid, uint32_t tag) {
    const float* p = part + tid * 2;
    uint2 v0, v1, v2, v3;
    int it = 0;
    while (true) {
        v0 = ld_rlx2(p); v1 = ld_rlx2(p + 512); v2 = ld_rlx2(p + 1024); v3 = ld_rlx2(p + 1536);
        uint32_t bad = ((v0.x ^ tag) | (v0.y ^ tag) | (v1.x ^ tag) | (v1.y ^ tag) |
                        (v2.x ^ tag) | (v2.y ^ tag) | (v3.x ^ tag) | (v3.y ^ tag)) & 0xffu;
        if (__all_sync(0xffffffffu, bad == 0)) break;
        if (++it > SPIN_LIMIT) __trap();
    }
    float x = (untag(v0.x) + untag(v1.x)) + (untag(v2.x) + untag(v3.x));
    float y = (untag(v0.y) + untag(v1.y)) + (untag(v2.y) + untag(v3.y));
    sts32(in + ((tid >> 3) & 3) * 272 + (tid >> 5) * 32 + (tid & 1) * 16 + (tid & 6) * 2, pack_bf16(x, y));
    bar_consumers();
}

constexpr uint32_t EMPTY = 0xffffffffu;
__device__ __forceinline__ void st_rlx(uint32_t* p, uint32_t v) {
    asm volatile("st.relaxed.gpu.global.b32 [%0], %1;" ::"l"(p), "r"(v) : "memory");
}
__device__ __forceinline__ void st_rlx_if(uint64_t p, uint32_t v, bool on) {
    asm volatile("{\n.reg .pred p;\nsetp.ne.u32 p, %2, 0;\n@p st.relaxed.gpu.global.b32 [%0], %1;\n}" ::"l"(p), "r"(v), "r"((uint32_t)on) : "memory");
}
__device__ __forceinline__ void st_if(uint64_t p, uint32_t v, bool on) {
    asm volatile("{\n.reg .pred p;\nsetp.ne.u32 p, %2, 0;\n@p st.global.b32 [%0], %1;\n}" ::"l"(p), "r"(v), "r"((uint32_t)on) : "memory");
}
__device__ __forceinline__ void st_rlx2(uint32_t* p, uint32_t v0, uint32_t v1) {
    asm volatile("st.relaxed.gpu.global.v2.b32 [%0], {%1,%2};" ::"l"(p), "r"(v0), "r"(v1) : "memory");
}
__device__ __forceinline__ void ld_rlx4_if(uint4& v, const void* p, bool need) {
    asm volatile("{\n.reg .pred p;\nsetp.ne.u32 p, %5, 0;\n@p ld.relaxed.gpu.global.v4.b32 {%0,%1,%2,%3}, [%4];\n}"
                 : "+r"(v.x), "+r"(v.y), "+r"(v.z), "+r"(v.w) : "l"(p), "r"((uint32_t)need) : "memory");
}

template <int N, class F>
__device__ __forceinline__ bool refetch(uint4 (&x)[N], F addr) {
    uint32_t m[N], m0 = 0;
#pragma unroll
    for (int i = 0; i < N; i++) {
        m[i] = max(max(x[i].x, x[i].y), max(x[i].z, x[i].w));
        m0 = max(m0, m[i]);
    }
    if (!__any_sync(0xffffffffu, m0 == EMPTY)) return false;
#pragma unroll
    for (int i = 0; i < N; i++) ld_rlx4_if(x[i], addr(i), m[i] == EMPTY);
    return true;
}

__device__ __forceinline__ unsigned read_counter(const unsigned* cnt) {
    unsigned v;
    asm volatile("ld.relaxed.gpu.global.u32 %0, [%1];" : "=r"(v) : "l"(cnt) : "memory");
    return v;
}
__device__ __forceinline__ unsigned epoch_of(unsigned cnt) {
    asm volatile("" : "+r"(cnt) :: "memory");
    return cnt + 1;
}
__device__ __forceinline__ uint32_t epoch_tag(unsigned epoch) { return (epoch & 0x7fu) | 0x80u; }

__device__ __forceinline__ void signal_and_wait(unsigned* cnt, unsigned target, int lane) {
    if (lane == 0) asm volatile("red.release.gpu.global.add.u32 [%0], 1;" ::"l"(cnt) : "memory");
    int it = 0;
    while (true) {
        unsigned v;
        asm volatile("ld.acquire.gpu.global.u32 %0, [%1];" : "=r"(v) : "l"(cnt) : "memory");
        if (__all_sync(0xffffffffu, (int)(v - target) >= 0)) break;
        if (++it > SPIN_LIMIT) __trap();
    }
    asm volatile("fence.proxy.async.global;" ::: "memory");
}

__global__ void __cluster_dims__(2, 1, 1) __launch_bounds__(NTHR, 1)
fused_decode_kernel(const uint2 first, const __nv_bfloat16* __restrict__ xA, const __nv_bfloat16* __restrict__ xB,
                    const __nv_bfloat16* __restrict__ wqA, const __nv_bfloat16* __restrict__ wqB,
                    const __nv_bfloat16* __restrict__ Kc, const __nv_bfloat16* __restrict__ Vc,
                    __nv_bfloat16* __restrict__ out, Scratch* gs, const __grid_constant__ Maps maps) {
    extern __shared__ __align__(1024) unsigned char smem_raw[];
    const uint32_t sb = smem_u32(smem_raw);
    const int tid = threadIdx.x, lane = tid & 31;
    const int cta = blockIdx.x, h = cta >> 2, j = cta & 3;
    asm volatile("{\n.reg .b32 l;\n.reg .b64 a;\nmad.lo.u32 l, %2, 32, %0;\nmov.b64 a, {l, %1};\nprefetch.global.L2 [a];\n}"
                 ::"r"(first.x + blockIdx.x * (NTHR * 32)), "r"(first.y), "r"(threadIdx.x) : "memory");
    const uint32_t trow = threadIdx.x >> 4;
    const uint32_t tile_src = trow * (8192 - 256) + (threadIdx.x * 16 + ((blockIdx.x * 0x100040u) & 0x301f00u));
    const uint32_t tile_dst = sb + ((threadIdx.x ^ (trow & 7)) << 4);
    auto lsu_piece = [&](int k) {
#pragma unroll
        for (int q = 2 * k; q < 2 * k + 2; q++)
            asm volatile("cp.async.cg.shared.global [%0], [%1], 16;" ::"r"(tile_dst + q * 4096),
                         "l"(reinterpret_cast<const char*>((k < 4 ? wqA : wqB) + (q & 7) * 16 * 4096) + tile_src) : "memory");
        if ((k & 3) == 3) asm volatile("cp.async.commit_group;" ::: "memory");
    };
    if (tid < 256) {
#pragma unroll
        for (int k = 0; k < 4; k++) lsu_piece(k);
    }
    const uint32_t tz = timer_ns() - LEAD;
    unsigned cnt1;
    if (tid < 256) cnt1 = read_counter(gs->cnt[blockIdx.x]);
    uint4 xv;
    if (tid < 128) {
        const __nv_bfloat16* x = (tid < 64 ? xB : xA) + ((tid >> 4) & 3) * 512 + j * 128 + (tid & 15) * 8;
        xv = __ldg(reinterpret_cast<const uint4*>(x));
    }
    const int w = __shfl_sync(0xffffffffu, tid >> 5, 0);
    const int pr = cta >> 1;
    const int slice = pr < 4 ? pr : pr < 36 ? 4 + ((pr - 4) & 7) * 4 + ((pr - 4) >> 3) : 36 + (pr - 36) % 7 * 4 + (pr - 36) / 7;

    if (w >= 8) {
        if (lane == 0) {
            const uint32_t full = sb + SM_FULL + (IT_WUK + (w & 3) * 14) * 8, empty = sb + SM_EMPTY + (w & 3) * 13 * 8,
                           last = sb + SM_LAST + (w & 3) * 32;
#pragma unroll
            for (int i = 0; i < 14; i++) mbar_init(full + i * 8, 1);
#pragma unroll
            for (int i = 0; i < 13; i++) mbar_init(empty + i * 8, 8);
#pragma unroll
            for (int i = 0; i < 4; i++) mbar_init(last + i * 8, 1);
#pragma unroll
            for (int i = 0; i < 14; i++) {
                const int b = IT_WUK + 42 + i;
                mbar_expect_tx(full + i * 8, (w == 10 && b - 14 == IT_OP) ? SLOT + 1024 : (w == 11 && b == BAR_LAT) ? 4096 : (w == 11 && b == BAR_QA) ? 8192 : SLOT);
            }
#pragma unroll
            for (int i = 0; i < 4; i++) mbar_expect_tx(last + i * 8, i == 1 && w == 8 && !(j & 1) ? 2048 + 256 : 2048);
            asm volatile("fence.mbarrier_init.release.cluster;" ::: "memory");
            if (w == 10) sts64(sb + SM_PACE, tz, PACE * 16);
        }
        asm volatile("bar.sync 2, 128;" ::: "memory");
        asm volatile("bar.arrive 4, 384;" ::: "memory");
    }
    if (w == 10) {
        if (lane == 0) {
            int slope = 0;
#pragma unroll
            for (int k = 0; k < NWIN; k++) {
                const int c = win_pos(k);
                uint32_t acc = 0;
#pragma unroll
                for (int p = c; p < c + 4; p++) {
                    mbar_wait(sb + SM_FULL + (p < IT_Q ? p : p < IT_OP - 2 ? p + 2 : p + 4) * 8);
                    acc += timer_ns() - tz - p * PACE - ((p * slope) >> 4);
                }
                if (k == 0) mbar_wait(sb + SM_FULL + IT_Q * 8);
                asm volatile("red.relaxed.gpu.global.add.u64 [%0], %1;" ::"l"(&gs->late[k]),
                             "l"((uint64_t)tz << 32 | (1u << 24) + min(acc >> 2, 65535u)) : "memory");
                uint2 v;
                int it = 0;
                do { v = ld_rlx2(&gs->late[k]); } while ((v.x >> 24) != NCTA && ++it < 1000);
                if (it == 1000) break;
                const int late = (v.x & 0xffffffu) / NCTA;
                slope = max(-320, min(480, slope + (late - win_late(k)) * (GAIN * 2) / (2 * c + 3)));
                sts64(sb + SM_PACE, k < NWIN - 1 ? tz : tz + (int)(v.y - tz * NCTA) / NCTA, PACE * 16 + slope);
            }
        }
        return;
    }
    if (w >= 8) {
        auto wait_due = [&](uint32_t p, uint32_t shift) {
            uint32_t a, b;
            do {
                asm volatile("ld.volatile.shared.v2.b32 {%0,%1}, [%2];" : "=r"(a), "=r"(b) : "r"(sb + SM_PACE) : "memory");
            } while (__all_sync(0xffffffffu, (int)(timer_ns() - (a + ((p * b) >> 4) + shift)) < 0));
        };
        if (w != 9) {
            const int half = w & 1;
            const uint64_t pol = evict_first();
            const uint32_t rows = (slice < 32 ? ROWS_A : ROWS_B) >> ((j & 1) * 32 + half * 4);
            const int kv0 = (half * 4 + (cta >> 5) + ROT) * 128 + (cta & 31);
            int slot = IT_WUK, tail = IT_WUK - INFLIGHT;
            uint32_t np = IT_WUK, shift = half ? PACE / 4 : -(PACE / 4);
#pragma unroll 1
            for (int i = IT_WUK; i < NITEM; i++) {
                const uint32_t dst = sb + slot * SLOT + half * (SLOT / 2), bar = sb + SM_FULL + i * 8;
                if (++slot == NSLOT) slot = 0;
                if ((i & ~1) == IT_Q || (i & ~1) == IT_OP) continue;
                const bool ckv = i >= IT_C && i < IT_K1, wo = i >= IT_WO;
                const bool tiled = ckv || i < IT_K0 || i >= IT_WUV;
                const CUtensorMap* tm = &maps.wuk + (i < IT_K0 ? 0 : ckv ? 4 : wo ? 2 + (slice >> 5) : 1);
                const int c0 = wo ? (slice & 31) * 16 : i >= IT_WUV ? cta * 32 : 0;
                const int c1 = i < IT_K0 ? j * 128 + (i & 1) * 64 + half * 32 : ckv ? cta * 128 + (i - IT_C) * 16 + half * 8 : wo ? 0 : half * 128;
                const int c2 = i < IT_K0 ? h * 2 : ckv ? 0 : wo ? rows >> (i - IT_WO) * 8 & 15 : i & 1;
                const int c = i < IT_Q ? i - IT_K0 : i < IT_V0 ? i - IT_K1 + 8 : i < IT_OP ? i - IT_V0 : i - IT_V1 + 8;
                const __nv_bfloat16* src = (i < IT_V0 ? Kc : Vc) + (size_t)((c * 1024 + kv0) & 0x3fff) * (SLOT / 4);
                if (i >= NSLOT) mbar_wait(sb + SM_EMPTY + (i - NSLOT) * 8);
                if (tail >= IT_WUK && !wo) mbar_wait(sb + SM_FULL + tail * 8);
                ++tail;
                if (tail == IT_Q || tail == IT_OP) tail += 2;
                if (wo) {
                    const int n = (i - IT_WO) * 2 + half;
                    np = IT_WO - 4;
                    shift = TAPER + ((j & 1) ? OS0 + n * OS1 : n < 4 ? OF0 + n * OF1 : OF2 + (n - 4) * OF3 + (slice < 32 ? OA : 0));
                }
                wait_due(np, shift);
                ++np;
                if (i == IT_WUV - 1) shift += TAPER;
                if (i >= NITEM - 2) {
#pragma unroll
                    for (int q = 0; q < 4; q++)
                        tma3d(dst + q * 2048, tm + 3, c0, q * 64, c2, sb + SM_LAST + half * 64 + q * 16 + (i & 1) * 8, pol);
                }
                else if (tiled) tma3d(dst, tm, c0, c1, c2, bar, pol);
                else bulk_load(dst, src, SLOT / 2, bar, pol);
            }
        } else {
            if (lane < sizeof(Maps) / 128) asm volatile("prefetch.tensormap [%0];" ::"l"(&maps.wuk + lane) : "memory");
            cnt1 = read_counter(gs->cnt[blockIdx.x]);
            asm volatile("bar.sync 3, 288;" ::: "memory");
            const unsigned epoch = epoch_of(cnt1);
            if (lane == 0) st_rlx(gs->cnt[cta], epoch);
            signal_and_wait(&gs->cnt[0][1], epoch * NCTA, lane);
            if (lane == 0) {
                bulk_load_nohint(sb + SM_PF, gs->qa[cta >> 5], 4096, sb + SM_FULL + BAR_QA * 8);
                bulk_load_nohint(sb + SM_SC, gs->qa[cta >> 5][16], 4096, sb + SM_FULL + BAR_QA * 8);
                const uint4* q = gs->q[cta >> 5];
                bulk_load_nohint(sb + slot_off(IT_Q), q, SLOT, sb + SM_FULL + IT_Q * 8);
                bulk_load_nohint(sb + slot_off(IT_Q + 1), q + 1024, SLOT, sb + SM_FULL + (IT_Q + 1) * 8);
            }
            asm volatile("bar.sync 3, 288;" ::: "memory");
            signal_and_wait(&gs->cnt[0][2], epoch * NCTA, lane);
            mbar_wait(sb + SM_EMPTY + (IT_OP - NSLOT) * 8);
            mbar_wait(sb + SM_EMPTY + (IT_OP + 1 - NSLOT) * 8);
            if (lane == 0) {
                const uint4* op = gs->op[cta];
                bulk_load_nohint(sb + SM_MX, gs->stat[h], 1024, sb + SM_FULL + IT_OP * 8);
                uint32_t t1 = timer_ns();
#pragma unroll 1
                for (int i = 0; i < 8; i++) {
                    while ((int)(timer_ns() - t1) < 0) {}
                    t1 += OPGAP;
                    bulk_load_nohint(sb + slot_off(IT_OP) + i * 4096, op + i * 256, 4096, sb + SM_FULL + (IT_OP + i / 4) * 8);
                }
            }
            mbar_wait(sb + SM_FULL + (IT_V1 + 4) * 8);
            if (lane == 0) bulk_load_nohint(sb + SM_LAT, gs->lat[h], 4096, sb + SM_FULL + BAR_LAT * 8);
            mbar_wait(sb + SM_EMPTY + (IT_X - NSLOT) * 8);
            mbar_wait(sb + SM_FULL + (IT_WUV + 1) * 8);
            wait_due(IT_WO - 4, TAPER + ((j & 1) ? XS : XF));
            if (lane == 0) bulk_load_nohint(sb + slot_off(IT_X), gs->x[slice >> 5][(j & 1) * 16], SLOT, sb + SM_FULL + IT_X * 8);
        }
        return;
    }

    const int g = lane >> 2, t = lane & 3;
    const uint32_t in0 = sb + SM_IN0, in1 = sb + SM_IN1;
    const int ba = cta >> 5, ha = cta & 31;
    auto xpos = [](uint64_t piece, int head) { return (int)(piece >> (head >> 1) * 4 & 15) * 2 + (head & 1); };
    uint32_t* const ctx_dst = &gs->x[1][xpos(PIECE_B, h)][(j * 4 + (w & 3)) * 16 + ((g ^ (w & 2)) & 3) * 4 + ((t - w) & 3)];
    const int oc = (lane & 8) + (lane & 1) * 4 + (lane >> 3 & 2) + (g & 1);
    uint32_t* const o_dst = &gs->x[0][xpos(PIECE_A, ha)][ba * 64 + (oc ^ (ba & 1) * 4) * 4 + ((w - oc) & 3)];
    uint32_t* const lat_dst = &gs->lat[h][g & 3][j * 64 + ((w >> 1) ^ (g & 1)) * 16 + t * 4 + ((w * 2 ^ t) & 2)];
    {
#pragma unroll
        for (int k = 4; k < 8; k++) {
            while (__all_sync(0xffffffffu, (int)(timer_ns() - (tz + SECOND + (k - 4) * (PACE / 2))) < 0)) {}
            lsu_piece(k);
        }
        if (lane < 16) st_rlx2(lat_dst, EMPTY, EMPTY);
        if (lane >= 16 && w < 4) st_rlx(ctx_dst, EMPTY);
        if (w >= 4 && !(lane & 2)) st_rlx(o_dst, EMPTY);
        if (cta == 0 && w == 5) st_rlx((uint32_t*)gs->late + lane, 0u);
        if (tid < 128) sts128((tid < 64 ? in0 : in1) + ((tid >> 4) & 3) * 272 + (tid & 15) * 16, xv);
        asm volatile("cp.async.wait_group 1;" ::: "memory");
    }
    asm volatile("bar.sync 4, 384;" ::: "memory");
    const uint32_t tag = epoch_tag(epoch_of(cnt1));

    float acc[2][2];
    tile_mma<true, false>(sb, IT_WQA, in1, w, lane, acc);
    publish(gs->part[1][cta], w, lane, acc, tag);
    asm volatile("cp.async.wait_group 0;" ::: "memory");
    bar_consumers();
    tile_mma<true, false>(sb, IT_WQB, in0, w, lane, acc);
    publish(gs->part[0][cta], w, lane, acc, tag);
    gather(gs->part[1][h * 4], in1, tid, tag);
    if (tid < 16) {
        const int u = j * 32 + h - ROT;
        gs->qa[u & 3][u >> 2 & 31][tid] = lds128(in1 + j * 272 + tid * 16);
    }

    const float SC = 0.08838834764831845f * 1.4426950408889634f;
    gather(gs->part[0][h * 4], in0, tid, tag);
    tile_mma<false>(sb, IT_WUK, in0, w, lane, acc);
    if (lane < 16) {
        uint32_t* q = reinterpret_cast<uint32_t*>(gs->q[g]) + (2 * j + (w >> 2)) * 1024 + h * 32 + t;
        const int ch = 2 * (w & 3);
        q[((ch) ^ (h & 7)) * 4]     = pack_bf16(acc[0][0] * SC, acc[0][1] * SC);
        q[((ch + 1) ^ (h & 7)) * 4] = pack_bf16(acc[1][0] * SC, acc[1][1] * SC);
    }
    __syncwarp();
    asm volatile("bar.arrive 3, 288;" ::: "memory");

    auto win = [&](int ph, int hf) { return (ph * 64 + w * 8 + hf * 4 + ba + ROT) & 127; };
    auto k_item = [&](int ph, uint32_t q) {
        uint32_t qf[2][16];
#pragma unroll
        for (int c = 0; c < 8; c++) {
#pragma unroll
            for (int k = 0; k < 4; k++) qf[k >> 1][2 * c + (k & 1)] = lds32(q + k * 128 + ((c ^ g) << 4) + t * 4);
        }
        const int item = (ph ? IT_K1 : IT_K0) + w;
        mbar_wait(sb + SM_FULL + item * 8);
        const uint32_t base = sb + slot_off(item) + ((lane & 7) + (lane & 8)) * 256 + ((lane >> 4) << 7);
        float s[4][4];
#pragma unroll
        for (int T = 0; T < 4; T++) { s[T][0] = s[T][1] = s[T][2] = s[T][3] = 0.f; }
#pragma unroll
        for (int c = 0; c < 8; c++) {
            const uint32_t a = base + ((c ^ (lane & 7)) << 4);
#pragma unroll
            for (int T = 0; T < 4; T++) {
                uint32_t r0, r1, r2, r3;
                ldsm4(a + T * 4096, r0, r1, r2, r3);
                mma16816(s[T], r0, r1, r2, r3, qf[T >> 1][2 * c], qf[T >> 1][2 * c + 1]);
            }
        }
        __syncwarp();
        if (lane == 0) mbar_arrive8(sb + SM_EMPTY + item * 8);
        if (t == (g >> 1)) {
#pragma unroll
            for (int T = 0; T < 4; T++) {
                stsf(q + (16 * T + g) * 4,     (g & 1) ? s[T][1] : s[T][0]);
                stsf(q + (16 * T + g + 8) * 4, (g & 1) ? s[T][3] : s[T][2]);
            }
        }
        __syncwarp();
        const float2 v = ldsf2(q + lane * 8);
        float m = fmaxf(v.x, v.y);
#pragma unroll
        for (int d = 1; d < 16; d <<= 1) m = fmaxf(m, __shfl_xor_sync(0xffffffffu, m, d));
        m *= SC;
        const uint32_t p = pack_bf16(ex2(fmaf(v.x, SC, -m)), ex2(fmaf(v.y, SC, -m)));
        float l = bf_lo(p) + bf_hi(p);
#pragma unroll
        for (int d = 1; d < 16; d <<= 1) l += __shfl_xor_sync(0xffffffffu, l, d);
        sts32(sb + SM_PA + w * 256 + ph * 128 + lane * 4, p);
        if (!(lane & 15)) st_rlx2(&gs->sa[win(ph, lane >> 4)][ha].x, __float_as_uint(m), __float_as_uint(l));
        __syncwarp();
    };
#pragma unroll
    for (int k = 0; k < 4; k++) st_rlx2(&gs->oa[win(k >> 1, k & 1)][ha][lane].x, EMPTY, EMPTY);
    if (!(lane & 15)) st_rlx2(&gs->sa[win(1, lane >> 4)][ha].x, EMPTY, EMPTY);
    mbar_wait(sb + SM_FULL + BAR_QA * 8);
    k_item(0, sb + SM_PF + w * 512);

    {
        float s[2][2][4];
#pragma unroll
        for (int i = 0; i < 16; i++) (&s[0][0][0])[i] = 0.f;
        mbar_wait(sb + SM_FULL + IT_Q * 8);
        mbar_wait(sb + SM_FULL + (IT_Q + 1) * 8);
        mbar_wait(sb + SM_FULL + (IT_C + w) * 8);
        const uint32_t cb0 = sb + slot_off(IT_C + w) + (lane & 7) * 128 + (lane >> 4) * 8192;
        const uint32_t cx = (((lane >> 3) & 1) ^ (lane & 7)) << 4;
        const uint32_t qr = ((lane & 7) + (lane & 8)) * 128;
        const uint32_t qx = ((lane >> 4) ^ (lane & 7)) << 4;
#pragma unroll
        for (int cb = 0; cb < 8; cb++) {
            const uint32_t qb = sb + slot_off(IT_Q + (cb >> 2)) + (cb & 3) * 4096 + qr;
#pragma unroll
            for (int k4 = 0; k4 < 4; k4++) {
                uint32_t b0, b1, b2, b3, a0, a1, a2, a3;
                ldsm4(cb0 + cb * 1024 + (cx ^ (k4 << 5)), b0, b1, b2, b3);
                ldsm4(qb + (qx ^ (k4 << 5)), a0, a1, a2, a3);
                mma16816(s[0][0], a0, a1, a2, a3, b0, b1);
                mma16816(s[0][1], a0, a1, a2, a3, b2, b3);
                ldsm4(qb + 2048 + (qx ^ (k4 << 5)), a0, a1, a2, a3);
                mma16816(s[1][0], a0, a1, a2, a3, b0, b1);
                mma16816(s[1][1], a0, a1, a2, a3, b2, b3);
            }
        }
        __syncwarp();
        if (lane == 0) { mbar_arrive(sb + SM_EMPTY + IT_Q * 8); mbar_arrive(sb + SM_EMPTY + (IT_Q + 1) * 8); }
#pragma unroll
        for (int r = 0; r < 4; r++) {
            const int mt = r >> 1, hi = (r & 1) * 2;
            float m = fmaxf(fmaxf(s[mt][0][hi], s[mt][0][hi + 1]), fmaxf(s[mt][1][hi], s[mt][1][hi + 1]));
            m = fmaxf(m, __shfl_xor_sync(0xffffffffu, m, 1));
            m = fmaxf(m, __shfl_xor_sync(0xffffffffu, m, 2));
            if (t == 0) stsf(sb + SM_MX + (8 * r + g) * 32 + w * 4, m);
        }
        bar_consumers();
        uint32_t pf[2][4];
#pragma unroll
        for (int r = 0; r < 4; r++) {
            const int mt = r >> 1, hi = r & 1;
            const float4 m0 = ldsf4(sb + SM_MX + (8 * r + g) * 32), m1 = ldsf4(sb + SM_MX + (8 * r + g) * 32 + 16);
            const float m = fmaxf(fmaxf(fmaxf(m0.x, m0.y), fmaxf(m0.z, m0.w)), fmaxf(fmaxf(m1.x, m1.y), fmaxf(m1.z, m1.w)));
            const uint32_t p0 = pack_bf16(ex2(s[mt][0][2 * hi] - m), ex2(s[mt][0][2 * hi + 1] - m));
            const uint32_t p1 = pack_bf16(ex2(s[mt][1][2 * hi] - m), ex2(s[mt][1][2 * hi + 1] - m));
            pf[mt][hi] = p0; pf[mt][2 + hi] = p1;
            float l = (bf_lo(p0) + bf_hi(p0)) + (bf_lo(p1) + bf_hi(p1));
            l += __shfl_xor_sync(0xffffffffu, l, 1);
            l += __shfl_xor_sync(0xffffffffu, l, 2);
            if (t == 0) stsf(sb + SM_SUM + (8 * r + g) * 32 + w * 4, l);
        }
        sts128(sb + SM_PF + (w * 2 + 0) * 512 + lane * 16, make_uint4(pf[0][0], pf[0][1], pf[0][2], pf[0][3]));
        sts128(sb + SM_PF + (w * 2 + 1) * 512 + lane * 16, make_uint4(pf[1][0], pf[1][1], pf[1][2], pf[1][3]));
        bar_consumers();
        if (w == 0) {
            const float4 m0 = ldsf4(sb + SM_MX + lane * 32), m1 = ldsf4(sb + SM_MX + lane * 32 + 16);
            const float4 l0 = ldsf4(sb + SM_SUM + lane * 32), l1 = ldsf4(sb + SM_SUM + lane * 32 + 16);
            const float m = fmaxf(fmaxf(fmaxf(m0.x, m0.y), fmaxf(m0.z, m0.w)), fmaxf(fmaxf(m1.x, m1.y), fmaxf(m1.z, m1.w)));
            const float l = ((l0.x + l0.y) + (l0.z + l0.w)) + ((l1.x + l1.y) + (l1.z + l1.w));
            gs->stat[lane][cta] = make_float2(m, l);
        }
        float o[2][8][4];
#pragma unroll
        for (int i = 0; i < 64; i++) (&o[0][0][0])[i] = 0.f;
        const uint32_t vr = w * 1024 + (lane & 7) * 128 + (lane & 8) * 1024;
        const uint32_t vx = ((lane >> 4) ^ (lane & 7)) << 4;
#pragma unroll
        for (int ks = 0; ks < 8; ks++) {
            const uint4 p0 = lds128(sb + SM_PF + (ks * 2 + 0) * 512 + lane * 16);
            const uint4 p1 = lds128(sb + SM_PF + (ks * 2 + 1) * 512 + lane * 16);
            const uint32_t vb = sb + slot_off(IT_C + ks) + vr;
#pragma unroll
            for (int n2 = 0; n2 < 4; n2++) {
                uint32_t b0, b1, b2, b3;
                ldsm4t(vb + (vx ^ (n2 << 5)), b0, b1, b2, b3);
                mma16816(o[0][2 * n2],     p0.x, p0.y, p0.z, p0.w, b0, b1);
                mma16816(o[0][2 * n2 + 1], p0.x, p0.y, p0.z, p0.w, b2, b3);
                mma16816(o[1][2 * n2],     p1.x, p1.y, p1.z, p1.w, b0, b1);
                mma16816(o[1][2 * n2 + 1], p1.x, p1.y, p1.z, p1.w, b2, b3);
            }
            __syncwarp();
            if (lane == 0) mbar_arrive(sb + SM_EMPTY + (IT_C + ks) * 8);
        }
        mbar_wait(sb + SM_FULL + (IT_K1 + 1 + (w * 3 >> 2)) * 8);
#pragma unroll
        for (int r = 0; r < 4; r++) {
            const int mt = r >> 1, hi = (r & 1) * 2;
            uint4* dst = gs->op[(8 * r + g) * 4 + (w >> 1)] + (cta >> 6) * 1024 + (w & 1) * 512 + (cta & 63) * 8;
#pragma unroll
            for (int u = 0; u < 2; u++) {
                uint4 v;
                v.x = pack_bf16(o[mt][4 * u][hi],     o[mt][4 * u][hi + 1]);
                v.y = pack_bf16(o[mt][4 * u + 1][hi], o[mt][4 * u + 1][hi + 1]);
                v.z = pack_bf16(o[mt][4 * u + 2][hi], o[mt][4 * u + 2][hi + 1]);
                v.w = pack_bf16(o[mt][4 * u + 3][hi], o[mt][4 * u + 3][hi + 1]);
                dst[(t + 4 * u) ^ (cta & 7)] = v;
            }
        }
        asm volatile("bar.arrive 3, 288;" ::: "memory");
    }

    k_item(1, sb + SM_SC + w * 512);

    auto v_item = [&](int ph) {
        float oa[4][4];
#pragma unroll
        for (int i = 0; i < 16; i++) (&oa[0][0])[i] = 0.f;
        uint32_t p[8];
#pragma unroll
        for (int i = 0; i < 8; i++) p[i] = lds32(sb + SM_PA + w * 256 + ph * 128 + i * 16 + t * 4);
        const int item = (ph ? IT_V1 : IT_V0) + w;
        mbar_wait(sb + SM_FULL + item * 8);
        const uint32_t base = sb + slot_off(item) + ((lane & 7) + ((lane >> 4) << 3)) * 256 + ((lane & 8) << 4);
#pragma unroll
        for (int c = 0; c < 8; c++) {
            const uint32_t a = base + ((c ^ (lane & 7)) << 4);
            const uint32_t mask = ((c == (g ^ (2 * t))) ? 0x0000ffffu : 0u) | ((c == (g ^ (2 * t + 1))) ? 0xffff0000u : 0u);
#pragma unroll
            for (int T = 0; T < 4; T++) {
                uint32_t r0, r1, r2, r3;
                ldsm4t(a + T * 4096, r0, r1, r2, r3);
                mma16816(oa[T], r0, r1, r2, r3, p[2 * T] & mask, p[2 * T + 1] & mask);
            }
        }
#pragma unroll
        for (int T = 0; T < 4; T += 2)
            st_rlx2(&gs->oa[win(ph, T >> 1)][ha][lane].x, pack_bf16(oa[T][0] + oa[T + 1][0], oa[T][1] + oa[T + 1][1]),
                    pack_bf16(oa[T][2] + oa[T + 1][2], oa[T][3] + oa[T + 1][3]));
        __syncwarp();
        if (lane == 0) mbar_arrive8(sb + SM_EMPTY + item * 8);
    };
    mbar_wait(sb + SM_EMPTY + (IT_K1 - 1) * 8);
    sts64(sb + SM_FIN + tid * 8, EMPTY, EMPTY);
    if (w == 0) sts32(sb + SM_CNT + lane * 4, 0u);
    v_item(0);

    mbar_wait(sb + SM_FULL + IT_OP * 8);
    if (w < 4) {
        const float2 st = ldsf2(sb + SM_MX + tid * 8);
        float m = st.x;
#pragma unroll
        for (int d = 1; d < 32; d <<= 1) m = fmaxf(m, __shfl_xor_sync(0xffffffffu, m, d));
        const uint32_t wb = pack_bf16(ex2(st.x - m), 0.f);
        float l = bf_lo(wb) * st.y;
#pragma unroll
        for (int d = 1; d < 32; d <<= 1) l += __shfl_xor_sync(0xffffffffu, l, d);
#pragma unroll
        for (int bb = 0; bb < 4; bb++) sts16(in0 + bb * 272 + tid * 2, bb == w ? (uint16_t)wb : (uint16_t)0);
        if (lane == 0) stsf(sb + SM_ML + 64 + w * 4, 1.f / l);
    }
    bar_consumers();
    tile_mma<true>(sb, IT_OP, in0, w, lane, acc);
    if (lane < 16) {
        const float inv = ldsf(sb + SM_ML + 64 + g * 4);
        const uint32_t v0 = pack_bf16(acc[0][0] * inv, acc[0][1] * inv), v1 = pack_bf16(acc[1][0] * inv, acc[1][1] * inv);
        st_rlx2(lat_dst, (t & 1) ? v1 : v0, (t & 1) ? v0 : v1);
    }

    uint2 st;
    if (w >= 4) st = ld_rlx2(&gs->sa[cta][lane]);
    v_item(1);
    if (w >= 4) {
        int it = 0;
        while (__any_sync(0xffffffffu, max(st.x, st.y) == EMPTY)) {
            st = ld_rlx2(&gs->sa[cta][lane]);
            if (++it > SPIN_LIMIT) __trap();
        }
        mbar_wait(sb + SM_FULL + (IT_V1 - 8 + max(8, (cta - ROT) >> 3 & 15)) * 8);
        const uint4* rec = (const uint4*)gs->oa[cta][g] + (w & 3) * 4 + t;
        uint4 r[4];
#pragma unroll
        for (int i = 0; i < 4; i++) ld_rlx4_if(r[i], rec + i * 128, true);
        float m = __uint_as_float(st.x);
#pragma unroll
        for (int d = 1; d < 32; d <<= 1) m = fmaxf(m, __shfl_xor_sync(0xffffffffu, m, d));
        float e = ex2(__uint_as_float(st.x) - m), l = e * __uint_as_float(st.y);
#pragma unroll
        for (int d = 1; d < 32; d <<= 1) l += __shfl_xor_sync(0xffffffffu, l, d);
        e /= l;
        float wt[4], a[8];
#pragma unroll
        for (int i = 0; i < 4; i++) wt[i] = __shfl_sync(0xffffffffu, e, g + 8 * i);
        while (refetch(r, [&](int i) { return rec + i * 128; }))
            if (++it > SPIN_LIMIT) __trap();
#pragma unroll
        for (int k = 0; k < 4; k++) {
            a[2 * k] = a[2 * k + 1] = 0.f;
#pragma unroll
            for (int i = 0; i < 4; i++) {
                const uint32_t v = k == 0 ? r[i].x : k == 1 ? r[i].y : k == 2 ? r[i].z : r[i].w;
                a[2 * k] = fmaf(wt[i], bf_lo(v), a[2 * k]);
                a[2 * k + 1] = fmaf(wt[i], bf_hi(v), a[2 * k + 1]);
            }
        }
#pragma unroll
        for (int n = 4; n > 0; n >>= 1) {
#pragma unroll
            for (int k = 0; k < n; k++) {
                const bool up = g & n;
                a[k] = (up ? a[k + n] : a[k]) + __shfl_xor_sync(0xffffffffu, up ? a[k] : a[k + n], 4 * n);
            }
        }
        const float y = __shfl_xor_sync(0xffffffffu, a[0], 2);
        if (!(lane & 2)) st_rlx(o_dst, pack_bf16(a[0], y));
    }

    if (w < 4) {
        const uint32_t lo = (g & 3) * 1024 + (g >> 2) * 512 + (g & 1) * 64 + t * 16;
        const int wd = ((lane >> 2 & 2) + (lane >> 4)) ^ (lane >> 1 & 3);
        const uint32_t base = sb + ((lane & 6) * 4 + wd * 2 + (lane & 1)) * 64 + (((w ^ wd) & 3) << 4);
        const uint64_t dst = __shfl_sync(0xffffffffu, (unsigned long long)ctx_dst, lane);
        mbar_wait(sb + SM_FULL + BAR_LAT * 8);
        uint4 a[8];
#pragma unroll
        for (int i = 0; i < 8; i++) a[i] = lds128(sb + SM_LAT + (lo ^ (i * 64)));
        int it = 0;
        while (refetch(a, [&](int i) { return (const char*)gs->lat[h] + (lo ^ (i * 64)); }))
            if (++it > SPIN_LIMIT) __trap();
        float v0 = 0.f, v1 = 0.f;
#pragma unroll
        for (int i = 0; i < 2; i++) {
            float c[4][4];
#pragma unroll
            for (int k = 0; k < 16; k++) (&c[0][0])[k] = 0.f;
            c[0][0] = v0; c[0][1] = v1;
            mbar_wait(sb + SM_FULL + (IT_WUV + i) * 8);
#pragma unroll
            for (int kk = 0; kk < 8; kk++) {
                uint32_t r0, r1, r2, r3;
                ldsm4t(base + slot_off(IT_WUV + i) + kk * 2048, r0, r1, r2, r3);
                mma16816(c[2 * (kk & 1)],     a[kk].x, a[kk].y, a[kk].z, a[kk].w, r0, r1);
                mma16816(c[2 * (kk & 1) + 1], a[kk].x, a[kk].y, a[kk].z, a[kk].w, r2, r3);
            }
            v0 = (c[0][0] + c[1][2]) + (c[2][0] + c[3][2]);
            v1 = (c[0][1] + c[1][3]) + (c[2][1] + c[3][3]);
            if (i == 0) { v0 = __shfl_xor_sync(0xffffffffu, v0, 16); v1 = __shfl_xor_sync(0xffffffffu, v1, 16); }
        }
        st_rlx_if(dst, pack_bf16(v0, v1), lane >= 16);
    }

    {
        const bool isB = slice >= 32;
        const int r = j & 1;
        const uint32_t cs = isB ? 256 : 64;
        const uint32_t xl = (isB ? t * 64 + (((g >> 1) ^ (t & 2)) << 4) : (g >> 1) * 256 + ((g & 2) * 2 + t) * 16) + (w >> 1) * 1024 + (w & 1) * 2 * cs;
        auto xoff = [&](int i) { return (i >> 1) * 4096 + (xl ^ ((i & 1) * cs)); };
        const char* src = (const char*)gs->x[slice >> 5][r * 16];
        uint32_t off[2];
#pragma unroll
        for (int u = 0; u < 2; u++) {
            const int tt = (lane & 7) >> 1, row = 8 * tt + 2 * ((2 * u + (lane >> 4) + tt) & 3) + (lane & 1);
            off[u] = sb + w * 2048 + row * 32 + ((((lane >> 3) ^ (row >> 2)) & 1) << 4);
        }
        uint32_t fin[2], rcv[2];
#pragma unroll
        for (int e = 0; e < 2; e++) {
            const uint32_t o = t * 16 + (e ^ (t >> 1)) * 8 + g;
            fin[e] = __shfl_sync(0xffffffffu, sb + SM_FIN + (w >> 1) * 512 + o * 8 + ((w ^ t) & 1) * 4, lane);
            rcv[e] = __shfl_sync(0xffffffffu, sb + SM_RCV + o * 4, lane);
        }
        const uint32_t cnt = __shfl_sync(0xffffffffu, sb + SM_CNT + lane * 4, lane), sum = __shfl_sync(0xffffffffu, sb + SM_FIN + lane * 16, lane);
        const uint32_t inc = __shfl_sync(0xffffffffu, lane, 1 + r), last = __shfl_sync(0xffffffffu, lane, 7 + 7 * r);
        const uint32_t snd = __shfl_sync(0xffffffffu, map_cta(sb + SM_RCV + lane * 8, 0), lane),
                       sbar = __shfl_sync(0xffffffffu, map_cta(sb + SM_LAST + 8 + (lane & 16), 0), lane & 15);
        const uint64_t dst = __shfl_sync(0xffffffffu, (unsigned long long)(out + (lane >> 3) * 1024 + slice * 16 + ((lane ^ (lane >> 2 & 4)) & 7) * 2), lane);
        uint32_t a[2][4][4];
        uint4 x[8];
        float c[4][4];
        auto load_w = [&](int i) {
            mbar_wait(i < 2 ? sb + SM_FULL + (IT_WO + i) * 8 : sb + SM_LAST + w * 16 + (i & 1) * 8);
#pragma unroll
            for (int q = 0; q < 4; q++)
                ldsm4t(slot_off(IT_WO + i) + off[q & 1] + (q >> 1) * 1024, a[i & 1][q][0], a[i & 1][q][1], a[i & 1][q][2], a[i & 1][q][3]);
        };
        auto mma_w = [&](int i) {
#pragma unroll
            for (int q = 0; q < 4; q++) {
                const uint4& b = x[2 * i + (q >> 1)];
                if (i == 0) c[q][0] = c[q][1] = c[q][2] = c[q][3] = 0.f;
                mma16816(c[q], a[i & 1][q][0], a[i & 1][q][1], a[i & 1][q][2], a[i & 1][q][3], (q & 1) ? b.z : b.x, (q & 1) ? b.w : b.y);
            }
        };
        load_w(0); load_w(1);
        mbar_wait(sb + SM_FULL + IT_X * 8);
#pragma unroll
        for (int i = 0; i < 8; i++) x[i] = lds128(sb + slot_off(IT_X) + xoff(i));
        int it = 0;
        while (true) {
            mma_w(0); mma_w(1);
            if (!refetch(x, [&](int i) { return src + xoff(i); })) break;
            if (++it > SPIN_LIMIT) __trap();
        }
        load_w(2);
        mma_w(2);
        load_w(3);
        uint32_t rank;
        const float pr[2] = {ldsf_if(rcv[0], w == 0 && r == 0), ldsf_if(rcv[1], w == 0 && r == 0)};
        mma_w(3);
#pragma unroll
        for (int e = 0; e < 2; e++) stv(fin[e], (((c[0][2 * e] + pr[e]) + c[1][2 * e]) + c[2][2 * e]) + c[3][2 * e]);
        float4 p[4];
        float s0, s1;
        auto add_up = [&]() {
#pragma unroll
            for (int k = 0; k < 4; k++) p[k] = ldv4(sum + k * 512);
            const float a0 = ((p[0].x + p[0].y) + (p[1].x + p[1].y)) + (p[2].x + p[2].y), b0 = p[3].x + p[3].y;
            const float a1 = ((p[0].z + p[0].w) + (p[1].z + p[1].w)) + (p[2].z + p[2].w), b1 = p[3].z + p[3].w;
            s0 = a0 + b0; s1 = a1 + b1;
            uint32_t nan;
            asm("{\n.reg .pred p;\nsetp.ne.u32 p, %5, 0;\nsetp.nan.or.f32 p, %1, %2, p;\nsetp.nan.or.f32 p, %3, %4, p;\nselp.u32 %0, 1, 0, p;\n}"
                : "=r"(nan) : "f"(a0), "f"(a1), "f"(b0), "f"(b1), "r"(r));
            return nan;
        };
        asm volatile("atom.relaxed.cta.shared.add.u32 %0, [%1], %2;" : "=r"(rank) : "r"(cnt), "r"(inc) : "memory");
        const uint32_t redo = add_up();
        st_if(dst, pack_bf16(s0, s1), rank == 7);
        if (!redo) return;
        const bool num = s0 == s0 && s1 == s1;
        st_async64_if(snd, s0, s1, sbar, rank == 14 && num);
        if (rank != last || num) return;
        auto mx = [](float4 q) { return max(max(__float_as_uint(q.x), __float_as_uint(q.y)), max(__float_as_uint(q.z), __float_as_uint(q.w))); };
        for (it = 0; max(max(mx(p[0]), mx(p[1])), max(mx(p[2]), mx(p[3]))) == EMPTY; it++) {
            add_up();
            if (it > SPIN_LIMIT) __trap();
        }
        if (r) st_async64_if(snd, s0, s1, sbar, true);
        else st_if(dst, pack_bf16(s0, s1), true);
    }
}

typedef CUresult (*EncodeTiledFn)(CUtensorMap*, CUtensorMapDataType, cuuint32_t, void*, const cuuint64_t*,
                                  const cuuint64_t*, const cuuint32_t*, const cuuint32_t*, CUtensorMapInterleave,
                                  CUtensorMapSwizzle, CUtensorMapL2promotion, CUtensorMapFloatOOBfill);

void encode_map(EncodeTiledFn enc, CUtensorMap* tm, const void* p, cuuint64_t cols, cuuint64_t rows,
                cuuint32_t brows, cuuint32_t bblk) {
    cuuint64_t dims[3] = {64, rows, cols / 64};
    cuuint64_t strides[2] = {cols * 2, 128};
    cuuint32_t box[3] = {64, brows, bblk};
    cuuint32_t es[3] = {1, 1, 1};
    enc(tm, CU_TENSOR_MAP_DATA_TYPE_BFLOAT16, 3, const_cast<void*>(p), dims, strides, box, es,
        CU_TENSOR_MAP_INTERLEAVE_NONE, CU_TENSOR_MAP_SWIZZLE_128B, CU_TENSOR_MAP_L2_PROMOTION_L2_256B,
        CU_TENSOR_MAP_FLOAT_OOB_FILL_NONE);
}

void encode_slice_map(EncodeTiledFn enc, CUtensorMap* tm, const void* p, cuuint64_t cols, cuuint64_t rows,
                      cuuint32_t bcols, cuuint32_t brows) {
    cuuint64_t dims[3] = {cols, 256, rows / 256};
    cuuint64_t strides[2] = {cols * 2, cols * 512};
    cuuint32_t box[3] = {bcols, brows, 1};
    cuuint32_t es[3] = {1, 1, 1};
    enc(tm, CU_TENSOR_MAP_DATA_TYPE_BFLOAT16, 3, const_cast<void*>(p), dims, strides, box, es, CU_TENSOR_MAP_INTERLEAVE_NONE,
        bcols == 16 ? CU_TENSOR_MAP_SWIZZLE_32B : CU_TENSOR_MAP_SWIZZLE_64B, CU_TENSOR_MAP_L2_PROMOTION_L2_128B,
        CU_TENSOR_MAP_FLOAT_OOB_FILL_NONE);
}

}

extern "C" void kernel_launch(void* const* d_in, const int* in_sizes, int n_in, void* d_out, int out_size) {
    (void)in_sizes; (void)n_in; (void)out_size;
    static EncodeTiledFn enc = nullptr;
    static Scratch* gs = nullptr;
    if (!enc) {
        cudaGetSymbolAddress((void**)&gs, g_scratch);
        void* fn = nullptr;
        cudaDriverEntryPointQueryResult qr;
        cudaGetDriverEntryPoint("cuTensorMapEncodeTiled", &fn, cudaEnableDefault, &qr);
        enc = (EncodeTiledFn)fn;
        cudaFuncSetAttribute(fused_decode_kernel, cudaFuncAttributeMaxDynamicSharedMemorySize, SM_END);
    }
    Maps maps;
    encode_map(enc, &maps.wuk, d_in[8], 4096, 512, 32, 2);
    encode_slice_map(enc, &maps.wuv, d_in[9], 4096, 512, 32, 128);
    encode_slice_map(enc, &maps.woB, d_in[10], 512, 4096, 16, 256);
    encode_slice_map(enc, &maps.woA, d_in[4], 512, 4096, 16, 256);
    encode_slice_map(enc, &maps.endB, d_in[10], 512, 4096, 16, 64);
    encode_slice_map(enc, &maps.endA, d_in[4], 512, 4096, 16, 64);
    encode_map(enc, &maps.ckv, d_in[6], 512, 16384, 8, 8);
    uint64_t first = (uint64_t)d_in[3];
    if ((uint32_t)first >= 0xffe00000u) first += 1 << 21;
    fused_decode_kernel<<<NCTA, NTHR, SM_END>>>(make_uint2((uint32_t)first, (uint32_t)(first >> 32)),
                                                (const __nv_bfloat16*)d_in[0], (const __nv_bfloat16*)d_in[5],
                                                (const __nv_bfloat16*)d_in[3], (const __nv_bfloat16*)d_in[7],
                                                (const __nv_bfloat16*)d_in[1] + 3072 * 128, (const __nv_bfloat16*)d_in[2] + 3072 * 128,
                                                (__nv_bfloat16*)d_out, gs, maps);
}
```

```cpp
#include <cuda_runtime.h>
#include <cuda_bf16.h>
#include <cuda.h>
#include <stdint.h>

namespace {

constexpr int NCTA   = 128;
constexpr int NSLOT  = 13;
constexpr int SLOT   = 16384;
constexpr int NITEM  = 56;
constexpr int NTHR   = 384;

constexpr int INFLIGHT = 4;
constexpr int PACE     = 638;
constexpr int LEAD     = 580;
constexpr int SECOND   = 1205;
constexpr int TAPER    = 272;
constexpr int OS0      = -115;
constexpr int OS1      = 242;
constexpr int OF0      = -252;
constexpr int OF1      = 471;
constexpr int OF2      = 1660;
constexpr int OF3      = 168;
constexpr int OA       = 38;
constexpr int XS       = 1294;
constexpr int XF       = 1600;
constexpr uint64_t ROWS_A = 0x170fdba954326ec8ull, ROWS_B = 0x7659fecb321048daull;
constexpr uint64_t inverse(uint64_t rows) {
    uint64_t r = 0;
    for (uint64_t n = 0; n < 16; n++) r |= n << (rows >> n * 4 & 15) * 4;
    return r;
}
constexpr uint64_t PIECE_A = inverse(ROWS_A), PIECE_B = inverse(ROWS_B);
constexpr int OPGAP    = 256;
constexpr int NWIN     = 4;
__device__ constexpr int win_pos(int k)  { return k == 0 ? 10 : k == 1 ? 20 : k == 2 ? 31 : 38; }
__device__ constexpr int win_late(int k) { return k == 0 ? 1850 : k == 1 ? 1765 : k == 2 ? 1860 : 1715; }
constexpr int GAIN     = 11;

constexpr int IT_WQB = 0, IT_WQA = 2, IT_WUK = 4, IT_K0 = 6, IT_Q = 14, IT_C = 16, IT_K1 = 24, IT_V0 = 32,
              IT_OP = 40, IT_V1 = 42, IT_WUV = 50, IT_WO = 52;
constexpr int IT_X = 56;
constexpr int BAR_LAT = 55;

constexpr int SM_FULL  = NSLOT * SLOT;
constexpr int SM_EMPTY = SM_FULL + 512;
constexpr int SM_IN0   = SM_EMPTY + 512;
constexpr int SM_IN1   = SM_IN0 + 1088;
constexpr int SM_SC    = SM_IN1 + 1088;
constexpr int SM_PA    = SM_SC + 4096;
constexpr int SM_PF    = SM_PA + 2048;
constexpr int SM_MX    = SM_PF + 8192;
constexpr int SM_ML    = SM_MX + 1024;
constexpr int SM_LAST  = SM_ML + 128;
constexpr int SM_CNT   = SM_LAST + 128;
constexpr int SM_RCV   = SM_CNT + 128;
constexpr int SM_PACE  = SM_RCV + 256;
constexpr int SM_END   = SM_PACE + 32;
constexpr int SM_LAT   = SM_PF + 4096;
constexpr int SM_FIN   = SM_SC;
constexpr int SM_SUM   = SM_IN0;
static_assert(SM_END <= 232448, "smem");

struct Maps { CUtensorMap wuk, wuv, woA, woB, ckv, endA, endB; };

struct Scratch {
    uint64_t late[16];
    unsigned cnt[NCTA][32];
    float    part[2][NCTA][512];
    uint32_t x[2][32][256];
    uint32_t lat[32][4][256];
    uint4    q[4][2048];
    uint4    op[NCTA][2048];
    float2   stat[32][128];
};
__device__ __align__(128) Scratch g_scratch;

constexpr int SPIN_LIMIT = 1 << 22;

__device__ __forceinline__ uint32_t smem_u32(const void* p) { return (uint32_t)__cvta_generic_to_shared(p); }
__device__ __forceinline__ void mbar_init(uint32_t bar, uint32_t cnt) {
    asm volatile("mbarrier.init.shared::cta.b64 [%0], %1;" ::"r"(bar), "r"(cnt) : "memory");
}
__device__ __forceinline__ void mbar_expect_tx(uint32_t bar, uint32_t bytes) {
    asm volatile("mbarrier.arrive.expect_tx.shared::cta.b64 _, [%0], %1;" ::"r"(bar), "r"(bytes) : "memory");
}
__device__ __forceinline__ void mbar_arrive(uint32_t bar) {
    asm volatile("mbarrier.arrive.shared::cta.b64 _, [%0];" ::"r"(bar) : "memory");
}
__device__ __forceinline__ void mbar_arrive8(uint32_t bar) {
    asm volatile("mbarrier.arrive.shared::cta.b64 _, [%0], 8;" ::"r"(bar) : "memory");
}
__device__ __forceinline__ void mbar_wait(uint32_t bar) {
    uint32_t done;
    int it = 0;
    do {
        asm volatile("{\n.reg .pred p;\nmbarrier.try_wait.parity.shared::cta.b64 p, [%1], 0;\nselp.u32 %0, 1, 0, p;\n}"
                     : "=r"(done) : "r"(bar) : "memory");
        if (++it > SPIN_LIMIT) __trap();
    } while (!done);
}
__device__ __forceinline__ uint32_t map_cta(uint32_t a, uint32_t rank) {
    uint32_t r; asm("mapa.shared::cluster.u32 %0, %1, %2;" : "=r"(r) : "r"(a), "r"(rank)); return r;
}
__device__ __forceinline__ void st_async64_if(uint32_t a, float x, float y, uint32_t bar, bool on) {
    asm volatile("{\n.reg .pred p;\nsetp.ne.u32 p, %4, 0;\n@p st.async.shared::cluster.mbarrier::complete_tx::bytes.v2.f32 [%0], {%1,%2}, [%3];\n}"
                 ::"r"(a), "f"(x), "f"(y), "r"(bar), "r"((uint32_t)on) : "memory");
}
__device__ __forceinline__ uint64_t evict_first() {
    uint64_t pol; asm volatile("createpolicy.fractional.L2::evict_first.b64 %0, 1.0;" : "=l"(pol)); return pol;
}
#define ELECT "{\n.reg .pred p;\nelect.sync _|p, 0xffffffff;\n@p "
__device__ __forceinline__ void bulk_load(uint32_t dst, const void* src, uint32_t bytes, uint32_t bar, uint64_t pol) {
    asm volatile(ELECT "cp.async.bulk.shared::cluster.global.mbarrier::complete_tx::bytes.L2::cache_hint [%0], [%1], %2, [%3], %4;\n}"
                 ::"r"(dst), "l"(src), "r"(bytes), "r"(bar), "l"(pol) : "memory");
}
__device__ __forceinline__ void bulk_load_nohint(uint32_t dst, const void* src, uint32_t bytes, uint32_t bar) {
    asm volatile("cp.async.bulk.shared::cluster.global.mbarrier::complete_tx::bytes [%0], [%1], %2, [%3];"
                 ::"r"(dst), "l"(src), "r"(bytes), "r"(bar) : "memory");
}
__device__ __forceinline__ void tma3d(uint32_t dst, const CUtensorMap* tm, int c0, int c1, int c2, uint32_t bar, uint64_t pol) {
    asm volatile(ELECT "cp.async.bulk.tensor.3d.shared::cluster.global.mbarrier::complete_tx::bytes.L2::cache_hint [%0], [%1, {%3, %4, %5}], [%2], %6;\n}"
                 ::"r"(dst), "l"(tm), "r"(bar), "r"(c0), "r"(c1), "r"(c2), "l"(pol) : "memory");
}
__device__ __forceinline__ void ldsm4(uint32_t a, uint32_t& r0, uint32_t& r1, uint32_t& r2, uint32_t& r3) {
    asm volatile("ldmatrix.sync.aligned.m8n8.x4.shared.b16 {%0,%1,%2,%3}, [%4];"
                 : "=r"(r0), "=r"(r1), "=r"(r2), "=r"(r3) : "r"(a) : "memory");
}
__device__ __forceinline__ void ldsm4t(uint32_t a, uint32_t& r0, uint32_t& r1, uint32_t& r2, uint32_t& r3) {
    asm volatile("ldmatrix.sync.aligned.m8n8.x4.trans.shared.b16 {%0,%1,%2,%3}, [%4];"
                 : "=r"(r0), "=r"(r1), "=r"(r2), "=r"(r3) : "r"(a) : "memory");
}
__device__ __forceinline__ void mma16816(float (&c)[4], uint32_t a0, uint32_t a1, uint32_t a2, uint32_t a3,
                                         uint32_t b0, uint32_t b1) {
    asm volatile("mma.sync.aligned.m16n8k16.row.col.f32.bf16.bf16.f32 {%0,%1,%2,%3}, {%4,%5,%6,%7}, {%8,%9}, {%0,%1,%2,%3};"
                 : "+f"(c[0]), "+f"(c[1]), "+f"(c[2]), "+f"(c[3])
                 : "r"(a0), "r"(a1), "r"(a2), "r"(a3), "r"(b0), "r"(b1));
}
__device__ __forceinline__ uint32_t lds32(uint32_t a) {
    uint32_t v; asm volatile("ld.shared.b32 %0, [%1];" : "=r"(v) : "r"(a) : "memory"); return v;
}
__device__ __forceinline__ float ldsf(uint32_t a) {
    float v; asm volatile("ld.shared.f32 %0, [%1];" : "=f"(v) : "r"(a) : "memory"); return v;
}
__device__ __forceinline__ float2 ldsf2(uint32_t a) {
    float2 v; asm volatile("ld.shared.v2.f32 {%0,%1}, [%2];" : "=f"(v.x), "=f"(v.y) : "r"(a) : "memory"); return v;
}
__device__ __forceinline__ float4 ldsf4(uint32_t a) {
    float4 v; asm volatile("ld.shared.v4.f32 {%0,%1,%2,%3}, [%4];" : "=f"(v.x), "=f"(v.y), "=f"(v.z), "=f"(v.w) : "r"(a) : "memory"); return v;
}
__device__ __forceinline__ uint4 lds128(uint32_t a) {
    uint4 v; asm volatile("ld.shared.v4.b32 {%0,%1,%2,%3}, [%4];" : "=r"(v.x), "=r"(v.y), "=r"(v.z), "=r"(v.w) : "r"(a) : "memory"); return v;
}
__device__ __forceinline__ float ldsf_if(uint32_t a, bool on) {
    float v = 0.f;
    asm volatile("{\n.reg .pred p;\nsetp.ne.u32 p, %2, 0;\n@p ld.shared.f32 %0, [%1];\n}" : "+f"(v) : "r"(a), "r"((uint32_t)on) : "memory");
    return v;
}
__device__ __forceinline__ float4 ldv4(uint32_t a) {
    float4 v; asm volatile("ld.volatile.shared.v4.f32 {%0,%1,%2,%3}, [%4];" : "=f"(v.x), "=f"(v.y), "=f"(v.z), "=f"(v.w) : "r"(a) : "memory"); return v;
}
__device__ __forceinline__ void stv(uint32_t a, float v) { asm volatile("st.volatile.shared.f32 [%0], %1;" ::"r"(a), "f"(v) : "memory"); }
__device__ __forceinline__ void sts16(uint32_t a, uint16_t v) { asm volatile("st.shared.b16 [%0], %1;" ::"r"(a), "h"(v) : "memory"); }
__device__ __forceinline__ void sts32(uint32_t a, uint32_t v) { asm volatile("st.shared.b32 [%0], %1;" ::"r"(a), "r"(v) : "memory"); }
__device__ __forceinline__ void stsf(uint32_t a, float v) { asm volatile("st.shared.f32 [%0], %1;" ::"r"(a), "f"(v) : "memory"); }
__device__ __forceinline__ void sts64(uint32_t a, uint32_t x, uint32_t y) {
    asm volatile("st.shared.v2.b32 [%0], {%1,%2};" ::"r"(a), "r"(x), "r"(y) : "memory");
}
__device__ __forceinline__ void sts128(uint32_t a, uint4 v) {
    asm volatile("st.shared.v4.b32 [%0], {%1,%2,%3,%4};" ::"r"(a), "r"(v.x), "r"(v.y), "r"(v.z), "r"(v.w) : "memory");
}
__device__ __forceinline__ uint32_t pack_bf16(float lo, float hi) {
    uint32_t r; asm("cvt.rn.bf16x2.f32 %0, %1, %2;" : "=r"(r) : "f"(hi), "f"(lo)); return r;
}
__device__ __forceinline__ float bf_lo(uint32_t v) { return __uint_as_float(v << 16); }
__device__ __forceinline__ float bf_hi(uint32_t v) { return __uint_as_float(v & 0xffff0000u); }
__device__ __forceinline__ float ex2(float x) { float y; asm("ex2.approx.ftz.f32 %0, %1;" : "=f"(y) : "f"(x)); return y; }
__device__ __forceinline__ uint32_t timer_ns() { uint32_t t; asm volatile("mov.u32 %0, %%globaltimer_lo;" : "=r"(t)); return t; }
__device__ __forceinline__ void bar_consumers() { asm volatile("bar.sync 1, 256;" ::: "memory"); }

__device__ __forceinline__ uint32_t tagf(float v, uint32_t tag) { return (__float_as_uint(v) & 0xffffff00u) | tag; }
__device__ __forceinline__ uint2 ld_rlx2(const void* p) {
    uint64_t v; asm volatile("ld.relaxed.gpu.global.b64 %0, [%1];" : "=l"(v) : "l"(p) : "memory");
    return make_uint2((uint32_t)v, (uint32_t)(v >> 32));
}
__device__ __forceinline__ float untag(uint32_t v) { return __uint_as_float(v & 0xffffff00u); }

__device__ __forceinline__ uint32_t slot_off(int item) { return (uint32_t)(item % NSLOT) * SLOT; }

template <bool TRANS, bool TMA = true>
__device__ __forceinline__ void tile_mma(uint32_t sb, int item, uint32_t in, int w, int lane, float (&acc)[2][2]) {
    const int g = lane >> 2, t = lane & 3;
    float c[4][4];
#pragma unroll
    for (int i = 0; i < 16; i++) (&c[0][0])[i] = 0.f;
    uint32_t a[16];
    const uint32_t ia = in + (g & 3) * 272 + t * 4;
#pragma unroll
    for (int i = 0; i < 16; i++) a[i] = lds32(ia + i * 16);
    const uint32_t s0 = sb + slot_off(item), s1 = sb + slot_off(item + 1);
    if (TRANS) {
        const int r = (lane & 7) + (lane & 8);
        const int ch = 2 * (w & 3) + (lane >> 4);
        const uint32_t off = (TMA ? (w >> 2) * 8192 + r * 128 : (w >> 2) * 128 + r * 256) + ((ch ^ (lane & 7)) << 4);
#pragma unroll
        for (int kk = 0; kk < 8; kk++) {
            if (TMA && (kk & 3) == 0) mbar_wait(sb + SM_FULL + (item + (kk >> 2)) * 8);
            uint32_t r0, r1, r2, r3;
            ldsm4t(((kk >> 2) ? s1 : s0) + off + (kk & 3) * (TMA ? 2048 : 4096), r0, r1, r2, r3);
            mma16816(c[2 * (kk & 1)],     a[2 * kk], 0u, a[2 * kk + 1], 0u, r0, r1);
            mma16816(c[2 * (kk & 1) + 1], a[2 * kk], 0u, a[2 * kk + 1], 0u, r2, r3);
        }
    } else {
        mbar_wait(sb + SM_FULL + (item + (w >> 2)) * 8);
        const int r = 16 * (w & 3) + (lane & 7) + ((lane >> 4) << 3);
        const uint32_t base = ((w >> 2) ? s1 : s0) + (r & 32) * 128 + r * 128 + ((((lane >> 3) & 1) ^ (lane & 7)) << 4);
#pragma unroll
        for (int kk = 0; kk < 8; kk++) {
            uint32_t r0, r1, r2, r3;
            ldsm4((base ^ ((kk & 3) << 5)) + (kk >> 2) * 4096, r0, r1, r2, r3);
            mma16816(c[2 * (kk & 1)],     a[2 * kk], 0u, a[2 * kk + 1], 0u, r0, r1);
            mma16816(c[2 * (kk & 1) + 1], a[2 * kk], 0u, a[2 * kk + 1], 0u, r2, r3);
        }
    }
    __syncwarp();
    if (lane == 0) {
        mbar_arrive(sb + SM_EMPTY + item * 8);
        mbar_arrive(sb + SM_EMPTY + (item + 1) * 8);
    }
    acc[0][0] = c[0][0] + c[2][0]; acc[0][1] = c[0][1] + c[2][1];
    acc[1][0] = c[1][0] + c[3][0]; acc[1][1] = c[1][1] + c[3][1];
}

__device__ __forceinline__ void publish(float* dst, int w, int lane, const float (&acc)[2][2], uint32_t tag) {
    if (lane < 16)
        asm volatile("st.relaxed.gpu.global.v4.b32 [%0], {%1,%2,%3,%4};" ::"l"(dst + w * 64 + lane * 4),
                     "r"(tagf(acc[0][0], tag)), "r"(tagf(acc[0][1], tag)), "r"(tagf(acc[1][0], tag)), "r"(tagf(acc[1][1], tag)) : "memory");
}

__device__ __forceinline__ void gather(const float* part, uint32_t in, int tid, uint32_t tag) {
    const float* p = part + tid * 2;
    uint2 v0, v1, v2, v3;
    int it = 0;
    while (true) {
        v0 = ld_rlx2(p); v1 = ld_rlx2(p + 512); v2 = ld_rlx2(p + 1024); v3 = ld_rlx2(p + 1536);
        uint32_t bad = ((v0.x ^ tag) | (v0.y ^ tag) | (v1.x ^ tag) | (v1.y ^ tag) |
                        (v2.x ^ tag) | (v2.y ^ tag) | (v3.x ^ tag) | (v3.y ^ tag)) & 0xffu;
        if (__all_sync(0xffffffffu, bad == 0)) break;
        if (++it > SPIN_LIMIT) __trap();
    }
    float x = (untag(v0.x) + untag(v1.x)) + (untag(v2.x) + untag(v3.x));
    float y = (untag(v0.y) + untag(v1.y)) + (untag(v2.y) + untag(v3.y));
    sts32(in + ((tid >> 3) & 3) * 272 + (tid >> 5) * 32 + (tid & 1) * 16 + (tid & 6) * 2, pack_bf16(x, y));
    bar_consumers();
}

constexpr uint32_t EMPTY = 0xffffffffu;
__device__ __forceinline__ void st_rlx(uint32_t* p, uint32_t v) {
    asm volatile("st.relaxed.gpu.global.b32 [%0], %1;" ::"l"(p), "r"(v) : "memory");
}
__device__ __forceinline__ void st_rlx_if(uint64_t p, uint32_t v, bool on) {
    asm volatile("{\n.reg .pred p;\nsetp.ne.u32 p, %2, 0;\n@p st.relaxed.gpu.global.b32 [%0], %1;\n}" ::"l"(p), "r"(v), "r"((uint32_t)on) : "memory");
}
__device__ __forceinline__ void st_if(uint64_t p, uint32_t v, bool on) {
    asm volatile("{\n.reg .pred p;\nsetp.ne.u32 p, %2, 0;\n@p st.global.b32 [%0], %1;\n}" ::"l"(p), "r"(v), "r"((uint32_t)on) : "memory");
}
__device__ __forceinline__ void st_rlx2(uint32_t* p, uint32_t v0, uint32_t v1) {
    asm volatile("st.relaxed.gpu.global.v2.b32 [%0], {%1,%2};" ::"l"(p), "r"(v0), "r"(v1) : "memory");
}
__device__ __forceinline__ void ld_rlx4_if(uint4& v, const void* p, bool need) {
    asm volatile("{\n.reg .pred p;\nsetp.ne.u32 p, %5, 0;\n@p ld.relaxed.gpu.global.v4.b32 {%0,%1,%2,%3}, [%4];\n}"
                 : "+r"(v.x), "+r"(v.y), "+r"(v.z), "+r"(v.w) : "l"(p), "r"((uint32_t)need) : "memory");
}

template <class F>
__device__ __forceinline__ bool refetch(uint4 (&x)[8], F addr) {
    uint32_t m[8], m0 = 0;
#pragma unroll
    for (int i = 0; i < 8; i++) {
        m[i] = max(max(x[i].x, x[i].y), max(x[i].z, x[i].w));
        m0 = max(m0, m[i]);
    }
    if (!__any_sync(0xffffffffu, m0 == EMPTY)) return false;
#pragma unroll
    for (int i = 0; i < 8; i++) ld_rlx4_if(x[i], addr(i), m[i] == EMPTY);
    return true;
}

__device__ __forceinline__ unsigned read_counter(const unsigned* cnt) {
    unsigned v;
    asm volatile("ld.relaxed.gpu.global.u32 %0, [%1];" : "=r"(v) : "l"(cnt) : "memory");
    return v;
}
__device__ __forceinline__ unsigned epoch_of(unsigned cnt) {
    asm volatile("" : "+r"(cnt) :: "memory");
    return cnt + 1;
}
__device__ __forceinline__ uint32_t epoch_tag(unsigned epoch) { return (epoch & 0x7fu) | 0x80u; }

__device__ __forceinline__ void signal_and_wait(unsigned* cnt, unsigned target, int lane) {
    if (lane == 0) asm volatile("red.release.gpu.global.add.u32 [%0], 1;" ::"l"(cnt) : "memory");
    int it = 0;
    while (true) {
        unsigned v;
        asm volatile("ld.acquire.gpu.global.u32 %0, [%1];" : "=r"(v) : "l"(cnt) : "memory");
        if (__all_sync(0xffffffffu, (int)(v - target) >= 0)) break;
        if (++it > SPIN_LIMIT) __trap();
    }
    asm volatile("fence.proxy.async.global;" ::: "memory");
}

__global__ void __cluster_dims__(2, 1, 1) __launch_bounds__(NTHR, 1)
fused_decode_kernel(const uint2 first, const __nv_bfloat16* __restrict__ xA, const __nv_bfloat16* __restrict__ xB,
                    const __nv_bfloat16* __restrict__ wqB, const __nv_bfloat16* __restrict__ wqA,
                    const __nv_bfloat16* __restrict__ Kc, const __nv_bfloat16* __restrict__ Vc,
                    __nv_bfloat16* __restrict__ out, Scratch* gs, const __grid_constant__ Maps maps) {
    extern __shared__ __align__(1024) unsigned char smem_raw[];
    const uint32_t sb = smem_u32(smem_raw);
    const int tid = threadIdx.x, lane = tid & 31;
    const int cta = blockIdx.x, h = cta >> 2, j = cta & 3;
    const size_t kv_off = (size_t)blockIdx.x * 4096 * 128;
    asm volatile("{\n.reg .b32 l;\n.reg .b64 a;\nmad.lo.u32 l, %2, 32, %0;\nmov.b64 a, {l, %1};\nprefetch.global.L2 [a];\n}"
                 ::"r"(first.x + blockIdx.x * (NTHR * 32)), "r"(first.y), "r"(threadIdx.x) : "memory");
    const uint32_t trow = threadIdx.x >> 4;
    const uint32_t tile_src = trow * (8192 - 256) + (threadIdx.x * 16 + ((blockIdx.x * 0x100040u) & 0x301f00u));
    const uint32_t tile_dst = sb + ((threadIdx.x ^ (trow & 7)) << 4);
    auto lsu_piece = [&](int k) {
#pragma unroll
        for (int q = 2 * k; q < 2 * k + 2; q++)
            asm volatile("cp.async.cg.shared.global [%0], [%1], 16;" ::"r"(tile_dst + q * 4096),
                         "l"(reinterpret_cast<const char*>((k < 4 ? wqB : wqA) + (q & 7) * 16 * 4096) + tile_src) : "memory");
        if ((k & 3) == 3) asm volatile("cp.async.commit_group;" ::: "memory");
    };
    if (tid < 256) {
#pragma unroll
        for (int k = 0; k < 4; k++) lsu_piece(k);
    }
    const uint32_t tz = timer_ns() - LEAD;
    unsigned cnt1;
    if (tid < 256) cnt1 = read_counter(gs->cnt[blockIdx.x]);
    uint4 xv;
    if (tid < 128) {
        const __nv_bfloat16* x = (tid < 64 ? xB : xA) + ((tid >> 4) & 3) * 512 + j * 128 + (tid & 15) * 8;
        xv = __ldg(reinterpret_cast<const uint4*>(x));
    }
    const int w = __shfl_sync(0xffffffffu, tid >> 5, 0);
    const int pr = cta >> 1;
    const int slice = pr < 4 ? pr : pr < 36 ? 4 + ((pr - 4) & 7) * 4 + ((pr - 4) >> 3) : 36 + (pr - 36) % 7 * 4 + (pr - 36) / 7;

    if (w >= 8) {
        if (lane == 0) {
            const uint32_t full = sb + SM_FULL + (IT_WUK + (w & 3) * 14) * 8, empty = sb + SM_EMPTY + (w & 3) * 13 * 8,
                           last = sb + SM_LAST + (w & 3) * 32;
#pragma unroll
            for (int i = 0; i < 14; i++) mbar_init(full + i * 8, 1);
#pragma unroll
            for (int i = 0; i < 13; i++) mbar_init(empty + i * 8, 8);
#pragma unroll
            for (int i = 0; i < 4; i++) mbar_init(last + i * 8, 1);
#pragma unroll
            for (int i = 0; i < 14; i++) {
                const int b = IT_WUK + 42 + i;
                mbar_expect_tx(full + i * 8, (w == 10 && b - 14 == IT_OP) ? SLOT + 1024 : (w == 11 && b == BAR_LAT) ? 4096 : SLOT);
            }
#pragma unroll
            for (int i = 0; i < 4; i++) mbar_expect_tx(last + i * 8, i == 1 && w == 8 && !(j & 1) ? 2048 + 256 : 2048);
            asm volatile("fence.mbarrier_init.release.cluster;" ::: "memory");
            if (w == 10) sts64(sb + SM_PACE, tz, PACE * 16);
        }
        asm volatile("bar.sync 2, 128;" ::: "memory");
        asm volatile("bar.arrive 4, 384;" ::: "memory");
    }
    if (w == 10) {
        if (lane == 0) {
            int slope = 0;
#pragma unroll
            for (int k = 0; k < NWIN; k++) {
                const int c = win_pos(k);
                uint32_t acc = 0;
#pragma unroll
                for (int p = c; p < c + 4; p++) {
                    mbar_wait(sb + SM_FULL + (p < IT_Q ? p : p < IT_OP - 2 ? p + 2 : p + 4) * 8);
                    acc += timer_ns() - tz - p * PACE - ((p * slope) >> 4);
                }
                if (k == 0) mbar_wait(sb + SM_FULL + IT_Q * 8);
                asm volatile("red.relaxed.gpu.global.add.u64 [%0], %1;" ::"l"(&gs->late[k]),
                             "l"((uint64_t)tz << 32 | (1u << 24) + min(acc >> 2, 65535u)) : "memory");
                uint2 v;
                int it = 0;
                do { v = ld_rlx2(&gs->late[k]); } while ((v.x >> 24) != NCTA && ++it < 1000);
                if (it == 1000) break;
                const int late = (v.x & 0xffffffu) / NCTA;
                slope = max(-320, min(480, slope + (late - win_late(k)) * (GAIN * 2) / (2 * c + 3)));
                sts64(sb + SM_PACE, k < NWIN - 1 ? tz : tz + (int)(v.y - tz * NCTA) / NCTA, PACE * 16 + slope);
            }
        }
        return;
    }
    if (w >= 8) {
        auto wait_due = [&](uint32_t p, uint32_t shift) {
            uint32_t a, b;
            do {
                asm volatile("ld.volatile.shared.v2.b32 {%0,%1}, [%2];" : "=r"(a), "=r"(b) : "r"(sb + SM_PACE) : "memory");
            } while (__all_sync(0xffffffffu, (int)(timer_ns() - (a + ((p * b) >> 4) + shift)) < 0));
        };
        if (w != 9) {
            const int half = w & 1;
            const uint64_t pol = evict_first();
            const uint32_t rows = (slice < 32 ? ROWS_A : ROWS_B) >> ((j & 1) * 32 + half * 4);
            int slot = IT_WUK, tail = IT_WUK - INFLIGHT;
            uint32_t np = IT_WUK, shift = half ? PACE / 4 : -(PACE / 4);
#pragma unroll 1
            for (int i = IT_WUK; i < NITEM; i++) {
                const uint32_t dst = sb + slot * SLOT + half * (SLOT / 2), bar = sb + SM_FULL + i * 8;
                if (++slot == NSLOT) slot = 0;
                if ((i & ~1) == IT_Q || (i & ~1) == IT_OP) continue;
                const bool ckv = i >= IT_C && i < IT_K1, wo = i >= IT_WO;
                const bool tiled = ckv || i < IT_K0 || i >= IT_WUV;
                const CUtensorMap* tm = &maps.wuk + (i < IT_K0 ? 0 : ckv ? 4 : wo ? 2 + (slice >> 5) : 1);
                const int c0 = wo ? (slice & 31) * 16 : i >= IT_WUV ? cta * 32 : 0;
                const int c1 = i < IT_K0 ? j * 128 + (i & 1) * 64 + half * 32 : ckv ? cta * 128 + (i - IT_C) * 16 + half * 8 : wo ? 0 : half * 128;
                const int c2 = i < IT_K0 ? h * 2 : ckv ? 0 : wo ? rows >> (i - IT_WO) * 8 & 15 : i & 1;
                const int c = i < IT_Q ? i - IT_K0 : i < IT_V0 ? i - IT_K1 + 8 : i < IT_OP ? i - IT_V0 : i - IT_V1 + 8;
                const __nv_bfloat16* src = (i < IT_V0 ? Kc : Vc) + kv_off + (size_t)((c ^ (j & 1) * 7) * 2 + half) * (SLOT / 4);
                if (i >= NSLOT) mbar_wait(sb + SM_EMPTY + (i - NSLOT) * 8);
                if (tail >= IT_WUK && !wo) mbar_wait(sb + SM_FULL + tail * 8);
                ++tail;
                if (tail == IT_Q || tail == IT_OP) tail += 2;
                if (wo) {
                    const int n = (i - IT_WO) * 2 + half;
                    np = IT_WO - 4;
                    shift = TAPER + ((j & 1) ? OS0 + n * OS1 : n < 4 ? OF0 + n * OF1 : OF2 + (n - 4) * OF3 + (slice < 32 ? OA : 0));
                }
                wait_due(np, shift);
                ++np;
                if (i == IT_WUV - 1) shift += TAPER;
                if (i >= NITEM - 2) {
#pragma unroll
                    for (int q = 0; q < 4; q++)
                        tma3d(dst + q * 2048, tm + 3, c0, q * 64, c2, sb + SM_LAST + half * 64 + q * 16 + (i & 1) * 8, pol);
                }
                else if (tiled) tma3d(dst, tm, c0, c1, c2, bar, pol);
                else bulk_load(dst, src, SLOT / 2, bar, pol);
            }
        } else {
            if (lane < sizeof(Maps) / 128) asm volatile("prefetch.tensormap [%0];" ::"l"(&maps.wuk + lane) : "memory");
            cnt1 = read_counter(gs->cnt[blockIdx.x]);
            asm volatile("bar.sync 3, 288;" ::: "memory");
            const unsigned epoch = epoch_of(cnt1);
            if (lane == 0) st_rlx(gs->cnt[cta], epoch);
            signal_and_wait(&gs->cnt[0][1], epoch * NCTA, lane);
            if (lane == 0) {
                const uint4* q = gs->q[cta >> 5];
                bulk_load_nohint(sb + slot_off(IT_Q), q, SLOT, sb + SM_FULL + IT_Q * 8);
                bulk_load_nohint(sb + slot_off(IT_Q + 1), q + 1024, SLOT, sb + SM_FULL + (IT_Q + 1) * 8);
            }
            asm volatile("bar.sync 3, 288;" ::: "memory");
            signal_and_wait(&gs->cnt[0][2], epoch * NCTA, lane);
            mbar_wait(sb + SM_EMPTY + (IT_OP - NSLOT) * 8);
            mbar_wait(sb + SM_EMPTY + (IT_OP + 1 - NSLOT) * 8);
            if (lane == 0) {
                const uint4* op = gs->op[cta];
                bulk_load_nohint(sb + SM_MX, gs->stat[h], 1024, sb + SM_FULL + IT_OP * 8);
                uint32_t t1 = timer_ns();
#pragma unroll 1
                for (int i = 0; i < 8; i++) {
                    while ((int)(timer_ns() - t1) < 0) {}
                    t1 += OPGAP;
                    bulk_load_nohint(sb + slot_off(IT_OP) + i * 4096, op + i * 256, 4096, sb + SM_FULL + (IT_OP + i / 4) * 8);
                }
            }
            mbar_wait(sb + SM_FULL + (IT_V1 + 4) * 8);
            if (lane == 0) bulk_load_nohint(sb + SM_LAT, gs->lat[h], 4096, sb + SM_FULL + BAR_LAT * 8);
            mbar_wait(sb + SM_EMPTY + (IT_X - NSLOT) * 8);
            mbar_wait(sb + SM_FULL + (IT_WUV + 1) * 8);
            wait_due(IT_WO - 4, TAPER + ((j & 1) ? XS : XF));
            if (lane == 0) bulk_load_nohint(sb + slot_off(IT_X), gs->x[slice >> 5][(j & 1) * 16], SLOT, sb + SM_FULL + IT_X * 8);
        }
        return;
    }

    const int g = lane >> 2, t = lane & 3;
    const uint32_t in0 = sb + SM_IN0, in1 = sb + SM_IN1;
    const int ba = cta >> 5, ha = cta & 31;
    auto xpos = [](uint64_t piece, int head) { return (int)(piece >> (head >> 1) * 4 & 15) * 2 + (head & 1); };
    uint32_t* const ctx_dst = &gs->x[1][xpos(PIECE_B, h)][(j * 4 + (w & 3)) * 16 + ((g ^ (w & 2)) & 3) * 4 + ((t - w) & 3)];
    uint32_t* const o_dst = &gs->x[0][xpos(PIECE_A, ha)][ba * 64 + ((tid & 60) ^ ((ba & 1) * 16)) + ((t - g) & 3)];
    uint32_t* const lat_dst = &gs->lat[h][g & 3][j * 64 + ((w >> 1) ^ (g & 1)) * 16 + t * 4 + ((w * 2 ^ t) & 2)];
    {
#pragma unroll
        for (int k = 4; k < 8; k++) {
            while (__all_sync(0xffffffffu, (int)(timer_ns() - (tz + SECOND + (k - 4) * (PACE / 2))) < 0)) {}
            lsu_piece(k);
        }
        if (lane < 16) st_rlx2(lat_dst, EMPTY, EMPTY);
        if (lane >= 16 && w < 4) st_rlx(ctx_dst, EMPTY);
        if (w >= 6) st_rlx(o_dst, EMPTY);
        if (cta == 0 && w == 5) st_rlx((uint32_t*)gs->late + lane, 0u);
        if (tid < 128) sts128((tid < 64 ? in0 : in1) + ((tid >> 4) & 3) * 272 + (tid & 15) * 16, xv);
        asm volatile("cp.async.wait_group 1;" ::: "memory");
    }
    asm volatile("bar.sync 4, 384;" ::: "memory");
    const uint32_t tag = epoch_tag(epoch_of(cnt1));

    float acc[2][2];
    tile_mma<true, false>(sb, IT_WQB, in0, w, lane, acc);
    publish(gs->part[0][cta], w, lane, acc, tag);
    asm volatile("cp.async.wait_group 0;" ::: "memory");
    bar_consumers();
    tile_mma<true, false>(sb, IT_WQA, in1, w, lane, acc);
    publish(gs->part[1][cta], w, lane, acc, tag);
    bar_consumers();

    const float SC = 0.08838834764831845f * 1.4426950408889634f;
    gather(gs->part[0][h * 4], in0, tid, tag);
    tile_mma<false>(sb, IT_WUK, in0, w, lane, acc);
    if (lane < 16) {
        uint32_t* q = reinterpret_cast<uint32_t*>(gs->q[g]) + (2 * j + (w >> 2)) * 1024 + h * 32 + t;
        const int ch = 2 * (w & 3);
        q[((ch) ^ (h & 7)) * 4]     = pack_bf16(acc[0][0] * SC, acc[0][1] * SC);
        q[((ch + 1) ^ (h & 7)) * 4] = pack_bf16(acc[1][0] * SC, acc[1][1] * SC);
    }
    __syncwarp();
    asm volatile("bar.arrive 3, 288;" ::: "memory");
    gather(gs->part[1][ha * 4], in1, tid, tag);

    uint32_t qf[16];
#pragma unroll
    for (int c = 0; c < 8; c++) {
        qf[2 * c]     = lds32(in1 + ba * 272 + ((c ^ g) << 4) + t * 4);
        qf[2 * c + 1] = lds32(in1 + ba * 272 + 128 + ((c ^ g) << 4) + t * 4);
    }
    const uint32_t sc_w = sb + SM_SC + w * 512;
    auto k_item = [&](int item, uint32_t sc) {
        mbar_wait(sb + SM_FULL + item * 8);
        const uint32_t base = sb + slot_off(item) + ((lane & 7) + (lane & 8)) * 256 + ((lane >> 4) << 7);
        float s[4][4];
#pragma unroll
        for (int T = 0; T < 4; T++) { s[T][0] = s[T][1] = s[T][2] = s[T][3] = 0.f; }
#pragma unroll
        for (int c = 0; c < 8; c++) {
            const uint32_t a = base + ((c ^ (lane & 7)) << 4);
#pragma unroll
            for (int T = 0; T < 4; T++) {
                uint32_t r0, r1, r2, r3;
                ldsm4(a + T * 4096, r0, r1, r2, r3);
                mma16816(s[T], r0, r1, r2, r3, qf[2 * c], qf[2 * c + 1]);
            }
        }
        __syncwarp();
        if (lane == 0) mbar_arrive8(sb + SM_EMPTY + item * 8);
        if (t == (g >> 1)) {
#pragma unroll
            for (int T = 0; T < 4; T++) {
                stsf(sc + (16 * T + g) * 4,     (g & 1) ? s[T][1] : s[T][0]);
                stsf(sc + (16 * T + g + 8) * 4, (g & 1) ? s[T][3] : s[T][2]);
            }
        }
    };
    k_item(IT_K0 + w, sc_w);

    {
        float s[2][2][4];
#pragma unroll
        for (int i = 0; i < 16; i++) (&s[0][0][0])[i] = 0.f;
        mbar_wait(sb + SM_FULL + IT_Q * 8);
        mbar_wait(sb + SM_FULL + (IT_Q + 1) * 8);
        mbar_wait(sb + SM_FULL + (IT_C + w) * 8);
        const uint32_t cb0 = sb + slot_off(IT_C + w) + (lane & 7) * 128 + (lane >> 4) * 8192;
        const uint32_t cx = (((lane >> 3) & 1) ^ (lane & 7)) << 4;
        const uint32_t qr = ((lane & 7) + (lane & 8)) * 128;
        const uint32_t qx = ((lane >> 4) ^ (lane & 7)) << 4;
#pragma unroll
        for (int cb = 0; cb < 8; cb++) {
            const uint32_t qb = sb + slot_off(IT_Q + (cb >> 2)) + (cb & 3) * 4096 + qr;
#pragma unroll
            for (int k4 = 0; k4 < 4; k4++) {
                uint32_t b0, b1, b2, b3, a0, a1, a2, a3;
                ldsm4(cb0 + cb * 1024 + (cx ^ (k4 << 5)), b0, b1, b2, b3);
                ldsm4(qb + (qx ^ (k4 << 5)), a0, a1, a2, a3);
                mma16816(s[0][0], a0, a1, a2, a3, b0, b1);
                mma16816(s[0][1], a0, a1, a2, a3, b2, b3);
                ldsm4(qb + 2048 + (qx ^ (k4 << 5)), a0, a1, a2, a3);
                mma16816(s[1][0], a0, a1, a2, a3, b0, b1);
                mma16816(s[1][1], a0, a1, a2, a3, b2, b3);
            }
        }
        __syncwarp();
        if (lane == 0) { mbar_arrive(sb + SM_EMPTY + IT_Q * 8); mbar_arrive(sb + SM_EMPTY + (IT_Q + 1) * 8); }
#pragma unroll
        for (int r = 0; r < 4; r++) {
            const int mt = r >> 1, hi = (r & 1) * 2;
            float m = fmaxf(fmaxf(s[mt][0][hi], s[mt][0][hi + 1]), fmaxf(s[mt][1][hi], s[mt][1][hi + 1]));
            m = fmaxf(m, __shfl_xor_sync(0xffffffffu, m, 1));
            m = fmaxf(m, __shfl_xor_sync(0xffffffffu, m, 2));
            if (t == 0) stsf(sb + SM_MX + (8 * r + g) * 32 + w * 4, m);
        }
        bar_consumers();
        uint32_t pf[2][4];
#pragma unroll
        for (int r = 0; r < 4; r++) {
            const int mt = r >> 1, hi = r & 1;
            const float4 m0 = ldsf4(sb + SM_MX + (8 * r + g) * 32), m1 = ldsf4(sb + SM_MX + (8 * r + g) * 32 + 16);
            const float m = fmaxf(fmaxf(fmaxf(m0.x, m0.y), fmaxf(m0.z, m0.w)), fmaxf(fmaxf(m1.x, m1.y), fmaxf(m1.z, m1.w)));
            const uint32_t p0 = pack_bf16(ex2(s[mt][0][2 * hi] - m), ex2(s[mt][0][2 * hi + 1] - m));
            const uint32_t p1 = pack_bf16(ex2(s[mt][1][2 * hi] - m), ex2(s[mt][1][2 * hi + 1] - m));
            pf[mt][hi] = p0; pf[mt][2 + hi] = p1;
            float l = (bf_lo(p0) + bf_hi(p0)) + (bf_lo(p1) + bf_hi(p1));
            l += __shfl_xor_sync(0xffffffffu, l, 1);
            l += __shfl_xor_sync(0xffffffffu, l, 2);
            if (t == 0) stsf(sb + SM_SUM + (8 * r + g) * 32 + w * 4, l);
        }
        sts128(sb + SM_PF + (w * 2 + 0) * 512 + lane * 16, make_uint4(pf[0][0], pf[0][1], pf[0][2], pf[0][3]));
        sts128(sb + SM_PF + (w * 2 + 1) * 512 + lane * 16, make_uint4(pf[1][0], pf[1][1], pf[1][2], pf[1][3]));
        bar_consumers();
        if (w == 0) {
            const float4 m0 = ldsf4(sb + SM_MX + lane * 32), m1 = ldsf4(sb + SM_MX + lane * 32 + 16);
            const float4 l0 = ldsf4(sb + SM_SUM + lane * 32), l1 = ldsf4(sb + SM_SUM + lane * 32 + 16);
            const float m = fmaxf(fmaxf(fmaxf(m0.x, m0.y), fmaxf(m0.z, m0.w)), fmaxf(fmaxf(m1.x, m1.y), fmaxf(m1.z, m1.w)));
            const float l = ((l0.x + l0.y) + (l0.z + l0.w)) + ((l1.x + l1.y) + (l1.z + l1.w));
            gs->stat[lane][cta] = make_float2(m, l);
        }
        float o[2][8][4];
#pragma unroll
        for (int i = 0; i < 64; i++) (&o[0][0][0])[i] = 0.f;
        const uint32_t vr = w * 1024 + (lane & 7) * 128 + (lane & 8) * 1024;
        const uint32_t vx = ((lane >> 4) ^ (lane & 7)) << 4;
#pragma unroll
        for (int ks = 0; ks < 8; ks++) {
            const uint4 p0 = lds128(sb + SM_PF + (ks * 2 + 0) * 512 + lane * 16);
            const uint4 p1 = lds128(sb + SM_PF + (ks * 2 + 1) * 512 + lane * 16);
            const uint32_t vb = sb + slot_off(IT_C + ks) + vr;
#pragma unroll
            for (int n2 = 0; n2 < 4; n2++) {
                uint32_t b0, b1, b2, b3;
                ldsm4t(vb + (vx ^ (n2 << 5)), b0, b1, b2, b3);
                mma16816(o[0][2 * n2],     p0.x, p0.y, p0.z, p0.w, b0, b1);
                mma16816(o[0][2 * n2 + 1], p0.x, p0.y, p0.z, p0.w, b2, b3);
                mma16816(o[1][2 * n2],     p1.x, p1.y, p1.z, p1.w, b0, b1);
                mma16816(o[1][2 * n2 + 1], p1.x, p1.y, p1.z, p1.w, b2, b3);
            }
            __syncwarp();
            if (lane == 0) mbar_arrive(sb + SM_EMPTY + (IT_C + ks) * 8);
        }
        mbar_wait(sb + SM_FULL + (IT_K1 + 1 + (w * 3 >> 2)) * 8);
#pragma unroll
        for (int r = 0; r < 4; r++) {
            const int mt = r >> 1, hi = (r & 1) * 2;
            uint4* dst = gs->op[(8 * r + g) * 4 + (w >> 1)] + (cta >> 6) * 1024 + (w & 1) * 512 + (cta & 63) * 8;
#pragma unroll
            for (int u = 0; u < 2; u++) {
                uint4 v;
                v.x = pack_bf16(o[mt][4 * u][hi],     o[mt][4 * u][hi + 1]);
                v.y = pack_bf16(o[mt][4 * u + 1][hi], o[mt][4 * u + 1][hi + 1]);
                v.z = pack_bf16(o[mt][4 * u + 2][hi], o[mt][4 * u + 2][hi + 1]);
                v.w = pack_bf16(o[mt][4 * u + 3][hi], o[mt][4 * u + 3][hi + 1]);
                dst[(t + 4 * u) ^ (cta & 7)] = v;
            }
        }
        asm volatile("bar.arrive 3, 288;" ::: "memory");
    }

    k_item(IT_K1 + w, sc_w + 256);
    __syncwarp();
    {
        const float4 s = ldsf4(sc_w + lane * 16);
        float m = fmaxf(fmaxf(s.x, s.y), fmaxf(s.z, s.w));
#pragma unroll
        for (int d = 1; d < 32; d <<= 1) m = fmaxf(m, __shfl_xor_sync(0xffffffffu, m, d));
        if (lane == 0) stsf(sb + SM_ML + w * 4, m);
        bar_consumers();
        const float4 m0 = ldsf4(sb + SM_ML), m1 = ldsf4(sb + SM_ML + 16);
        m = fmaxf(fmaxf(fmaxf(m0.x, m0.y), fmaxf(m0.z, m0.w)), fmaxf(fmaxf(m1.x, m1.y), fmaxf(m1.z, m1.w))) * SC;
        const uint32_t p0 = pack_bf16(ex2(fmaf(s.x, SC, -m)), ex2(fmaf(s.y, SC, -m)));
        const uint32_t p1 = pack_bf16(ex2(fmaf(s.z, SC, -m)), ex2(fmaf(s.w, SC, -m)));
        float l = (bf_lo(p0) + bf_hi(p0)) + (bf_lo(p1) + bf_hi(p1));
#pragma unroll
        for (int d = 1; d < 32; d <<= 1) l += __shfl_xor_sync(0xffffffffu, l, d);
        if (lane == 0) stsf(sb + SM_ML + 32 + w * 4, l);
        sts64(sb + SM_PA + w * 256 + lane * 8, p0, p1);
        __syncwarp();
    }

    float oa[4][4];
#pragma unroll
    for (int i = 0; i < 16; i++) (&oa[0][0])[i] = 0.f;
    auto v_item = [&](int item, uint32_t pa) {
        uint32_t p[8];
#pragma unroll
        for (int i = 0; i < 8; i++) p[i] = lds32(pa + i * 16 + t * 4);
        mbar_wait(sb + SM_FULL + item * 8);
        const uint32_t base = sb + slot_off(item) + ((lane & 7) + ((lane >> 4) << 3)) * 256 + ((lane & 8) << 4);
#pragma unroll
        for (int c = 0; c < 8; c++) {
            const uint32_t a = base + ((c ^ (lane & 7)) << 4);
            const uint32_t mask = ((c == (g ^ (2 * t))) ? 0x0000ffffu : 0u) | ((c == (g ^ (2 * t + 1))) ? 0xffff0000u : 0u);
#pragma unroll
            for (int T = 0; T < 4; T++) {
                uint32_t r0, r1, r2, r3;
                ldsm4t(a + T * 4096, r0, r1, r2, r3);
                mma16816(oa[T], r0, r1, r2, r3, p[2 * T] & mask, p[2 * T + 1] & mask);
            }
        }
        __syncwarp();
        if (lane == 0) mbar_arrive8(sb + SM_EMPTY + item * 8);
    };
    sts64(sb + SM_FIN + tid * 8, EMPTY, EMPTY);
    if (w == 0) sts32(sb + SM_CNT + lane * 4, 0u);
    v_item(IT_V0 + w, sb + SM_PA + w * 256);

    mbar_wait(sb + SM_FULL + IT_OP * 8);
    if (w < 4) {
        const float2 st = ldsf2(sb + SM_MX + tid * 8);
        float m = st.x;
#pragma unroll
        for (int d = 1; d < 32; d <<= 1) m = fmaxf(m, __shfl_xor_sync(0xffffffffu, m, d));
        const uint32_t wb = pack_bf16(ex2(st.x - m), 0.f);
        float l = bf_lo(wb) * st.y;
#pragma unroll
        for (int d = 1; d < 32; d <<= 1) l += __shfl_xor_sync(0xffffffffu, l, d);
#pragma unroll
        for (int bb = 0; bb < 4; bb++) sts16(in0 + bb * 272 + tid * 2, bb == w ? (uint16_t)wb : (uint16_t)0);
        if (lane == 0) stsf(sb + SM_ML + 64 + w * 4, 1.f / l);
    }
    bar_consumers();
    tile_mma<true>(sb, IT_OP, in0, w, lane, acc);
    if (lane < 16) {
        const float inv = ldsf(sb + SM_ML + 64 + g * 4);
        const uint32_t v0 = pack_bf16(acc[0][0] * inv, acc[0][1] * inv), v1 = pack_bf16(acc[1][0] * inv, acc[1][1] * inv);
        st_rlx2(lat_dst, (t & 1) ? v1 : v0, (t & 1) ? v0 : v1);
    }

    {
        const float4 l0 = ldsf4(sb + SM_ML + 32), l1 = ldsf4(sb + SM_ML + 48);
        const float inv = 1.f / (((l0.x + l0.y) + (l0.z + l0.w)) + ((l1.x + l1.y) + (l1.z + l1.w)));
        v_item(IT_V1 + w, sb + SM_PA + w * 256 + 128);
        const uint32_t so = sb + SM_PF + w * 512 + (16 * t + g) * 4;
        stsf(so,       (oa[0][0] + oa[1][0]) + (oa[2][0] + oa[3][0]));
        stsf(so + 32,  (oa[0][1] + oa[1][1]) + (oa[2][1] + oa[3][1]));
        stsf(so + 256, (oa[0][2] + oa[1][2]) + (oa[2][2] + oa[3][2]));
        stsf(so + 288, (oa[0][3] + oa[1][3]) + (oa[2][3] + oa[3][3]));
        if (w < 6) {
            asm volatile("bar.arrive 1, 256;" ::: "memory");
        } else {
            bar_consumers();
            float x = 0.f, y = 0.f;
#pragma unroll
            for (int i = 0; i < 8; i++) {
                const float2 v = ldsf2(sb + SM_PF + i * 512 + (tid & 63) * 8);
                x += v.x; y += v.y;
            }
            st_rlx(o_dst, pack_bf16(x * inv, y * inv));
        }
    }

    if (w < 4) {
        const uint32_t lo = (g & 3) * 1024 + (g >> 2) * 512 + (g & 1) * 64 + t * 16;
        const int wd = ((lane >> 2 & 2) + (lane >> 4)) ^ (lane >> 1 & 3);
        const uint32_t base = sb + ((lane & 6) * 4 + wd * 2 + (lane & 1)) * 64 + (((w ^ wd) & 3) << 4);
        const uint64_t dst = __shfl_sync(0xffffffffu, (unsigned long long)ctx_dst, lane);
        mbar_wait(sb + SM_FULL + BAR_LAT * 8);
        uint4 a[8];
#pragma unroll
        for (int i = 0; i < 8; i++) a[i] = lds128(sb + SM_LAT + (lo ^ (i * 64)));
        int it = 0;
        while (refetch(a, [&](int i) { return (const char*)gs->lat[h] + (lo ^ (i * 64)); }))
            if (++it > SPIN_LIMIT) __trap();
        float v0 = 0.f, v1 = 0.f;
#pragma unroll
        for (int i = 0; i < 2; i++) {
            float c[4][4];
#pragma unroll
            for (int k = 0; k < 16; k++) (&c[0][0])[k] = 0.f;
            c[0][0] = v0; c[0][1] = v1;
            mbar_wait(sb + SM_FULL + (IT_WUV + i) * 8);
#pragma unroll
            for (int kk = 0; kk < 8; kk++) {
                uint32_t r0, r1, r2, r3;
                ldsm4t(base + slot_off(IT_WUV + i) + kk * 2048, r0, r1, r2, r3);
                mma16816(c[2 * (kk & 1)],     a[kk].x, a[kk].y, a[kk].z, a[kk].w, r0, r1);
                mma16816(c[2 * (kk & 1) + 1], a[kk].x, a[kk].y, a[kk].z, a[kk].w, r2, r3);
            }
            v0 = (c[0][0] + c[1][2]) + (c[2][0] + c[3][2]);
            v1 = (c[0][1] + c[1][3]) + (c[2][1] + c[3][3]);
            if (i == 0) { v0 = __shfl_xor_sync(0xffffffffu, v0, 16); v1 = __shfl_xor_sync(0xffffffffu, v1, 16); }
        }
        st_rlx_if(dst, pack_bf16(v0, v1), lane >= 16);
    }

    {
        const bool isB = slice >= 32;
        const int r = j & 1;
        const uint32_t cs = isB ? 256 : 64;
        const uint32_t xl = (isB ? t * 64 + (((g >> 1) ^ (t & 2)) << 4) : (g >> 1) * 256 + ((g & 2) * 2 + t) * 16) + (w >> 1) * 1024 + (w & 1) * 2 * cs;
        auto xoff = [&](int i) { return (i >> 1) * 4096 + (xl ^ ((i & 1) * cs)); };
        const char* src = (const char*)gs->x[slice >> 5][r * 16];
        uint32_t off[2];
#pragma unroll
        for (int u = 0; u < 2; u++) {
            const int tt = (lane & 7) >> 1, row = 8 * tt + 2 * ((2 * u + (lane >> 4) + tt) & 3) + (lane & 1);
            off[u] = sb + w * 2048 + row * 32 + ((((lane >> 3) ^ (row >> 2)) & 1) << 4);
        }
        uint32_t fin[2], rcv[2];
#pragma unroll
        for (int e = 0; e < 2; e++) {
            const uint32_t o = t * 16 + (e ^ (t >> 1)) * 8 + g;
            fin[e] = __shfl_sync(0xffffffffu, sb + SM_FIN + (w >> 1) * 512 + o * 8 + ((w ^ t) & 1) * 4, lane);
            rcv[e] = __shfl_sync(0xffffffffu, sb + SM_RCV + o * 4, lane);
        }
        const uint32_t cnt = __shfl_sync(0xffffffffu, sb + SM_CNT + lane * 4, lane), sum = __shfl_sync(0xffffffffu, sb + SM_FIN + lane * 16, lane);
        const uint32_t inc = __shfl_sync(0xffffffffu, lane, 1 + r), last = __shfl_sync(0xffffffffu, lane, 7 + 7 * r);
        const uint32_t snd = __shfl_sync(0xffffffffu, map_cta(sb + SM_RCV + lane * 8, 0), lane),
                       sbar = __shfl_sync(0xffffffffu, map_cta(sb + SM_LAST + 8 + (lane & 16), 0), lane & 15);
        const uint64_t dst = __shfl_sync(0xffffffffu, (unsigned long long)(out + (lane >> 3) * 1024 + slice * 16 + ((lane ^ (lane >> 2 & 4)) & 7) * 2), lane);
        uint32_t a[2][4][4];
        uint4 x[8];
        float c[4][4];
        auto load_w = [&](int i) {
            mbar_wait(i < 2 ? sb + SM_FULL + (IT_WO + i) * 8 : sb + SM_LAST + w * 16 + (i & 1) * 8);
#pragma unroll
            for (int q = 0; q < 4; q++)
                ldsm4t(slot_off(IT_WO + i) + off[q & 1] + (q >> 1) * 1024, a[i & 1][q][0], a[i & 1][q][1], a[i & 1][q][2], a[i & 1][q][3]);
        };
        auto mma_w = [&](int i) {
#pragma unroll
            for (int q = 0; q < 4; q++) {
                const uint4& b = x[2 * i + (q >> 1)];
                if (i == 0) c[q][0] = c[q][1] = c[q][2] = c[q][3] = 0.f;
                mma16816(c[q], a[i & 1][q][0], a[i & 1][q][1], a[i & 1][q][2], a[i & 1][q][3], (q & 1) ? b.z : b.x, (q & 1) ? b.w : b.y);
            }
        };
        load_w(0); load_w(1);
        mbar_wait(sb + SM_FULL + IT_X * 8);
#pragma unroll
        for (int i = 0; i < 8; i++) x[i] = lds128(sb + slot_off(IT_X) + xoff(i));
        int it = 0;
        while (true) {
            mma_w(0); mma_w(1);
            if (!refetch(x, [&](int i) { return src + xoff(i); })) break;
            if (++it > SPIN_LIMIT) __trap();
        }
        load_w(2);
        mma_w(2);
        load_w(3);
        uint32_t rank;
        const float pr[2] = {ldsf_if(rcv[0], w == 0 && r == 0), ldsf_if(rcv[1], w == 0 && r == 0)};
        mma_w(3);
#pragma unroll
        for (int e = 0; e < 2; e++) stv(fin[e], (((c[0][2 * e] + pr[e]) + c[1][2 * e]) + c[2][2 * e]) + c[3][2 * e]);
        float4 p[4];
        float s0, s1;
        auto add_up = [&]() {
#pragma unroll
            for (int k = 0; k < 4; k++) p[k] = ldv4(sum + k * 512);
            const float a0 = ((p[0].x + p[0].y) + (p[1].x + p[1].y)) + (p[2].x + p[2].y), b0 = p[3].x + p[3].y;
            const float a1 = ((p[0].z + p[0].w) + (p[1].z + p[1].w)) + (p[2].z + p[2].w), b1 = p[3].z + p[3].w;
            s0 = a0 + b0; s1 = a1 + b1;
            uint32_t nan;
            asm("{\n.reg .pred p;\nsetp.ne.u32 p, %5, 0;\nsetp.nan.or.f32 p, %1, %2, p;\nsetp.nan.or.f32 p, %3, %4, p;\nselp.u32 %0, 1, 0, p;\n}"
                : "=r"(nan) : "f"(a0), "f"(a1), "f"(b0), "f"(b1), "r"(r));
            return nan;
        };
        asm volatile("atom.relaxed.cta.shared.add.u32 %0, [%1], %2;" : "=r"(rank) : "r"(cnt), "r"(inc) : "memory");
        const uint32_t redo = add_up();
        st_if(dst, pack_bf16(s0, s1), rank == 7);
        if (!redo) return;
        const bool num = s0 == s0 && s1 == s1;
        st_async64_if(snd, s0, s1, sbar, rank == 14 && num);
        if (rank != last || num) return;
        auto mx = [](float4 q) { return max(max(__float_as_uint(q.x), __float_as_uint(q.y)), max(__float_as_uint(q.z), __float_as_uint(q.w))); };
        for (it = 0; max(max(mx(p[0]), mx(p[1])), max(mx(p[2]), mx(p[3]))) == EMPTY; it++) {
            add_up();
            if (it > SPIN_LIMIT) __trap();
        }
        if (r) st_async64_if(snd, s0, s1, sbar, true);
        else st_if(dst, pack_bf16(s0, s1), true);
    }
}

typedef CUresult (*EncodeTiledFn)(CUtensorMap*, CUtensorMapDataType, cuuint32_t, void*, const cuuint64_t*,
                                  const cuuint64_t*, const cuuint32_t*, const cuuint32_t*, CUtensorMapInterleave,
                                  CUtensorMapSwizzle, CUtensorMapL2promotion, CUtensorMapFloatOOBfill);

void encode_map(EncodeTiledFn enc, CUtensorMap* tm, const void* p, cuuint64_t cols, cuuint64_t rows,
                cuuint32_t brows, cuuint32_t bblk) {
    cuuint64_t dims[3] = {64, rows, cols / 64};
    cuuint64_t strides[2] = {cols * 2, 128};
    cuuint32_t box[3] = {64, brows, bblk};
    cuuint32_t es[3] = {1, 1, 1};
    enc(tm, CU_TENSOR_MAP_DATA_TYPE_BFLOAT16, 3, const_cast<void*>(p), dims, strides, box, es,
        CU_TENSOR_MAP_INTERLEAVE_NONE, CU_TENSOR_MAP_SWIZZLE_128B, CU_TENSOR_MAP_L2_PROMOTION_L2_256B,
        CU_TENSOR_MAP_FLOAT_OOB_FILL_NONE);
}

void encode_slice_map(EncodeTiledFn enc, CUtensorMap* tm, const void* p, cuuint64_t cols, cuuint64_t rows,
                      cuuint32_t bcols, cuuint32_t brows) {
    cuuint64_t dims[3] = {cols, 256, rows / 256};
    cuuint64_t strides[2] = {cols * 2, cols * 512};
    cuuint32_t box[3] = {bcols, brows, 1};
    cuuint32_t es[3] = {1, 1, 1};
    enc(tm, CU_TENSOR_MAP_DATA_TYPE_BFLOAT16, 3, const_cast<void*>(p), dims, strides, box, es, CU_TENSOR_MAP_INTERLEAVE_NONE,
        bcols == 16 ? CU_TENSOR_MAP_SWIZZLE_32B : CU_TENSOR_MAP_SWIZZLE_64B, CU_TENSOR_MAP_L2_PROMOTION_L2_128B,
        CU_TENSOR_MAP_FLOAT_OOB_FILL_NONE);
}

}

extern "C" void kernel_launch(void* const* d_in, const int* in_sizes, int n_in, void* d_out, int out_size) {
    (void)in_sizes; (void)n_in; (void)out_size;
    static EncodeTiledFn enc = nullptr;
    static Scratch* gs = nullptr;
    if (!enc) {
        cudaGetSymbolAddress((void**)&gs, g_scratch);
        void* fn = nullptr;
        cudaDriverEntryPointQueryResult qr;
        cudaGetDriverEntryPoint("cuTensorMapEncodeTiled", &fn, cudaEnableDefault, &qr);
        enc = (EncodeTiledFn)fn;
        cudaFuncSetAttribute(fused_decode_kernel, cudaFuncAttributeMaxDynamicSharedMemorySize, SM_END);
    }
    Maps maps;
    encode_map(enc, &maps.wuk, d_in[8], 4096, 512, 32, 2);
    encode_slice_map(enc, &maps.wuv, d_in[9], 4096, 512, 32, 128);
    encode_slice_map(enc, &maps.woB, d_in[10], 512, 4096, 16, 256);
    encode_slice_map(enc, &maps.woA, d_in[4], 512, 4096, 16, 256);
    encode_slice_map(enc, &maps.endB, d_in[10], 512, 4096, 16, 64);
    encode_slice_map(enc, &maps.endA, d_in[4], 512, 4096, 16, 64);
    encode_map(enc, &maps.ckv, d_in[6], 512, 16384, 8, 8);
    uint64_t first = (uint64_t)d_in[7];
    if ((uint32_t)first >= 0xffe00000u) first += 1 << 21;
    fused_decode_kernel<<<NCTA, NTHR, SM_END>>>(make_uint2((uint32_t)first, (uint32_t)(first >> 32)),
                                                (const __nv_bfloat16*)d_in[0], (const __nv_bfloat16*)d_in[5],
                                                (const __nv_bfloat16*)d_in[7], (const __nv_bfloat16*)d_in[3],
                                                (const __nv_bfloat16*)d_in[1] + 3072 * 128, (const __nv_bfloat16*)d_in[2] + 3072 * 128,
                                                (__nv_bfloat16*)d_out, gs, maps);
}
```
